```python
import torch

def _softmax(x, axis=-1):
    return torch.softmax(x, dim=axis)
def _gelu(x):
    return torch.nn.functional.gelu(x, approximate="tanh")
def _silu(x):
    return torch.nn.functional.silu(x)
def _sigmoid(x):
    return torch.sigmoid(x)
def _layernorm(x, axis=-1, eps=1e-5):
    m = x.mean(dim=axis, keepdim=True)
    v = x.var(dim=axis, keepdim=True, unbiased=False)
    return (x - m) / torch.sqrt(v + eps)
def _scatter_add(tgt, idx, src, axis=0):
    return tgt.clone().index_add_(axis, idx, src)
def _segment_sum(src, seg, n):
    out = torch.zeros((n,) + src.shape[1:], dtype=src.dtype)
    return out.index_add_(0, seg, src)
def _pad(x, pw):
    flat = tuple(v for pair in reversed(pw) for v in pair)
    return torch.nn.functional.pad(x, flat)

kernel_name = 'sequential_preLN__mha_block__mixer_token_mlp__prompt'

def setup_inputs():

    _w = (lambda a: (lambda t: t.to(torch.bfloat16) if t.is_floating_point() else t)(torch.as_tensor(a)))
    def _A_setup():
        B, S, D, H = 1, 2048, 1024, 32
        return {
            "x": _w((lambda *s: torch.randn(*s, dtype=torch.bfloat16) * 0.05)(B, S, D)),
            "wqkv": _w((lambda *s: torch.randn(*s, dtype=torch.bfloat16) * 0.05)(D, 3 * D)),
            "wo": _w((lambda *s: torch.randn(*s, dtype=torch.bfloat16) * 0.05)(D, D)),
        }
    _A_in = _A_setup()

    def _B_setup():
        B, S, D, F = 1, 2048, 1024, 3584
        return {
            "x": _w((lambda *s: torch.randn(*s, dtype=torch.bfloat16) * 0.05)(B, S, D)),
            "w1": _w((lambda *s: torch.randn(*s, dtype=torch.bfloat16) * 3.2)(S, F) * (S ** -0.5)),
            "b1": _w((lambda *s: torch.randn(*s, dtype=torch.bfloat16) * 3.2)(F) * 0.02),
            "w2": _w((lambda *s: torch.randn(*s, dtype=torch.bfloat16) * 0.4)(F, S) * (F ** -0.5)),
            "b2": _w((lambda *s: torch.randn(*s, dtype=torch.bfloat16) * 0.4)(S) * 0.02),
        }
    _B_in = _B_setup()

    return {
        "A_x": _A_in["x"],
        "A_wqkv": _A_in["wqkv"],
        "A_wo": _A_in["wo"],
        "B_x": _B_in["x"],
        "B_w1": _B_in["w1"],
        "B_b1": _B_in["b1"],
        "B_w2": _B_in["w2"],
        "B_b2": _B_in["b2"],
    }

def reference(A_x, A_wqkv, A_wo, B_x, B_w1, B_b1, B_w2, B_b2):
    def _A_ref(x, wqkv, wo):
        B, S, D = x.shape
        H = 32
        Dh = D // H
        qkv = (lambda x, *d: x.permute(*d))((x @ wqkv).reshape(B, S, 3, H, Dh), 2, 0, 3, 1, 4)
        q, k, v = qkv[0], qkv[1], qkv[2]
        scores = torch.einsum("bhqd,bhkd->bhqk", q, k) * (Dh ** -0.5)
        p = _softmax(scores, axis=-1)
        o = torch.einsum("bhqk,bhkd->bhqd", p, v)
        return (lambda x, *d: x.permute(*d))(o, 0, 2, 1, 3).reshape(B, S, D) @ wo

    def _B_ref(x, w1, b1, w2, b2):
        B, S, D = x.shape
        h = _layernorm(x, axis=-1)
        u = torch.einsum("bsd,sf->bdf", h, w1) + b1
        u = _gelu(u)
        y = torch.einsum("bdf,fs->bds", u, w2) + b2
        return (lambda x, *d: x.permute(*d))(y, 0, 2, 1)

    x = A_x
    h = x + _A_ref(_layernorm(x, axis=-1), A_wqkv, A_wo)
    h2 = h + _B_ref(_layernorm(h, axis=-1), B_w1, B_b1, B_w2, B_b2)
    return h2
```

```cpp
#include <cuda_runtime.h>
#include <cuda_bf16.h>
#include <cuda.h>
#include <stdint.h>
#include <stdio.h>

typedef __nv_bfloat16 bf16;

namespace {

#define POLY_MASK 0x00
constexpr int SEQ = 2048, DM = 1024, NH = 32, HD = 32, FF = 3584;

__device__ __align__(1024) bf16 g_xn[SEQ * DM];
__device__ __align__(1024) bf16 g_qkv[3 * NH * SEQ * HD];
__device__ __align__(1024) bf16 g_o[SEQ * DM];
__device__ __align__(1024) bf16 g_h[SEQ * DM];
__device__ __align__(1024) bf16 g_hn[SEQ * DM];
__device__ __align__(1024) bf16 g_u[DM * FF];
__device__ uint32_t g_norm[3 * NH];

#define TL(kern, slot)

__device__ __forceinline__ uint32_t smem_u32(const void* p) { return (uint32_t)__cvta_generic_to_shared(p); }
__device__ __forceinline__ void mbar_init(uint32_t bar, uint32_t cnt) { asm volatile("mbarrier.init.shared::cta.b64 [%0], %1;" :: "r"(bar), "r"(cnt) : "memory"); }
__device__ __forceinline__ void mbar_expect_tx(uint32_t bar, uint32_t bytes) { asm volatile("mbarrier.arrive.expect_tx.shared::cta.b64 _, [%0], %1;" :: "r"(bar), "r"(bytes) : "memory"); }
__device__ __forceinline__ void mbar_arrive(uint32_t bar) { asm volatile("mbarrier.arrive.shared::cta.b64 _, [%0];" :: "r"(bar) : "memory"); }
__device__ __forceinline__ void mbar_wait(uint32_t bar, uint32_t parity) {
    asm volatile("{\n.reg .pred p;\nWAIT_%=:\nmbarrier.try_wait.parity.shared::cta.b64 p, [%0], %1;\n@p bra DONE_%=;\nbra WAIT_%=;\nDONE_%=:\n}" :: "r"(bar), "r"(parity) : "memory");
}
__device__ __forceinline__ void fence_barrier_init() { asm volatile("fence.mbarrier_init.release.cluster;" ::: "memory"); }
__device__ __forceinline__ void fence_proxy_async() { asm volatile("fence.proxy.async.shared::cta;" ::: "memory"); }
__device__ __forceinline__ void pdl_launch() { asm volatile("griddepcontrol.launch_dependents;" ::: "memory"); }
__device__ __forceinline__ void pdl_wait() { asm volatile("griddepcontrol.wait;" ::: "memory"); }
__device__ __forceinline__ void named_bar(int id, int n) { asm volatile("bar.sync %0, %1;" :: "r"(id), "r"(n) : "memory"); }
__device__ __forceinline__ void prefetch_map(const CUtensorMap* m) { asm volatile("prefetch.tensormap [%0];" :: "l"(m) : "memory"); }

__device__ __forceinline__ void tma_ld2(uint32_t dst, const CUtensorMap* m, uint32_t bar, int c0, int c1) {
    asm volatile("cp.async.bulk.tensor.2d.shared::cluster.global.mbarrier::complete_tx::bytes [%0], [%1, {%3, %4}], [%2];"
                 :: "r"(dst), "l"(m), "r"(bar), "r"(c0), "r"(c1) : "memory");
}
__device__ __forceinline__ void tma_ld3(uint32_t dst, const CUtensorMap* m, uint32_t bar, int c0, int c1, int c2) {
    asm volatile("cp.async.bulk.tensor.3d.shared::cluster.global.mbarrier::complete_tx::bytes [%0], [%1, {%3, %4, %5}], [%2];"
                 :: "r"(dst), "l"(m), "r"(bar), "r"(c0), "r"(c1), "r"(c2) : "memory");
}
__device__ __forceinline__ void tma_ld4(uint32_t dst, const CUtensorMap* m, uint32_t bar, int c0, int c1, int c2, int c3) {
    asm volatile("cp.async.bulk.tensor.4d.shared::cluster.global.mbarrier::complete_tx::bytes [%0], [%1, {%3, %4, %5, %6}], [%2];"
                 :: "r"(dst), "l"(m), "r"(bar), "r"(c0), "r"(c1), "r"(c2), "r"(c3) : "memory");
}
__device__ __forceinline__ void tma_st2(const CUtensorMap* m, uint32_t src, int c0, int c1) {
    asm volatile("cp.async.bulk.tensor.2d.global.shared::cta.bulk_group [%0, {%2, %3}], [%1];" :: "l"(m), "r"(src), "r"(c0), "r"(c1) : "memory");
}
__device__ __forceinline__ void tma_st3(const CUtensorMap* m, uint32_t src, int c0, int c1, int c2) {
    asm volatile("cp.async.bulk.tensor.3d.global.shared::cta.bulk_group [%0, {%2, %3, %4}], [%1];" :: "l"(m), "r"(src), "r"(c0), "r"(c1), "r"(c2) : "memory");
}
__device__ __forceinline__ void tma_st_commit() { asm volatile("cp.async.bulk.commit_group;" ::: "memory"); }
__device__ __forceinline__ void tma_st_wait() { asm volatile("cp.async.bulk.wait_group.read 0;" ::: "memory"); }

__device__ __forceinline__ void wg_fence() { asm volatile("wgmma.fence.sync.aligned;" ::: "memory"); }
__device__ __forceinline__ void wg_commit() { asm volatile("wgmma.commit_group.sync.aligned;" ::: "memory"); }
template <int N> __device__ __forceinline__ void wg_wait() { asm volatile("wgmma.wait_group.sync.aligned %0;" :: "n"(N) : "memory"); }
template <int R> __device__ __forceinline__ void reg_alloc() { asm volatile("setmaxnreg.inc.sync.aligned.u32 %0;" :: "n"(R)); }
template <int R> __device__ __forceinline__ void reg_dealloc() { asm volatile("setmaxnreg.dec.sync.aligned.u32 %0;" :: "n"(R)); }
template <int N> __device__ __forceinline__ void fence_regs(float (&d)[N]) {
#pragma unroll
    for (int i = 0; i < N; i++) asm volatile("" : "+f"(d[i]) :: "memory");
}

__device__ __forceinline__ uint64_t make_desc(uint32_t addr, uint32_t lbo, uint32_t sbo, uint32_t swz) {
    return (uint64_t)((addr & 0x3FFFF) >> 4) | ((uint64_t)(lbo >> 4) << 16) | ((uint64_t)(sbo >> 4) << 32) | ((uint64_t)swz << 62);
}
__device__ __forceinline__ uint32_t pack_bf16(float lo, float hi) { uint32_t d; asm("cvt.rn.bf16x2.f32 %0, %1, %2;" : "=r"(d) : "f"(hi), "f"(lo)); return d; }
__device__ __forceinline__ float bf_lo(uint32_t v) { return __uint_as_float(v << 16); }
__device__ __forceinline__ float bf_hi(uint32_t v) { return __uint_as_float(v & 0xFFFF0000u); }
__device__ __forceinline__ void stmatrix_x4(uint32_t addr, uint32_t r0, uint32_t r1, uint32_t r2, uint32_t r3) {
    asm volatile("stmatrix.sync.aligned.m8n8.x4.shared.b16 [%0], {%1, %2, %3, %4};" :: "r"(addr), "r"(r0), "r"(r1), "r"(r2), "r"(r3) : "memory");
}
__device__ __forceinline__ float ex2(float x) { float y; asm("ex2.approx.ftz.f32 %0, %1;" : "=f"(y) : "f"(x)); return y; }
__device__ __forceinline__ float tanh_fast(float x) { float y; asm("tanh.approx.f32 %0, %1;" : "=f"(y) : "f"(x)); return y; }

__device__ __forceinline__ void wgmma_ss_n192_t01(float (&d)[96], uint64_t da, uint64_t db, int scale_d) {
    asm volatile("{\n.reg .pred p;\nsetp.ne.b32 p, %98, 0;\n"
        "wgmma.mma_async.sync.aligned.m64n192k16.f32.bf16.bf16 {"
        "%0, %1, %2, %3, %4, %5, %6, %7, %8, %9, %10, %11, %12, %13, %14, %15, %16, %17, %18, %19, %20, %21, %22, %23, %24, %25, %26, %27, %28, %29, %30, %31,  "
        "%32, %33, %34, %35, %36, %37, %38, %39, %40, %41, %42, %43, %44, %45, %46, %47, %48, %49, %50, %51, %52, %53, %54, %55, %56, %57, %58, %59, %60, %61,  "
        "%62, %63, %64, %65, %66, %67, %68, %69, %70, %71, %72, %73, %74, %75, %76, %77, %78, %79, %80, %81, %82, %83, %84, %85, %86, %87, %88, %89, %90, %91,  "
        "%92, %93, %94, %95 "
        "}, %96, %97, p, 1, 1, 0, 1;\n}\n"
        : "+f"(d[0]), "+f"(d[1]), "+f"(d[2]), "+f"(d[3]), "+f"(d[4]), "+f"(d[5]), "+f"(d[6]), "+f"(d[7]), "+f"(d[8]), "+f"(d[9]), "+f"(d[10]), "+f"(d[11]),
          "+f"(d[12]), "+f"(d[13]), "+f"(d[14]), "+f"(d[15]), "+f"(d[16]), "+f"(d[17]), "+f"(d[18]), "+f"(d[19]), "+f"(d[20]), "+f"(d[21]), "+f"(d[22]),
          "+f"(d[23]), "+f"(d[24]), "+f"(d[25]), "+f"(d[26]), "+f"(d[27]), "+f"(d[28]), "+f"(d[29]), "+f"(d[30]), "+f"(d[31]), "+f"(d[32]), "+f"(d[33]),
          "+f"(d[34]), "+f"(d[35]), "+f"(d[36]), "+f"(d[37]), "+f"(d[38]), "+f"(d[39]), "+f"(d[40]), "+f"(d[41]), "+f"(d[42]), "+f"(d[43]), "+f"(d[44]),
          "+f"(d[45]), "+f"(d[46]), "+f"(d[47]), "+f"(d[48]), "+f"(d[49]), "+f"(d[50]), "+f"(d[51]), "+f"(d[52]), "+f"(d[53]), "+f"(d[54]), "+f"(d[55]),
          "+f"(d[56]), "+f"(d[57]), "+f"(d[58]), "+f"(d[59]), "+f"(d[60]), "+f"(d[61]), "+f"(d[62]), "+f"(d[63]), "+f"(d[64]), "+f"(d[65]), "+f"(d[66]),
          "+f"(d[67]), "+f"(d[68]), "+f"(d[69]), "+f"(d[70]), "+f"(d[71]), "+f"(d[72]), "+f"(d[73]), "+f"(d[74]), "+f"(d[75]), "+f"(d[76]), "+f"(d[77]),
          "+f"(d[78]), "+f"(d[79]), "+f"(d[80]), "+f"(d[81]), "+f"(d[82]), "+f"(d[83]), "+f"(d[84]), "+f"(d[85]), "+f"(d[86]), "+f"(d[87]), "+f"(d[88]),
          "+f"(d[89]), "+f"(d[90]), "+f"(d[91]), "+f"(d[92]), "+f"(d[93]), "+f"(d[94]), "+f"(d[95])
        : "l"(da), "l"(db), "r"(scale_d));
}
__device__ __forceinline__ void wgmma_ss_n128_t01(float (&d)[64], uint64_t da, uint64_t db, int scale_d) {
    asm volatile("{\n.reg .pred p;\nsetp.ne.b32 p, %66, 0;\n"
        "wgmma.mma_async.sync.aligned.m64n128k16.f32.bf16.bf16 {"
        "%0, %1, %2, %3, %4, %5, %6, %7, %8, %9, %10, %11, %12, %13, %14, %15, %16, %17, %18, %19, %20, %21, %22, %23, %24, %25, %26, %27, %28, %29, %30, %31,  "
        "%32, %33, %34, %35, %36, %37, %38, %39, %40, %41, %42, %43, %44, %45, %46, %47, %48, %49, %50, %51, %52, %53, %54, %55, %56, %57, %58, %59, %60, %61,  "
        "%62, %63 "
        "}, %64, %65, p, 1, 1, 0, 1;\n}\n"
        : "+f"(d[0]), "+f"(d[1]), "+f"(d[2]), "+f"(d[3]), "+f"(d[4]), "+f"(d[5]), "+f"(d[6]), "+f"(d[7]), "+f"(d[8]), "+f"(d[9]), "+f"(d[10]), "+f"(d[11]),
          "+f"(d[12]), "+f"(d[13]), "+f"(d[14]), "+f"(d[15]), "+f"(d[16]), "+f"(d[17]), "+f"(d[18]), "+f"(d[19]), "+f"(d[20]), "+f"(d[21]), "+f"(d[22]),
          "+f"(d[23]), "+f"(d[24]), "+f"(d[25]), "+f"(d[26]), "+f"(d[27]), "+f"(d[28]), "+f"(d[29]), "+f"(d[30]), "+f"(d[31]), "+f"(d[32]), "+f"(d[33]),
          "+f"(d[34]), "+f"(d[35]), "+f"(d[36]), "+f"(d[37]), "+f"(d[38]), "+f"(d[39]), "+f"(d[40]), "+f"(d[41]), "+f"(d[42]), "+f"(d[43]), "+f"(d[44]),
          "+f"(d[45]), "+f"(d[46]), "+f"(d[47]), "+f"(d[48]), "+f"(d[49]), "+f"(d[50]), "+f"(d[51]), "+f"(d[52]), "+f"(d[53]), "+f"(d[54]), "+f"(d[55]),
          "+f"(d[56]), "+f"(d[57]), "+f"(d[58]), "+f"(d[59]), "+f"(d[60]), "+f"(d[61]), "+f"(d[62]), "+f"(d[63])
        : "l"(da), "l"(db), "r"(scale_d));
}
__device__ __forceinline__ void wgmma_ss_n128_t10(float (&d)[64], uint64_t da, uint64_t db, int scale_d) {
    asm volatile("{\n.reg .pred p;\nsetp.ne.b32 p, %66, 0;\n"
        "wgmma.mma_async.sync.aligned.m64n128k16.f32.bf16.bf16 {"
        "%0, %1, %2, %3, %4, %5, %6, %7, %8, %9, %10, %11, %12, %13, %14, %15, %16, %17, %18, %19, %20, %21, %22, %23, %24, %25, %26, %27, %28, %29, %30, %31,  "
        "%32, %33, %34, %35, %36, %37, %38, %39, %40, %41, %42, %43, %44, %45, %46, %47, %48, %49, %50, %51, %52, %53, %54, %55, %56, %57, %58, %59, %60, %61,  "
        "%62, %63 "
        "}, %64, %65, p, 1, 1, 1, 0;\n}\n"
        : "+f"(d[0]), "+f"(d[1]), "+f"(d[2]), "+f"(d[3]), "+f"(d[4]), "+f"(d[5]), "+f"(d[6]), "+f"(d[7]), "+f"(d[8]), "+f"(d[9]), "+f"(d[10]), "+f"(d[11]),
          "+f"(d[12]), "+f"(d[13]), "+f"(d[14]), "+f"(d[15]), "+f"(d[16]), "+f"(d[17]), "+f"(d[18]), "+f"(d[19]), "+f"(d[20]), "+f"(d[21]), "+f"(d[22]),
          "+f"(d[23]), "+f"(d[24]), "+f"(d[25]), "+f"(d[26]), "+f"(d[27]), "+f"(d[28]), "+f"(d[29]), "+f"(d[30]), "+f"(d[31]), "+f"(d[32]), "+f"(d[33]),
          "+f"(d[34]), "+f"(d[35]), "+f"(d[36]), "+f"(d[37]), "+f"(d[38]), "+f"(d[39]), "+f"(d[40]), "+f"(d[41]), "+f"(d[42]), "+f"(d[43]), "+f"(d[44]),
          "+f"(d[45]), "+f"(d[46]), "+f"(d[47]), "+f"(d[48]), "+f"(d[49]), "+f"(d[50]), "+f"(d[51]), "+f"(d[52]), "+f"(d[53]), "+f"(d[54]), "+f"(d[55]),
          "+f"(d[56]), "+f"(d[57]), "+f"(d[58]), "+f"(d[59]), "+f"(d[60]), "+f"(d[61]), "+f"(d[62]), "+f"(d[63])
        : "l"(da), "l"(db), "r"(scale_d));
}
__device__ __forceinline__ void wgmma_ss_n224_t11(float (&d)[112], uint64_t da, uint64_t db, int scale_d) {
    asm volatile("{\n.reg .pred p;\nsetp.ne.b32 p, %114, 0;\n"
        "wgmma.mma_async.sync.aligned.m64n224k16.f32.bf16.bf16 {"
        "%0, %1, %2, %3, %4, %5, %6, %7, %8, %9, %10, %11, %12, %13, %14, %15, %16, %17, %18, %19, %20, %21, %22, %23, %24, %25, %26, %27, %28, %29, %30, %31,  "
        "%32, %33, %34, %35, %36, %37, %38, %39, %40, %41, %42, %43, %44, %45, %46, %47, %48, %49, %50, %51, %52, %53, %54, %55, %56, %57, %58, %59, %60, %61,  "
        "%62, %63, %64, %65, %66, %67, %68, %69, %70, %71, %72, %73, %74, %75, %76, %77, %78, %79, %80, %81, %82, %83, %84, %85, %86, %87, %88, %89, %90, %91,  "
        "%92, %93, %94, %95, %96, %97, %98, %99, %100, %101, %102, %103, %104, %105, %106, %107, %108, %109, %110, %111 "
        "}, %112, %113, p, 1, 1, 1, 1;\n}\n"
        : "+f"(d[0]), "+f"(d[1]), "+f"(d[2]), "+f"(d[3]), "+f"(d[4]), "+f"(d[5]), "+f"(d[6]), "+f"(d[7]), "+f"(d[8]), "+f"(d[9]), "+f"(d[10]), "+f"(d[11]),
          "+f"(d[12]), "+f"(d[13]), "+f"(d[14]), "+f"(d[15]), "+f"(d[16]), "+f"(d[17]), "+f"(d[18]), "+f"(d[19]), "+f"(d[20]), "+f"(d[21]), "+f"(d[22]),
          "+f"(d[23]), "+f"(d[24]), "+f"(d[25]), "+f"(d[26]), "+f"(d[27]), "+f"(d[28]), "+f"(d[29]), "+f"(d[30]), "+f"(d[31]), "+f"(d[32]), "+f"(d[33]),
          "+f"(d[34]), "+f"(d[35]), "+f"(d[36]), "+f"(d[37]), "+f"(d[38]), "+f"(d[39]), "+f"(d[40]), "+f"(d[41]), "+f"(d[42]), "+f"(d[43]), "+f"(d[44]),
          "+f"(d[45]), "+f"(d[46]), "+f"(d[47]), "+f"(d[48]), "+f"(d[49]), "+f"(d[50]), "+f"(d[51]), "+f"(d[52]), "+f"(d[53]), "+f"(d[54]), "+f"(d[55]),
          "+f"(d[56]), "+f"(d[57]), "+f"(d[58]), "+f"(d[59]), "+f"(d[60]), "+f"(d[61]), "+f"(d[62]), "+f"(d[63]), "+f"(d[64]), "+f"(d[65]), "+f"(d[66]),
          "+f"(d[67]), "+f"(d[68]), "+f"(d[69]), "+f"(d[70]), "+f"(d[71]), "+f"(d[72]), "+f"(d[73]), "+f"(d[74]), "+f"(d[75]), "+f"(d[76]), "+f"(d[77]),
          "+f"(d[78]), "+f"(d[79]), "+f"(d[80]), "+f"(d[81]), "+f"(d[82]), "+f"(d[83]), "+f"(d[84]), "+f"(d[85]), "+f"(d[86]), "+f"(d[87]), "+f"(d[88]),
          "+f"(d[89]), "+f"(d[90]), "+f"(d[91]), "+f"(d[92]), "+f"(d[93]), "+f"(d[94]), "+f"(d[95]), "+f"(d[96]), "+f"(d[97]), "+f"(d[98]), "+f"(d[99]),
          "+f"(d[100]), "+f"(d[101]), "+f"(d[102]), "+f"(d[103]), "+f"(d[104]), "+f"(d[105]), "+f"(d[106]), "+f"(d[107]), "+f"(d[108]), "+f"(d[109]),
          "+f"(d[110]), "+f"(d[111])
        : "l"(da), "l"(db), "r"(scale_d));
}
__device__ __forceinline__ void wgmma_rs_n64_t0(float (&d)[32], uint32_t a0, uint32_t a1, uint32_t a2, uint32_t a3, uint64_t db, int scale_d) {
    asm volatile("{\n.reg .pred p;\nsetp.ne.b32 p, %37, 0;\n"
        "wgmma.mma_async.sync.aligned.m64n64k16.f32.bf16.bf16 {"
        "%0, %1, %2, %3, %4, %5, %6, %7, %8, %9, %10, %11, %12, %13, %14, %15, %16, %17, %18, %19, %20, %21, %22, %23, %24, %25, %26, %27, %28, %29, %30, %31 "
        "}, {%32, %33, %34, %35}, %36, p, 1, 1, 0;\n}\n"
        : "+f"(d[0]), "+f"(d[1]), "+f"(d[2]), "+f"(d[3]), "+f"(d[4]), "+f"(d[5]), "+f"(d[6]), "+f"(d[7]), "+f"(d[8]), "+f"(d[9]), "+f"(d[10]), "+f"(d[11]),
          "+f"(d[12]), "+f"(d[13]), "+f"(d[14]), "+f"(d[15]), "+f"(d[16]), "+f"(d[17]), "+f"(d[18]), "+f"(d[19]), "+f"(d[20]), "+f"(d[21]), "+f"(d[22]),
          "+f"(d[23]), "+f"(d[24]), "+f"(d[25]), "+f"(d[26]), "+f"(d[27]), "+f"(d[28]), "+f"(d[29]), "+f"(d[30]), "+f"(d[31])
        : "r"(a0), "r"(a1), "r"(a2), "r"(a3), "l"(db), "r"(scale_d));
}
__device__ __forceinline__ void wgmma_rs_n40_t1(float (&d)[20], uint32_t a0, uint32_t a1, uint32_t a2, uint32_t a3, uint64_t db, int scale_d) {
    asm volatile("{\n.reg .pred p;\nsetp.ne.b32 p, %25, 0;\n"
        "wgmma.mma_async.sync.aligned.m64n40k16.f32.bf16.bf16 {"
        "%0, %1, %2, %3, %4, %5, %6, %7, %8, %9, %10, %11, %12, %13, %14, %15, %16, %17, %18, %19 "
        "}, {%20, %21, %22, %23}, %24, p, 1, 1, 1;\n}\n"
        : "+f"(d[0]), "+f"(d[1]), "+f"(d[2]), "+f"(d[3]), "+f"(d[4]), "+f"(d[5]), "+f"(d[6]), "+f"(d[7]), "+f"(d[8]), "+f"(d[9]), "+f"(d[10]), "+f"(d[11]),
          "+f"(d[12]), "+f"(d[13]), "+f"(d[14]), "+f"(d[15]), "+f"(d[16]), "+f"(d[17]), "+f"(d[18]), "+f"(d[19])
        : "r"(a0), "r"(a1), "r"(a2), "r"(a3), "l"(db), "r"(scale_d));
}

__device__ __forceinline__ float warp_sum(float v) {
#pragma unroll
    for (int o = 16; o > 0; o >>= 1) v += __shfl_xor_sync(0xffffffffu, v, o);
    return v;
}
template <bool TWICE>
__global__ void __launch_bounds__(256) ln_kernel(const bf16* __restrict__ in, bf16* __restrict__ out) {
    pdl_launch();
    if (TWICE) pdl_wait();
    if (!TWICE && blockIdx.x == 0 && threadIdx.x < 3 * NH) g_norm[threadIdx.x] = 0u;
    TL(TWICE ? 4 : 0, 0);
    const int row = blockIdx.x * 8 + (threadIdx.x >> 5), lane = threadIdx.x & 31;
    const uint4* src = reinterpret_cast<const uint4*>(in + (size_t)row * DM);
    uint4 v[4];
#pragma unroll
    for (int i = 0; i < 4; i++) v[i] = src[lane + 32 * i];
    float f[32];
#pragma unroll
    for (int i = 0; i < 4; i++) {
        f[8 * i + 0] = bf_lo(v[i].x); f[8 * i + 1] = bf_hi(v[i].x); f[8 * i + 2] = bf_lo(v[i].y); f[8 * i + 3] = bf_hi(v[i].y);
        f[8 * i + 4] = bf_lo(v[i].z); f[8 * i + 5] = bf_hi(v[i].z); f[8 * i + 6] = bf_lo(v[i].w); f[8 * i + 7] = bf_hi(v[i].w);
    }
#pragma unroll
    for (int pass = 0; pass < (TWICE ? 2 : 1); pass++) {
        float s = 0.f;
#pragma unroll
        for (int i = 0; i < 32; i++) s += f[i];
        const float mean = warp_sum(s) * (1.f / DM);
        float q = 0.f;
#pragma unroll
        for (int i = 0; i < 32; i++) { f[i] -= mean; q += f[i] * f[i]; }
        const float rstd = rsqrtf(warp_sum(q) * (1.f / DM) + 1e-5f);
#pragma unroll
        for (int i = 0; i < 32; i++) f[i] *= rstd;
    }
    uint4* dst = reinterpret_cast<uint4*>(out + (size_t)row * DM);
#pragma unroll
    for (int i = 0; i < 4; i++) {
        uint4 o;
        o.x = pack_bf16(f[8 * i + 0], f[8 * i + 1]); o.y = pack_bf16(f[8 * i + 2], f[8 * i + 3]);
        o.z = pack_bf16(f[8 * i + 4], f[8 * i + 5]); o.w = pack_bf16(f[8 * i + 6], f[8 * i + 7]);
        dst[lane + 32 * i] = o;
    }
    TL(TWICE ? 4 : 0, 3);
}

struct GemmSmem { uint32_t base, full0, empty0, aux; };

template <class C>
__device__ __forceinline__ GemmSmem gemm_setup(uint8_t* smem_raw) {
    GemmSmem s;
    s.base = smem_u32(smem_raw);
    s.full0 = s.base + C::BAR_OFF; s.empty0 = s.full0 + 8 * C::STAGES; s.aux = s.empty0 + 8 * C::STAGES;
    if (threadIdx.x == 0) {
        if (s.base & 1023) __trap();
        for (int i = 0; i < C::STAGES; i++) { mbar_init(s.full0 + 8 * i, 1); mbar_init(s.empty0 + 8 * i, 8); }
        mbar_init(s.aux, 1);
        fence_barrier_init();
    }
    __syncthreads();
    return s;
}

template <class C, class P>
__device__ __forceinline__ void gemm_producer(const GemmSmem& s, const P& p, int tm, int tn) {
#pragma unroll 1
    for (int k = 0; k < C::STAGES; k++) {
        mbar_expect_tx(s.full0 + 8 * k, C::STAGE_BYTES);
        C::load_w(p, s.base + k * C::STAGE_BYTES, s.full0 + 8 * k, k, tm, tn);
    }
    pdl_wait();
    C::load_aux(p, s, tm, tn);
#pragma unroll 1
    for (int k = 0; k < C::STAGES; k++) C::load_x(p, s.base + k * C::STAGE_BYTES, s.full0 + 8 * k, k, tm, tn);
    int st = 0; uint32_t ph = 0;
#pragma unroll 1
    for (int k = C::STAGES; k < C::KSTEPS; k++) {
        mbar_wait(s.empty0 + 8 * st, ph);
        mbar_expect_tx(s.full0 + 8 * st, C::STAGE_BYTES);
        C::load_w(p, s.base + st * C::STAGE_BYTES, s.full0 + 8 * st, k, tm, tn);
        C::load_x(p, s.base + st * C::STAGE_BYTES, s.full0 + 8 * st, k, tm, tn);
        if (++st == C::STAGES) { st = 0; ph ^= 1; }
    }
}

template <class C>
__device__ __forceinline__ void gemm_mainloop(const GemmSmem& s, int wg, float (&acc)[C::MB][C::BN / 2]) {
    const int lane = threadIdx.x & 31;
    int st = 0; uint32_t ph = 0;
    int prev = 0;
#pragma unroll
    for (int m = 0; m < C::MB; m++) fence_regs(acc[m]);
#pragma unroll 1
    for (int k = 0; k < C::KSTEPS; k++) {
        mbar_wait(s.full0 + 8 * st, ph);
        const uint32_t sb = s.base + st * C::STAGE_BYTES;
        wg_fence();
#pragma unroll
        for (int kk = 0; kk < 4; kk++) {
#pragma unroll
            for (int m = 0; m < C::MB; m++) C::mma(acc[m], C::desc_a(sb, wg, m, kk), C::desc_b(sb, kk), (k | kk) != 0);
        }
        wg_commit();
        if (k > 0) { wg_wait<1>(); if (lane == 0) mbar_arrive(s.empty0 + 8 * prev); }
        prev = st;
        if (++st == C::STAGES) { st = 0; ph ^= 1; }
    }
    wg_wait<0>();
#pragma unroll
    for (int m = 0; m < C::MB; m++) fence_regs(acc[m]);
}

struct QkvParams { CUtensorMap xn, w, out; };
struct QkvCfg {
    static constexpr int MB = 2, BN = 192, KSTEPS = 16, STAGES = 4, A_BYTES = 32768, B_BYTES = 24576;
    static constexpr int STAGE_BYTES = A_BYTES + B_BYTES, BAR_OFF = STAGES * STAGE_BYTES, SMEM = BAR_OFF + 128;
    static __device__ __forceinline__ void load_w(const QkvParams& p, uint32_t sb, uint32_t bar, int k, int tm, int tn) { tma_ld4(sb + A_BYTES, &p.w, bar, 0, k * 64, 0, tn); }
    static __device__ __forceinline__ void load_x(const QkvParams& p, uint32_t sb, uint32_t bar, int k, int tm, int tn) { tma_ld2(sb, &p.xn, bar, k * 64, tm * 256); }
    static __device__ __forceinline__ void load_aux(const QkvParams&, const GemmSmem&, int, int) {}
    static __device__ __forceinline__ uint64_t desc_a(uint32_t sb, int wg, int m, int kk) { return make_desc(sb + (wg * 128 + m * 64) * 128 + kk * 32, 16, 1024, 1); }
    static __device__ __forceinline__ uint64_t desc_b(uint32_t sb, int kk) { return make_desc(sb + A_BYTES + kk * 2048, 8192, 1024, 1); }
    static __device__ __forceinline__ void mma(float (&d)[96], uint64_t a, uint64_t b, int sc) { wgmma_ss_n192_t01(d, a, b, sc); }
};
__global__ void __launch_bounds__(384, 1) qkv_kernel(const __grid_constant__ QkvParams p) {
    extern __shared__ __align__(1024) uint8_t smem_raw[];
    pdl_launch();
    const int tm = blockIdx.x & 7, tn = blockIdx.x >> 3;
    if (threadIdx.x == 0) { prefetch_map(&p.xn); prefetch_map(&p.w); prefetch_map(&p.out); }
    const GemmSmem s = gemm_setup<QkvCfg>(smem_raw);
    const int wgi = threadIdx.x >> 7;
    if (wgi == 0) {
        reg_dealloc<40>();
        if (threadIdx.x == 0) gemm_producer<QkvCfg>(s, p, tm, tn);
    } else {
        reg_alloc<232>();
        const int wg = wgi - 1, warp = (threadIdx.x >> 5) & 3, lane = threadIdx.x & 31;
        float acc[2][96];
        pdl_wait();
        TL(1, 0);
        gemm_mainloop<QkvCfg>(s, wg, acc);
        TL(1, 1);
        named_bar(1, 256);
        const float qscale = 0.17677669529663687f * 1.4426950408889634f;
        float nmax[6];
#pragma unroll
        for (int i = 0; i < 6; i++) nmax[i] = 0.f;
#pragma unroll
        for (int m = 0; m < 2; m++) {
            const int rbase = wg * 128 + m * 64 + warp * 16;
            const int arow = rbase + ((lane >> 3) & 1) * 8 + (lane & 7);
#pragma unroll
            for (int sub = 0; sub < 6; sub++) {
                float v[16];
#pragma unroll
                for (int i = 0; i < 16; i++) v[i] = (sub < 2) ? acc[m][sub * 16 + i] * qscale : acc[m][sub * 16 + i];
                float n0 = 0.f, n1 = 0.f;
#pragma unroll
                for (int j = 0; j < 4; j++) {
                    n0 += v[4 * j] * v[4 * j] + v[4 * j + 1] * v[4 * j + 1];
                    n1 += v[4 * j + 2] * v[4 * j + 2] + v[4 * j + 3] * v[4 * j + 3];
                }
                n0 += __shfl_xor_sync(0xffffffffu, n0, 1); n1 += __shfl_xor_sync(0xffffffffu, n1, 1);
                n0 += __shfl_xor_sync(0xffffffffu, n0, 2); n1 += __shfl_xor_sync(0xffffffffu, n1, 2);
                nmax[sub] = __uint_as_float(max(max(__float_as_uint(n0), __float_as_uint(n1)), __float_as_uint(nmax[sub])));
#pragma unroll
                for (int jp = 0; jp < 2; jp++) {
                    const int chunk = jp * 2 + (lane >> 4);
                    const uint32_t addr = s.base + sub * 16384 + arow * 64 + ((chunk ^ ((arow >> 1) & 3)) << 4);
                    stmatrix_x4(addr, pack_bf16(v[8 * jp], v[8 * jp + 1]), pack_bf16(v[8 * jp + 2], v[8 * jp + 3]),
                                pack_bf16(v[8 * jp + 4], v[8 * jp + 5]), pack_bf16(v[8 * jp + 6], v[8 * jp + 7]));
                }
            }
        }
        fence_proxy_async();
        named_bar(2 + wg, 128);
        if ((threadIdx.x & 127) == 0) {
#pragma unroll
            for (int sub = 0; sub < 6; sub++)
                tma_st2(&p.out, s.base + sub * 16384 + wg * 8192, 0, (sub >> 1) * (NH * SEQ) + (tn * 2 + (sub & 1)) * SEQ + tm * 256 + wg * 128);
            tma_st_commit();
        }
#pragma unroll
        for (int sub = 0; sub < 6; sub++) {
            const uint32_t mx = __reduce_max_sync(0xffffffffu, __float_as_uint(nmax[sub]));
            if (lane == 0) atomicMax(&g_norm[(sub >> 1) * NH + tn * 2 + (sub & 1)], mx);
        }
        if ((threadIdx.x & 127) == 0) tma_st_wait();
        TL(1, 3);
    }
}

struct AttnParams { CUtensorMap kv; bf16* o; const bf16* qkv; };
constexpr int AT_STAGES = 8, AT_STAGE_BYTES = 16384, AT_ONES_OFF = AT_STAGES * AT_STAGE_BYTES, AT_BAR_OFF = AT_ONES_OFF + 1024, AT_SMEM = AT_BAR_OFF + 256;
constexpr int AT_TILES = 32;

__device__ __forceinline__ float ex2_poly(float x) {
    const float magic = 12582912.f;
    const float t = x + magic;
    const float f = x - (t - magic);
    float p = fmaf(f, 0.05550410866f, 0.24022650695f);
    p = fmaf(p, f, 0.69314718056f);
    p = fmaf(p, f, 1.0f);
    return __int_as_float(__float_as_int(p) + (__float_as_int(t) << 23));
}

__device__ __forceinline__ void attn_issue_tile(const AttnParams& p, uint32_t base, uint32_t full0, int g, int head) {
    const int st = g % AT_STAGES, key0 = (g & 15) * 128;
    const uint32_t bar = full0 + 8 * st, dst = base + st * AT_STAGE_BYTES;
    mbar_expect_tx(bar, AT_STAGE_BYTES);
    tma_ld2(dst, &p.kv, bar, 0, (NH + head) * SEQ + key0);
    tma_ld2(dst + 8192, &p.kv, bar, 0, (2 * NH + head) * SEQ + key0);
}
__device__ __forceinline__ void attn_qk(float (&sacc)[32], const uint32_t (&q)[8], uint32_t kaddr) {
    wgmma_rs_n64_t0(sacc, q[0], q[1], q[2], q[3], make_desc(kaddr, 16, 512, 2), 0);
    wgmma_rs_n64_t0(sacc, q[4], q[5], q[6], q[7], make_desc(kaddr + 32, 16, 512, 2), 1);
}
__device__ __forceinline__ void attn_pv(float (&o)[20], const uint32_t (&pr)[16], uint32_t vaddr, uint32_t ones, int first) {
#pragma unroll
    for (int kk = 0; kk < 4; kk++) {
        const uint32_t a = vaddr + kk * 1024;
        wgmma_rs_n40_t1(o, pr[4 * kk], pr[4 * kk + 1], pr[4 * kk + 2], pr[4 * kk + 3], make_desc(a, ones - a, 512, 2), (kk > 0) || !first);
    }
}

template <bool SAFE_MAX>
__device__ __forceinline__ void attn_body(const AttnParams& p, uint32_t base, uint32_t full0, uint32_t empty0, int head, int qchunk) {
    const int wg = threadIdx.x >> 7, warp = (threadIdx.x >> 5) & 3, lane = threadIdx.x & 31;
    const uint32_t ones = base + AT_ONES_OFF;
#pragma unroll 1
    for (int pass = 0; pass < 2; pass++) {
        const int row0 = qchunk * 512 + pass * 256 + wg * 64 + warp * 16 + (lane >> 2);
        uint32_t q[8];
        {
            const uint32_t* qp = reinterpret_cast<const uint32_t*>(p.qkv + ((size_t)head * SEQ + row0) * HD) + (lane & 3);
#pragma unroll
            for (int kk = 0; kk < 2; kk++) {
                q[4 * kk + 0] = __ldg(qp + kk * 8); q[4 * kk + 1] = __ldg(qp + kk * 8 + 8 * 16);
                q[4 * kk + 2] = __ldg(qp + kk * 8 + 4); q[4 * kk + 3] = __ldg(qp + kk * 8 + 4 + 8 * 16);
            }
        }
        float o[20];
        float sa[32], sb[32];
        uint32_t pr[16];
        float m0 = -INFINITY, m1 = -INFINITY;
#pragma unroll
        for (int i = 0; i < 20; i++) o[i] = 0.f;
        const int g0 = pass * 16;
        mbar_wait(full0 + 8 * (g0 % AT_STAGES), (g0 / AT_STAGES) & 1);
        wg_fence();
        attn_qk(sa, q, base + (g0 % AT_STAGES) * AT_STAGE_BYTES);
        wg_commit();
        wg_commit();
#pragma unroll 1
        for (int j = 0; j < 16; j++) {
            const int g = g0 + j;
            const int st = g % AT_STAGES;
            const uint32_t kb = base + st * AT_STAGE_BYTES, vb = kb + 8192;
            if (threadIdx.x == 0 && g >= 4 && g + 4 < AT_TILES) {
                const int gp = g - 4;
                mbar_wait(empty0 + 8 * (gp % AT_STAGES), (gp / AT_STAGES) & 1);
                attn_issue_tile(p, base, full0, g + 4, head);
            }
            __syncwarp();
#pragma unroll
            for (int half = 0; half < 2; half++) {
                float (&cur)[32] = half == 0 ? sa : sb;
                float (&nxt)[32] = half == 0 ? sb : sa;
                if (half == 0) {
                    wg_fence();
                    attn_qk(nxt, q, kb + 64 * 64);
                } else if (j < 15) {
                    const int g1 = g + 1, st1 = g1 % AT_STAGES;
                    mbar_wait(full0 + 8 * st1, (g1 / AT_STAGES) & 1);
                    wg_fence();
                    attn_qk(nxt, q, base + st1 * AT_STAGE_BYTES);
                }
                wg_commit();
                wg_wait<2>();
                fence_regs(cur);
                if (SAFE_MAX) {
                    float x0 = cur[0], x1 = cur[2];
#pragma unroll
                    for (int i = 0; i < 8; i++) { x0 = fmaxf(x0, fmaxf(cur[4 * i], cur[4 * i + 1])); x1 = fmaxf(x1, fmaxf(cur[4 * i + 2], cur[4 * i + 3])); }
                    x0 = fmaxf(x0, __shfl_xor_sync(0xffffffffu, x0, 1)); x1 = fmaxf(x1, __shfl_xor_sync(0xffffffffu, x1, 1));
                    x0 = fmaxf(x0, __shfl_xor_sync(0xffffffffu, x0, 2)); x1 = fmaxf(x1, __shfl_xor_sync(0xffffffffu, x1, 2));
                    const float n0 = fmaxf(m0, x0), n1 = fmaxf(m1, x1);
                    const float a0 = ex2(m0 - n0), a1 = ex2(m1 - n1);
                    m0 = n0; m1 = n1;
#pragma unroll
                    for (int i = 0; i < 8; i++) {
                        cur[4 * i] = ex2(cur[4 * i] - n0); cur[4 * i + 1] = ex2(cur[4 * i + 1] - n0);
                        cur[4 * i + 2] = ex2(cur[4 * i + 2] - n1); cur[4 * i + 3] = ex2(cur[4 * i + 3] - n1);
                    }
                    wg_wait<1>();
                    fence_regs(o);
#pragma unroll
                    for (int i = 0; i < 5; i++) { o[4 * i] *= a0; o[4 * i + 1] *= a0; o[4 * i + 2] *= a1; o[4 * i + 3] *= a1; }
                } else {
#pragma unroll
                    for (int i = 0; i < 32; i++) cur[i] = ((POLY_MASK >> (i & 7)) & 1) ? ex2_poly(cur[i]) : ex2(cur[i]);
                    wg_wait<1>();
                }
                if (half == 0 && g > 0 && lane == 0 && (j > 0)) mbar_arrive(empty0 + 8 * ((g - 1) % AT_STAGES));
#pragma unroll
                for (int i = 0; i < 16; i++) pr[i] = pack_bf16(cur[2 * i], cur[2 * i + 1]);
                wg_fence();
                attn_pv(o, pr, vb + half * 64 * 64, ones, 0);
                wg_commit();
            }
        }
        wg_wait<0>();
        fence_regs(o);
        if (lane == 0) mbar_arrive(empty0 + 8 * ((g0 + 15) % AT_STAGES));
        const float r0 = 1.f / o[16], r1 = 1.f / o[18];
        uint32_t* op = reinterpret_cast<uint32_t*>(p.o + (size_t)row0 * DM + head * HD) + (lane & 3);
#pragma unroll
        for (int j = 0; j < 4; j++) {
            op[j * 4] = pack_bf16(o[4 * j] * r0, o[4 * j + 1] * r0);
            op[j * 4 + 8 * (DM / 2)] = pack_bf16(o[4 * j + 2] * r1, o[4 * j + 3] * r1);
        }
    }
}

__global__ void __launch_bounds__(512, 1) attn_kernel(const __grid_constant__ AttnParams p) {
    extern __shared__ __align__(1024) uint8_t smem_raw[];
    pdl_launch();
    const uint32_t base = smem_u32(smem_raw);
    const uint32_t full0 = base + AT_BAR_OFF, empty0 = full0 + 8 * AT_STAGES;
    const int head = blockIdx.x >> 2, qchunk = blockIdx.x & 3;
    if (threadIdx.x == 0) {
        if (base & 1023) __trap();
        prefetch_map(&p.kv);
        for (int i = 0; i < AT_STAGES; i++) { mbar_init(full0 + 8 * i, 1); mbar_init(empty0 + 8 * i, 16); }
        fence_barrier_init();
    }
    if (threadIdx.x < 256) reinterpret_cast<uint32_t*>(smem_raw + AT_ONES_OFF)[threadIdx.x] = 0x3F803F80u;
    fence_proxy_async();
    __syncthreads();
    pdl_wait();
    TL(2, 0);
    if (threadIdx.x == 0) {
        for (int g = 0; g < AT_STAGES; g++) attn_issue_tile(p, base, full0, g, head);
    }
    __syncwarp();
    const float qn = __uint_as_float(g_norm[head]), kn = __uint_as_float(g_norm[NH + head]), vn = __uint_as_float(g_norm[2 * NH + head]);
    const bool bounded = (qn * kn <= 1.0e4f) && (vn <= 1.0e9f);
    if (bounded) attn_body<false>(p, base, full0, empty0, head, qchunk);
    else attn_body<true>(p, base, full0, empty0, head, qchunk);
    TL(2, 3);
}

struct ResParams { CUtensorMap a, b, res, out; const bf16* bias; };
template <bool MIX2>
struct ResCfg {
    static constexpr int MB = 1, BN = 128, KSTEPS = MIX2 ? 56 : 16, STAGES = 6, A_BYTES = 16384, B_BYTES = 16384;
    static constexpr int STAGE_BYTES = A_BYTES + B_BYTES, STG_OFF = STAGES * STAGE_BYTES, BAR_OFF = STG_OFF + 32768, SMEM = BAR_OFF + 128;
    static __device__ __forceinline__ void load_w(const ResParams& p, uint32_t sb, uint32_t bar, int k, int tm, int tn) {
        if (MIX2) tma_ld3(sb, &p.a, bar, 0, k * 64, tm * 2);
        else tma_ld3(sb + A_BYTES, &p.b, bar, 0, k * 64, tn * 2);
    }
    static __device__ __forceinline__ void load_x(const ResParams& p, uint32_t sb, uint32_t bar, int k, int tm, int tn) {
        if (MIX2) tma_ld2(sb + A_BYTES, &p.b, bar, k * 64, tn * 128);
        else tma_ld2(sb, &p.a, bar, k * 64, tm * 128);
    }
    static __device__ __forceinline__ void load_aux(const ResParams& p, const GemmSmem& s, int tm, int tn) {
        mbar_expect_tx(s.aux, 32768);
        tma_ld2(s.base + STG_OFF, &p.res, s.aux, tn * 128, tm * 128);
        tma_ld2(s.base + STG_OFF + 16384, &p.res, s.aux, tn * 128 + 64, tm * 128);
    }
    static __device__ __forceinline__ uint64_t desc_a(uint32_t sb, int wg, int m, int kk) {
        return MIX2 ? make_desc(sb + wg * 8192 + kk * 2048, 8192, 1024, 1) : make_desc(sb + wg * 8192 + kk * 32, 16, 1024, 1);
    }
    static __device__ __forceinline__ uint64_t desc_b(uint32_t sb, int kk) {
        return MIX2 ? make_desc(sb + A_BYTES + kk * 32, 16, 1024, 1) : make_desc(sb + A_BYTES + kk * 2048, 8192, 1024, 1);
    }
    static __device__ __forceinline__ void mma(float (&d)[64], uint64_t a, uint64_t b, int sc) {
        if (MIX2) wgmma_ss_n128_t10(d, a, b, sc); else wgmma_ss_n128_t01(d, a, b, sc);
    }
};
template <bool MIX2>
__global__ void __launch_bounds__(384, 1) res_gemm_kernel(const __grid_constant__ ResParams p) {
    using C = ResCfg<MIX2>;
    extern __shared__ __align__(1024) uint8_t smem_raw[];
    pdl_launch();
    const int tm = blockIdx.x & 15, tn = blockIdx.x >> 4;
    if (threadIdx.x == 0) { prefetch_map(&p.a); prefetch_map(&p.b); prefetch_map(&p.res); prefetch_map(&p.out); }
    const GemmSmem s = gemm_setup<C>(smem_raw);
    const int wgi = threadIdx.x >> 7;
    if (wgi == 0) {
        reg_dealloc<40>();
        if (threadIdx.x == 0) gemm_producer<C>(s, p, tm, tn);
    } else {
        reg_alloc<232>();
        const int wg = wgi - 1, warp = (threadIdx.x >> 5) & 3, lane = threadIdx.x & 31;
        float acc[1][64];
        pdl_wait();
        TL(MIX2 ? 6 : 3, 0);
        const int r0 = wg * 64 + warp * 16 + (lane >> 2);
        float b0 = 0.f, b1 = 0.f;
        if (MIX2) { b0 = __bfloat162float(p.bias[tm * 128 + r0]); b1 = __bfloat162float(p.bias[tm * 128 + r0 + 8]); }
        gemm_mainloop<C>(s, wg, acc);
        TL(MIX2 ? 6 : 3, 1);
        mbar_wait(s.aux, 0);
        uint8_t* stg = smem_raw + C::STG_OFF;
#pragma unroll
        for (int j = 0; j < 16; j++) {
            const int off = (j >> 3) * 16384 + r0 * 128 + (((j & 7) ^ (r0 & 7)) << 4) + (lane & 3) * 4;
            uint32_t* p0 = reinterpret_cast<uint32_t*>(stg + off);
            uint32_t* p1 = reinterpret_cast<uint32_t*>(stg + off + 8 * 128);
            const uint32_t x0 = *p0, x1 = *p1;
            *p0 = pack_bf16(acc[0][4 * j] + b0 + bf_lo(x0), acc[0][4 * j + 1] + b0 + bf_hi(x0));
            *p1 = pack_bf16(acc[0][4 * j + 2] + b1 + bf_lo(x1), acc[0][4 * j + 3] + b1 + bf_hi(x1));
        }
        fence_proxy_async();
        named_bar(2 + wg, 128);
        if ((threadIdx.x & 127) == 0) {
            tma_st2(&p.out, s.base + C::STG_OFF + wg * 8192, tn * 128, tm * 128 + wg * 64);
            tma_st2(&p.out, s.base + C::STG_OFF + 16384 + wg * 8192, tn * 128 + 64, tm * 128 + wg * 64);
            tma_st_commit();
            tma_st_wait();
        }
        TL(MIX2 ? 6 : 3, 3);
    }
}

struct Mix1Params { CUtensorMap hn, w1, out; const bf16* bias; };
struct Mix1Cfg {
    static constexpr int MB = 1, BN = 224, KSTEPS = 32, STAGES = 5, A_BYTES = 16384, B_BYTES = 28672;
    static constexpr int STAGE_BYTES = A_BYTES + B_BYTES, BIAS_OFF = STAGES * STAGE_BYTES, BAR_OFF = BIAS_OFF + 1024, SMEM = BAR_OFF + 128;
    static __device__ __forceinline__ void load_w(const Mix1Params& p, uint32_t sb, uint32_t bar, int k, int tm, int tn) { tma_ld3(sb + A_BYTES, &p.w1, bar, 0, k * 64, tn * 7); }
    static __device__ __forceinline__ void load_x(const Mix1Params& p, uint32_t sb, uint32_t bar, int k, int tm, int tn) { tma_ld3(sb, &p.hn, bar, 0, k * 64, tm * 2); }
    static __device__ __forceinline__ void load_aux(const Mix1Params&, const GemmSmem&, int, int) {}
    static __device__ __forceinline__ uint64_t desc_a(uint32_t sb, int wg, int m, int kk) { return make_desc(sb + wg * 8192 + kk * 2048, 8192, 1024, 1); }
    static __device__ __forceinline__ uint64_t desc_b(uint32_t sb, int kk) { return make_desc(sb + A_BYTES + kk * 1024, 4096, 512, 2); }
    static __device__ __forceinline__ void mma(float (&d)[112], uint64_t a, uint64_t b, int sc) { wgmma_ss_n224_t11(d, a, b, sc); }
};
__global__ void __launch_bounds__(384, 1) mix1_kernel(const __grid_constant__ Mix1Params p) {
    using C = Mix1Cfg;
    extern __shared__ __align__(1024) uint8_t smem_raw[];
    pdl_launch();
    const int tm = blockIdx.x & 7, tn = blockIdx.x >> 3;
    if (threadIdx.x == 0) { prefetch_map(&p.hn); prefetch_map(&p.w1); prefetch_map(&p.out); }
    float* sbias = reinterpret_cast<float*>(smem_raw + C::BIAS_OFF);
    if (threadIdx.x < 224) sbias[threadIdx.x] = __bfloat162float(p.bias[tn * 224 + threadIdx.x]);
    const GemmSmem s = gemm_setup<C>(smem_raw);
    const int wgi = threadIdx.x >> 7;
    if (wgi == 0) {
        reg_dealloc<40>();
        if (threadIdx.x == 0) gemm_producer<C>(s, p, tm, tn);
    } else {
        reg_alloc<232>();
        const int wg = wgi - 1, warp = (threadIdx.x >> 5) & 3, lane = threadIdx.x & 31;
        float acc[1][112];
        pdl_wait();
        TL(5, 0);
        gemm_mainloop<C>(s, wg, acc);
        TL(5, 1);
        named_bar(1, 256);
        const int arow = warp * 16 + ((lane >> 3) & 1) * 8 + (lane & 7);
        const uint32_t stg = s.base + wg * 28672;
#pragma unroll
        for (int jp = 0; jp < 14; jp++) {
            float v[8];
#pragma unroll
            for (int h = 0; h < 2; h++) {
                const float2 bb = *reinterpret_cast<const float2*>(sbias + (jp * 2 + h) * 8 + (lane & 3) * 2);
#pragma unroll
                for (int i = 0; i < 4; i++) {
                    const float x = acc[0][jp * 8 + h * 4 + i] + ((i & 1) ? bb.y : bb.x);
                    const float inner = x * fmaf(x * x, 0.0356774081363f, 0.7978845608029f);
                    const float hx = 0.5f * x;
                    v[h * 4 + i] = fmaf(hx, tanh_fast(inner), hx);
                }
            }
            const int j = jp * 2 + (lane >> 4);
            const uint32_t addr = stg + (j >> 2) * 4096 + arow * 64 + (((j & 3) ^ ((arow >> 1) & 3)) << 4);
            stmatrix_x4(addr, pack_bf16(v[0], v[1]), pack_bf16(v[2], v[3]), pack_bf16(v[4], v[5]), pack_bf16(v[6], v[7]));
        }
        fence_proxy_async();
        named_bar(2 + wg, 128);
        if ((threadIdx.x & 127) == 0) {
            tma_st3(&p.out, stg, 0, tm * 128 + wg * 64, tn * 7);
            tma_st_commit();
            tma_st_wait();
        }
        TL(5, 3);
    }
}

typedef CUresult (*EncodeFn)(CUtensorMap*, CUtensorMapDataType, cuuint32_t, void*, const cuuint64_t*, const cuuint64_t*, const cuuint32_t*,
                             const cuuint32_t*, CUtensorMapInterleave, CUtensorMapSwizzle, CUtensorMapL2promotion, CUtensorMapFloatOOBfill);
EncodeFn g_encode;

void make_map(CUtensorMap* m, const void* ptr, int rank, const uint64_t* dims, const uint64_t* strides_bytes, const uint32_t* box, CUtensorMapSwizzle swz) {
    cuuint64_t d[5], st[5]; cuuint32_t b[5], es[5];
    for (int i = 0; i < rank; i++) { d[i] = dims[i]; b[i] = box[i]; es[i] = 1; }
    for (int i = 0; i + 1 < rank; i++) st[i] = strides_bytes[i];
    CUresult r = g_encode(m, CU_TENSOR_MAP_DATA_TYPE_BFLOAT16, rank, const_cast<void*>(ptr), d, st, b, es, CU_TENSOR_MAP_INTERLEAVE_NONE, swz,
                          CU_TENSOR_MAP_L2_PROMOTION_L2_128B, CU_TENSOR_MAP_FLOAT_OOB_FILL_NONE);
    if (r != CUDA_SUCCESS) fprintf(stderr, "cuTensorMapEncodeTiled failed: %d\n", (int)r);
}
void map2d(CUtensorMap* m, const void* ptr, uint64_t cols, uint64_t rows, uint32_t bc, uint32_t br, CUtensorMapSwizzle swz) {
    uint64_t dims[2] = {cols, rows}, st[1] = {cols * 2}; uint32_t box[2] = {bc, br};
    make_map(m, ptr, 2, dims, st, box, swz);
}
void map3d(CUtensorMap* m, const void* ptr, uint64_t cols, uint64_t rows, uint32_t inner, uint32_t br, uint32_t nblk, CUtensorMapSwizzle swz) {
    uint64_t dims[3] = {inner, rows, cols / inner}, st[2] = {cols * 2, (uint64_t)inner * 2}; uint32_t box[3] = {inner, br, nblk};
    make_map(m, ptr, 3, dims, st, box, swz);
}

template <class... KArgs, class... Args>
void launch(void (*kern)(KArgs...), int grid, int block, int smem, bool pdl, Args&&... args) {
    cudaLaunchConfig_t cfg = {};
    cfg.gridDim = dim3(grid); cfg.blockDim = dim3(block); cfg.dynamicSmemBytes = smem; cfg.stream = 0;
    cudaLaunchAttribute at[1];
    at[0].id = cudaLaunchAttributeProgrammaticStreamSerialization; at[0].val.programmaticStreamSerializationAllowed = 1;
    cfg.attrs = at; cfg.numAttrs = pdl ? 1 : 0;
    cudaError_t e = cudaLaunchKernelEx(&cfg, kern, KArgs(args)...);
    if (e != cudaSuccess) fprintf(stderr, "launch failed: %s\n", cudaGetErrorString(e));
}

struct HostState {
    bool ready;
    const void* key[9];
    QkvParams qkv; AttnParams attn; ResParams wo, mix2; Mix1Params mix1;
    bf16 *xn, *qkvp, *o, *h, *hn, *u;
};
HostState g_hs;

}

#define USE_PDL 1

extern "C" void kernel_launch(void* const* d_in, const int* in_sizes, int n_in, void* d_out, int out_size) {
    const bf16* x = (const bf16*)d_in[0];
    const bf16* wqkv = (const bf16*)d_in[1];
    const bf16* wo = (const bf16*)d_in[2];
    const bf16* w1 = (const bf16*)d_in[4];
    const bf16* b1 = (const bf16*)d_in[5];
    const bf16* w2 = (const bf16*)d_in[6];
    const bf16* b2 = (const bf16*)d_in[7];
    HostState& hs = g_hs;
    bool same = hs.ready;
    for (int i = 0; i < 8 && same; i++) same = (hs.key[i] == d_in[i]);
    same = same && hs.key[8] == d_out;
    if (!same) {
        if (!g_encode) {
            void* fn = nullptr; cudaDriverEntryPointQueryResult qr;
            cudaGetDriverEntryPoint("cuTensorMapEncodeTiled", &fn, cudaEnableDefault, &qr);
            g_encode = (EncodeFn)fn;
            cudaFuncSetAttribute(qkv_kernel, cudaFuncAttributeMaxDynamicSharedMemorySize, QkvCfg::SMEM);
            cudaFuncSetAttribute(attn_kernel, cudaFuncAttributeMaxDynamicSharedMemorySize, AT_SMEM);
            cudaFuncSetAttribute(res_gemm_kernel<false>, cudaFuncAttributeMaxDynamicSharedMemorySize, ResCfg<false>::SMEM);
            cudaFuncSetAttribute(res_gemm_kernel<true>, cudaFuncAttributeMaxDynamicSharedMemorySize, ResCfg<true>::SMEM);
            cudaFuncSetAttribute(mix1_kernel, cudaFuncAttributeMaxDynamicSharedMemorySize, Mix1Cfg::SMEM);
        }
        cudaGetSymbolAddress((void**)&hs.xn, g_xn); cudaGetSymbolAddress((void**)&hs.qkvp, g_qkv); cudaGetSymbolAddress((void**)&hs.o, g_o);
        cudaGetSymbolAddress((void**)&hs.h, g_h); cudaGetSymbolAddress((void**)&hs.hn, g_hn); cudaGetSymbolAddress((void**)&hs.u, g_u);
        const CUtensorMapSwizzle S128 = CU_TENSOR_MAP_SWIZZLE_128B, S64 = CU_TENSOR_MAP_SWIZZLE_64B;
        map2d(&hs.qkv.xn, hs.xn, DM, SEQ, 64, 256, S128);
        {
            uint64_t dims[4] = {64, (uint64_t)DM, 3, 16}, st[3] = {3 * DM * 2, DM * 2, 128}; uint32_t box[4] = {64, 64, 3, 1};
            make_map(&hs.qkv.w, wqkv, 4, dims, st, box, S128);
        }
        map2d(&hs.qkv.out, hs.qkvp, HD, 3 * NH * SEQ, 32, 128, S64);
        hs.attn.kv = hs.qkv.out; hs.attn.o = hs.o; hs.attn.qkv = hs.qkvp;
        map2d(&hs.wo.a, hs.o, DM, SEQ, 64, 128, S128);
        map3d(&hs.wo.b, wo, DM, DM, 64, 64, 2, S128);
        map2d(&hs.wo.res, x, DM, SEQ, 64, 128, S128);
        map2d(&hs.wo.out, hs.h, DM, SEQ, 64, 64, S128);
        hs.wo.bias = nullptr;
        map3d(&hs.mix1.hn, hs.hn, DM, SEQ, 64, 64, 2, S128);
        map3d(&hs.mix1.w1, w1, FF, SEQ, 32, 64, 7, S64);
        map3d(&hs.mix1.out, hs.u, FF, DM, 32, 64, 7, S64);
        hs.mix1.bias = b1;
        map3d(&hs.mix2.a, w2, SEQ, FF, 64, 64, 2, S128);
        map2d(&hs.mix2.b, hs.u, FF, DM, 64, 128, S128);
        map2d(&hs.mix2.res, hs.h, DM, SEQ, 64, 128, S128);
        map2d(&hs.mix2.out, d_out, DM, SEQ, 64, 64, S128);
        hs.mix2.bias = b2;
        for (int i = 0; i < 8; i++) hs.key[i] = d_in[i];
        hs.key[8] = d_out;
        hs.ready = true;
    }
    const bool pdl = USE_PDL;
    launch(ln_kernel<false>, SEQ / 8, 256, 0, false, x, hs.xn);
    launch(qkv_kernel, 128, 384, QkvCfg::SMEM, pdl, hs.qkv);
    launch(attn_kernel, 128, 512, AT_SMEM, pdl, hs.attn);
    launch(res_gemm_kernel<false>, 128, 384, ResCfg<false>::SMEM, pdl, hs.wo);
    launch(ln_kernel<true>, SEQ / 8, 256, 0, pdl, (const bf16*)hs.h, hs.hn);
    launch(mix1_kernel, 128, 384, Mix1Cfg::SMEM, pdl, hs.mix1);
    launch(res_gemm_kernel<true>, 128, 384, ResCfg<true>::SMEM, pdl, hs.mix2);
}
```

```cpp
#include <cuda_runtime.h>
#include <cuda_bf16.h>
#include <cuda.h>
#include <stdint.h>
#include <stdio.h>

typedef __nv_bfloat16 bf16;

namespace {

#define POLY_MASK 0x49
constexpr int SEQ = 2048, DM = 1024, NH = 32, HD = 32, FF = 3584;

__device__ __align__(1024) bf16 g_xn[SEQ * DM];
__device__ __align__(1024) bf16 g_qkv[3 * NH * SEQ * HD];
__device__ __align__(1024) bf16 g_o[SEQ * DM];
__device__ __align__(1024) bf16 g_h[SEQ * DM];
__device__ __align__(1024) bf16 g_hn[SEQ * DM];
__device__ __align__(1024) bf16 g_u[DM * FF];
__device__ uint32_t g_norm[3 * NH];

#define TL(kern, slot)

__device__ __forceinline__ uint32_t smem_u32(const void* p) { return (uint32_t)__cvta_generic_to_shared(p); }
__device__ __forceinline__ void mbar_init(uint32_t bar, uint32_t cnt) { asm volatile("mbarrier.init.shared::cta.b64 [%0], %1;" :: "r"(bar), "r"(cnt) : "memory"); }
__device__ __forceinline__ void mbar_expect_tx(uint32_t bar, uint32_t bytes) { asm volatile("mbarrier.arrive.expect_tx.shared::cta.b64 _, [%0], %1;" :: "r"(bar), "r"(bytes) : "memory"); }
__device__ __forceinline__ void mbar_arrive(uint32_t bar) { asm volatile("mbarrier.arrive.shared::cta.b64 _, [%0];" :: "r"(bar) : "memory"); }
__device__ __forceinline__ void mbar_wait(uint32_t bar, uint32_t parity) {
    asm volatile("{\n.reg .pred p;\nWAIT_%=:\nmbarrier.try_wait.parity.shared::cta.b64 p, [%0], %1;\n@p bra DONE_%=;\nbra WAIT_%=;\nDONE_%=:\n}" :: "r"(bar), "r"(parity) : "memory");
}
__device__ __forceinline__ void fence_barrier_init() { asm volatile("fence.mbarrier_init.release.cluster;" ::: "memory"); }
__device__ __forceinline__ void fence_proxy_async() { asm volatile("fence.proxy.async.shared::cta;" ::: "memory"); }
__device__ __forceinline__ void pdl_launch() { asm volatile("griddepcontrol.launch_dependents;" ::: "memory"); }
__device__ __forceinline__ void pdl_wait() { asm volatile("griddepcontrol.wait;" ::: "memory"); }
__device__ __forceinline__ void named_bar(int id, int n) { asm volatile("bar.sync %0, %1;" :: "r"(id), "r"(n) : "memory"); }
__device__ __forceinline__ void prefetch_map(const CUtensorMap* m) { asm volatile("prefetch.tensormap [%0];" :: "l"(m) : "memory"); }

__device__ __forceinline__ void tma_ld2(uint32_t dst, const CUtensorMap* m, uint32_t bar, int c0, int c1) {
    asm volatile("cp.async.bulk.tensor.2d.shared::cluster.global.mbarrier::complete_tx::bytes [%0], [%1, {%3, %4}], [%2];"
                 :: "r"(dst), "l"(m), "r"(bar), "r"(c0), "r"(c1) : "memory");
}
__device__ __forceinline__ void tma_ld3(uint32_t dst, const CUtensorMap* m, uint32_t bar, int c0, int c1, int c2) {
    asm volatile("cp.async.bulk.tensor.3d.shared::cluster.global.mbarrier::complete_tx::bytes [%0], [%1, {%3, %4, %5}], [%2];"
                 :: "r"(dst), "l"(m), "r"(bar), "r"(c0), "r"(c1), "r"(c2) : "memory");
}
__device__ __forceinline__ void tma_ld4(uint32_t dst, const CUtensorMap* m, uint32_t bar, int c0, int c1, int c2, int c3) {
    asm volatile("cp.async.bulk.tensor.4d.shared::cluster.global.mbarrier::complete_tx::bytes [%0], [%1, {%3, %4, %5, %6}], [%2];"
                 :: "r"(dst), "l"(m), "r"(bar), "r"(c0), "r"(c1), "r"(c2), "r"(c3) : "memory");
}
__device__ __forceinline__ void tma_st2(const CUtensorMap* m, uint32_t src, int c0, int c1) {
    asm volatile("cp.async.bulk.tensor.2d.global.shared::cta.bulk_group [%0, {%2, %3}], [%1];" :: "l"(m), "r"(src), "r"(c0), "r"(c1) : "memory");
}
__device__ __forceinline__ void tma_st3(const CUtensorMap* m, uint32_t src, int c0, int c1, int c2) {
    asm volatile("cp.async.bulk.tensor.3d.global.shared::cta.bulk_group [%0, {%2, %3, %4}], [%1];" :: "l"(m), "r"(src), "r"(c0), "r"(c1), "r"(c2) : "memory");
}
__device__ __forceinline__ void tma_st_commit() { asm volatile("cp.async.bulk.commit_group;" ::: "memory"); }
__device__ __forceinline__ void tma_st_wait() { asm volatile("cp.async.bulk.wait_group.read 0;" ::: "memory"); }

__device__ __forceinline__ void wg_fence() { asm volatile("wgmma.fence.sync.aligned;" ::: "memory"); }
__device__ __forceinline__ void wg_commit() { asm volatile("wgmma.commit_group.sync.aligned;" ::: "memory"); }
template <int N> __device__ __forceinline__ void wg_wait() { asm volatile("wgmma.wait_group.sync.aligned %0;" :: "n"(N) : "memory"); }
template <int R> __device__ __forceinline__ void reg_alloc() { asm volatile("setmaxnreg.inc.sync.aligned.u32 %0;" :: "n"(R)); }
template <int R> __device__ __forceinline__ void reg_dealloc() { asm volatile("setmaxnreg.dec.sync.aligned.u32 %0;" :: "n"(R)); }
template <int N> __device__ __forceinline__ void fence_regs(float (&d)[N]) {
#pragma unroll
    for (int i = 0; i < N; i++) asm volatile("" : "+f"(d[i]) :: "memory");
}

__device__ __forceinline__ uint32_t desc_lo(uint32_t addr, uint32_t lbo) { return (addr >> 4) | ((lbo >> 4) << 16); }
__device__ __forceinline__ uint32_t pack_bf16(float lo, float hi) { uint32_t d; asm("cvt.rn.bf16x2.f32 %0, %1, %2;" : "=r"(d) : "f"(hi), "f"(lo)); return d; }
__device__ __forceinline__ float bf_lo(uint32_t v) { return __uint_as_float(v << 16); }
__device__ __forceinline__ float bf_hi(uint32_t v) { return __uint_as_float(v & 0xFFFF0000u); }
__device__ __forceinline__ void stmatrix_x4(uint32_t addr, uint32_t r0, uint32_t r1, uint32_t r2, uint32_t r3) {
    asm volatile("stmatrix.sync.aligned.m8n8.x4.shared.b16 [%0], {%1, %2, %3, %4};" :: "r"(addr), "r"(r0), "r"(r1), "r"(r2), "r"(r3) : "memory");
}
__device__ __forceinline__ float ex2(float x) { float y; asm("ex2.approx.ftz.f32 %0, %1;" : "=f"(y) : "f"(x)); return y; }
__device__ __forceinline__ float tanh_fast(float x) { float y; asm("tanh.approx.f32 %0, %1;" : "=f"(y) : "f"(x)); return y; }

__device__ __forceinline__ void mma_qkv(float (&d)[96], uint32_t alo, uint32_t blo, int scale_d) {
    asm volatile("{\n.reg .pred p;\n.reg .b64 da, db;\nsetp.ne.b32 p, %98, 0;\nmov.b64 da, {%96, 0x40000040};\nmov.b64 db, {%97, 0x40000040};\n"
        "wgmma.mma_async.sync.aligned.m64n192k16.f32.bf16.bf16 {"
        "%0, %1, %2, %3, %4, %5, %6, %7, %8, %9, %10, %11, %12, %13, %14, %15, %16, %17, %18, %19, %20, %21, %22, %23, %24, %25, %26, %27, %28, %29, %30, %31,  "
        "%32, %33, %34, %35, %36, %37, %38, %39, %40, %41, %42, %43, %44, %45, %46, %47, %48, %49, %50, %51, %52, %53, %54, %55, %56, %57, %58, %59, %60, %61,  "
        "%62, %63, %64, %65, %66, %67, %68, %69, %70, %71, %72, %73, %74, %75, %76, %77, %78, %79, %80, %81, %82, %83, %84, %85, %86, %87, %88, %89, %90, %91,  "
        "%92, %93, %94, %95 "
        "}, da, db, p, 1, 1, 0, 1;\n}\n"
        : "+f"(d[0]), "+f"(d[1]), "+f"(d[2]), "+f"(d[3]), "+f"(d[4]), "+f"(d[5]), "+f"(d[6]), "+f"(d[7]), "+f"(d[8]), "+f"(d[9]), "+f"(d[10]), "+f"(d[11]),
          "+f"(d[12]), "+f"(d[13]), "+f"(d[14]), "+f"(d[15]), "+f"(d[16]), "+f"(d[17]), "+f"(d[18]), "+f"(d[19]), "+f"(d[20]), "+f"(d[21]), "+f"(d[22]),
          "+f"(d[23]), "+f"(d[24]), "+f"(d[25]), "+f"(d[26]), "+f"(d[27]), "+f"(d[28]), "+f"(d[29]), "+f"(d[30]), "+f"(d[31]), "+f"(d[32]), "+f"(d[33]),
          "+f"(d[34]), "+f"(d[35]), "+f"(d[36]), "+f"(d[37]), "+f"(d[38]), "+f"(d[39]), "+f"(d[40]), "+f"(d[41]), "+f"(d[42]), "+f"(d[43]), "+f"(d[44]),
          "+f"(d[45]), "+f"(d[46]), "+f"(d[47]), "+f"(d[48]), "+f"(d[49]), "+f"(d[50]), "+f"(d[51]), "+f"(d[52]), "+f"(d[53]), "+f"(d[54]), "+f"(d[55]),
          "+f"(d[56]), "+f"(d[57]), "+f"(d[58]), "+f"(d[59]), "+f"(d[60]), "+f"(d[61]), "+f"(d[62]), "+f"(d[63]), "+f"(d[64]), "+f"(d[65]), "+f"(d[66]),
          "+f"(d[67]), "+f"(d[68]), "+f"(d[69]), "+f"(d[70]), "+f"(d[71]), "+f"(d[72]), "+f"(d[73]), "+f"(d[74]), "+f"(d[75]), "+f"(d[76]), "+f"(d[77]),
          "+f"(d[78]), "+f"(d[79]), "+f"(d[80]), "+f"(d[81]), "+f"(d[82]), "+f"(d[83]), "+f"(d[84]), "+f"(d[85]), "+f"(d[86]), "+f"(d[87]), "+f"(d[88]),
          "+f"(d[89]), "+f"(d[90]), "+f"(d[91]), "+f"(d[92]), "+f"(d[93]), "+f"(d[94]), "+f"(d[95])
        : "r"(alo), "r"(blo), "r"(scale_d));
}
__device__ __forceinline__ void mma_wo(float (&d)[64], uint32_t alo, uint32_t blo, int scale_d) {
    asm volatile("{\n.reg .pred p;\n.reg .b64 da, db;\nsetp.ne.b32 p, %66, 0;\nmov.b64 da, {%64, 0x40000040};\nmov.b64 db, {%65, 0x40000040};\n"
        "wgmma.mma_async.sync.aligned.m64n128k16.f32.bf16.bf16 {"
        "%0, %1, %2, %3, %4, %5, %6, %7, %8, %9, %10, %11, %12, %13, %14, %15, %16, %17, %18, %19, %20, %21, %22, %23, %24, %25, %26, %27, %28, %29, %30, %31,  "
        "%32, %33, %34, %35, %36, %37, %38, %39, %40, %41, %42, %43, %44, %45, %46, %47, %48, %49, %50, %51, %52, %53, %54, %55, %56, %57, %58, %59, %60, %61,  "
        "%62, %63 "
        "}, da, db, p, 1, 1, 0, 1;\n}\n"
        : "+f"(d[0]), "+f"(d[1]), "+f"(d[2]), "+f"(d[3]), "+f"(d[4]), "+f"(d[5]), "+f"(d[6]), "+f"(d[7]), "+f"(d[8]), "+f"(d[9]), "+f"(d[10]), "+f"(d[11]),
          "+f"(d[12]), "+f"(d[13]), "+f"(d[14]), "+f"(d[15]), "+f"(d[16]), "+f"(d[17]), "+f"(d[18]), "+f"(d[19]), "+f"(d[20]), "+f"(d[21]), "+f"(d[22]),
          "+f"(d[23]), "+f"(d[24]), "+f"(d[25]), "+f"(d[26]), "+f"(d[27]), "+f"(d[28]), "+f"(d[29]), "+f"(d[30]), "+f"(d[31]), "+f"(d[32]), "+f"(d[33]),
          "+f"(d[34]), "+f"(d[35]), "+f"(d[36]), "+f"(d[37]), "+f"(d[38]), "+f"(d[39]), "+f"(d[40]), "+f"(d[41]), "+f"(d[42]), "+f"(d[43]), "+f"(d[44]),
          "+f"(d[45]), "+f"(d[46]), "+f"(d[47]), "+f"(d[48]), "+f"(d[49]), "+f"(d[50]), "+f"(d[51]), "+f"(d[52]), "+f"(d[53]), "+f"(d[54]), "+f"(d[55]),
          "+f"(d[56]), "+f"(d[57]), "+f"(d[58]), "+f"(d[59]), "+f"(d[60]), "+f"(d[61]), "+f"(d[62]), "+f"(d[63])
        : "r"(alo), "r"(blo), "r"(scale_d));
}
__device__ __forceinline__ void mma_mix2(float (&d)[64], uint32_t alo, uint32_t blo, int scale_d) {
    asm volatile("{\n.reg .pred p;\n.reg .b64 da, db;\nsetp.ne.b32 p, %66, 0;\nmov.b64 da, {%64, 0x40000040};\nmov.b64 db, {%65, 0x40000040};\n"
        "wgmma.mma_async.sync.aligned.m64n128k16.f32.bf16.bf16 {"
        "%0, %1, %2, %3, %4, %5, %6, %7, %8, %9, %10, %11, %12, %13, %14, %15, %16, %17, %18, %19, %20, %21, %22, %23, %24, %25, %26, %27, %28, %29, %30, %31,  "
        "%32, %33, %34, %35, %36, %37, %38, %39, %40, %41, %42, %43, %44, %45, %46, %47, %48, %49, %50, %51, %52, %53, %54, %55, %56, %57, %58, %59, %60, %61,  "
        "%62, %63 "
        "}, da, db, p, 1, 1, 1, 0;\n}\n"
        : "+f"(d[0]), "+f"(d[1]), "+f"(d[2]), "+f"(d[3]), "+f"(d[4]), "+f"(d[5]), "+f"(d[6]), "+f"(d[7]), "+f"(d[8]), "+f"(d[9]), "+f"(d[10]), "+f"(d[11]),
          "+f"(d[12]), "+f"(d[13]), "+f"(d[14]), "+f"(d[15]), "+f"(d[16]), "+f"(d[17]), "+f"(d[18]), "+f"(d[19]), "+f"(d[20]), "+f"(d[21]), "+f"(d[22]),
          "+f"(d[23]), "+f"(d[24]), "+f"(d[25]), "+f"(d[26]), "+f"(d[27]), "+f"(d[28]), "+f"(d[29]), "+f"(d[30]), "+f"(d[31]), "+f"(d[32]), "+f"(d[33]),
          "+f"(d[34]), "+f"(d[35]), "+f"(d[36]), "+f"(d[37]), "+f"(d[38]), "+f"(d[39]), "+f"(d[40]), "+f"(d[41]), "+f"(d[42]), "+f"(d[43]), "+f"(d[44]),
          "+f"(d[45]), "+f"(d[46]), "+f"(d[47]), "+f"(d[48]), "+f"(d[49]), "+f"(d[50]), "+f"(d[51]), "+f"(d[52]), "+f"(d[53]), "+f"(d[54]), "+f"(d[55]),
          "+f"(d[56]), "+f"(d[57]), "+f"(d[58]), "+f"(d[59]), "+f"(d[60]), "+f"(d[61]), "+f"(d[62]), "+f"(d[63])
        : "r"(alo), "r"(blo), "r"(scale_d));
}
__device__ __forceinline__ void mma_mix1(float (&d)[112], uint32_t alo, uint32_t blo, int scale_d) {
    asm volatile("{\n.reg .pred p;\n.reg .b64 da, db;\nsetp.ne.b32 p, %114, 0;\nmov.b64 da, {%112, 0x40000040};\nmov.b64 db, {%113, 0x80000020};\n"
        "wgmma.mma_async.sync.aligned.m64n224k16.f32.bf16.bf16 {"
        "%0, %1, %2, %3, %4, %5, %6, %7, %8, %9, %10, %11, %12, %13, %14, %15, %16, %17, %18, %19, %20, %21, %22, %23, %24, %25, %26, %27, %28, %29, %30, %31,  "
        "%32, %33, %34, %35, %36, %37, %38, %39, %40, %41, %42, %43, %44, %45, %46, %47, %48, %49, %50, %51, %52, %53, %54, %55, %56, %57, %58, %59, %60, %61,  "
        "%62, %63, %64, %65, %66, %67, %68, %69, %70, %71, %72, %73, %74, %75, %76, %77, %78, %79, %80, %81, %82, %83, %84, %85, %86, %87, %88, %89, %90, %91,  "
        "%92, %93, %94, %95, %96, %97, %98, %99, %100, %101, %102, %103, %104, %105, %106, %107, %108, %109, %110, %111 "
        "}, da, db, p, 1, 1, 1, 1;\n}\n"
        : "+f"(d[0]), "+f"(d[1]), "+f"(d[2]), "+f"(d[3]), "+f"(d[4]), "+f"(d[5]), "+f"(d[6]), "+f"(d[7]), "+f"(d[8]), "+f"(d[9]), "+f"(d[10]), "+f"(d[11]),
          "+f"(d[12]), "+f"(d[13]), "+f"(d[14]), "+f"(d[15]), "+f"(d[16]), "+f"(d[17]), "+f"(d[18]), "+f"(d[19]), "+f"(d[20]), "+f"(d[21]), "+f"(d[22]),
          "+f"(d[23]), "+f"(d[24]), "+f"(d[25]), "+f"(d[26]), "+f"(d[27]), "+f"(d[28]), "+f"(d[29]), "+f"(d[30]), "+f"(d[31]), "+f"(d[32]), "+f"(d[33]),
          "+f"(d[34]), "+f"(d[35]), "+f"(d[36]), "+f"(d[37]), "+f"(d[38]), "+f"(d[39]), "+f"(d[40]), "+f"(d[41]), "+f"(d[42]), "+f"(d[43]), "+f"(d[44]),
          "+f"(d[45]), "+f"(d[46]), "+f"(d[47]), "+f"(d[48]), "+f"(d[49]), "+f"(d[50]), "+f"(d[51]), "+f"(d[52]), "+f"(d[53]), "+f"(d[54]), "+f"(d[55]),
          "+f"(d[56]), "+f"(d[57]), "+f"(d[58]), "+f"(d[59]), "+f"(d[60]), "+f"(d[61]), "+f"(d[62]), "+f"(d[63]), "+f"(d[64]), "+f"(d[65]), "+f"(d[66]),
          "+f"(d[67]), "+f"(d[68]), "+f"(d[69]), "+f"(d[70]), "+f"(d[71]), "+f"(d[72]), "+f"(d[73]), "+f"(d[74]), "+f"(d[75]), "+f"(d[76]), "+f"(d[77]),
          "+f"(d[78]), "+f"(d[79]), "+f"(d[80]), "+f"(d[81]), "+f"(d[82]), "+f"(d[83]), "+f"(d[84]), "+f"(d[85]), "+f"(d[86]), "+f"(d[87]), "+f"(d[88]),
          "+f"(d[89]), "+f"(d[90]), "+f"(d[91]), "+f"(d[92]), "+f"(d[93]), "+f"(d[94]), "+f"(d[95]), "+f"(d[96]), "+f"(d[97]), "+f"(d[98]), "+f"(d[99]),
          "+f"(d[100]), "+f"(d[101]), "+f"(d[102]), "+f"(d[103]), "+f"(d[104]), "+f"(d[105]), "+f"(d[106]), "+f"(d[107]), "+f"(d[108]), "+f"(d[109]),
          "+f"(d[110]), "+f"(d[111])
        : "r"(alo), "r"(blo), "r"(scale_d));
}
__device__ __forceinline__ void mma_qk0(float (&d)[32], uint32_t alo, uint32_t blo) {
    asm volatile("{\n.reg .pred p;\n.reg .b64 da, db;\nsetp.ne.b32 p, 0, 0;\nmov.b64 da, {%32, 0x80000020};\nmov.b64 db, {%33, 0x80000020};\n"
        "wgmma.mma_async.sync.aligned.m64n64k16.f32.bf16.bf16 {"
        "%0, %1, %2, %3, %4, %5, %6, %7, %8, %9, %10, %11, %12, %13, %14, %15, %16, %17, %18, %19, %20, %21, %22, %23, %24, %25, %26, %27, %28, %29, %30, %31 "
        "}, da, db, p, 1, 1, 0, 0;\n}\n"
        : "=f"(d[0]), "=f"(d[1]), "=f"(d[2]), "=f"(d[3]), "=f"(d[4]), "=f"(d[5]), "=f"(d[6]), "=f"(d[7]), "=f"(d[8]), "=f"(d[9]), "=f"(d[10]), "=f"(d[11]),
          "=f"(d[12]), "=f"(d[13]), "=f"(d[14]), "=f"(d[15]), "=f"(d[16]), "=f"(d[17]), "=f"(d[18]), "=f"(d[19]), "=f"(d[20]), "=f"(d[21]), "=f"(d[22]),
          "=f"(d[23]), "=f"(d[24]), "=f"(d[25]), "=f"(d[26]), "=f"(d[27]), "=f"(d[28]), "=f"(d[29]), "=f"(d[30]), "=f"(d[31])
        : "r"(alo), "r"(blo));
}
__device__ __forceinline__ void mma_qk1(float (&d)[32], uint32_t alo, uint32_t blo, int scale_d) {
    asm volatile("{\n.reg .pred p;\n.reg .b64 da, db;\nsetp.ne.b32 p, %34, 0;\nmov.b64 da, {%32, 0x80000020};\nmov.b64 db, {%33, 0x80000020};\n"
        "wgmma.mma_async.sync.aligned.m64n64k16.f32.bf16.bf16 {"
        "%0, %1, %2, %3, %4, %5, %6, %7, %8, %9, %10, %11, %12, %13, %14, %15, %16, %17, %18, %19, %20, %21, %22, %23, %24, %25, %26, %27, %28, %29, %30, %31 "
        "}, da, db, p, 1, 1, 0, 0;\n}\n"
        : "+f"(d[0]), "+f"(d[1]), "+f"(d[2]), "+f"(d[3]), "+f"(d[4]), "+f"(d[5]), "+f"(d[6]), "+f"(d[7]), "+f"(d[8]), "+f"(d[9]), "+f"(d[10]), "+f"(d[11]),
          "+f"(d[12]), "+f"(d[13]), "+f"(d[14]), "+f"(d[15]), "+f"(d[16]), "+f"(d[17]), "+f"(d[18]), "+f"(d[19]), "+f"(d[20]), "+f"(d[21]), "+f"(d[22]),
          "+f"(d[23]), "+f"(d[24]), "+f"(d[25]), "+f"(d[26]), "+f"(d[27]), "+f"(d[28]), "+f"(d[29]), "+f"(d[30]), "+f"(d[31])
        : "r"(alo), "r"(blo), "r"(scale_d));
}
__device__ __forceinline__ void mma_pv(float (&d)[20], uint32_t a0, uint32_t a1, uint32_t a2, uint32_t a3, uint32_t blo, int scale_d) {
    asm volatile("{\n.reg .pred p;\n.reg .b64 da, db;\nsetp.ne.b32 p, %25, 0;\nmov.b64 db, {%24, 0x80000020};\n"
        "wgmma.mma_async.sync.aligned.m64n40k16.f32.bf16.bf16 {"
        "%0, %1, %2, %3, %4, %5, %6, %7, %8, %9, %10, %11, %12, %13, %14, %15, %16, %17, %18, %19 "
        "}, {%20, %21, %22, %23}, db, p, 1, 1, 1;\n}\n"
        : "+f"(d[0]), "+f"(d[1]), "+f"(d[2]), "+f"(d[3]), "+f"(d[4]), "+f"(d[5]), "+f"(d[6]), "+f"(d[7]), "+f"(d[8]), "+f"(d[9]), "+f"(d[10]), "+f"(d[11]),
          "+f"(d[12]), "+f"(d[13]), "+f"(d[14]), "+f"(d[15]), "+f"(d[16]), "+f"(d[17]), "+f"(d[18]), "+f"(d[19])
        : "r"(a0), "r"(a1), "r"(a2), "r"(a3), "r"(blo), "r"(scale_d));
}

__device__ __forceinline__ float warp_sum(float v) {
#pragma unroll
    for (int o = 16; o > 0; o >>= 1) v += __shfl_xor_sync(0xffffffffu, v, o);
    return v;
}
template <bool TWICE>
__global__ void __launch_bounds__(256) ln_kernel(const bf16* __restrict__ in, bf16* __restrict__ out) {
    pdl_launch();
    if (TWICE) pdl_wait();
    if (!TWICE && blockIdx.x == 0 && threadIdx.x < 3 * NH) g_norm[threadIdx.x] = 0u;
    TL(TWICE ? 4 : 0, 0);
    const int row = blockIdx.x * 8 + (threadIdx.x >> 5), lane = threadIdx.x & 31;
    const uint4* src = reinterpret_cast<const uint4*>(in + (size_t)row * DM);
    uint4 v[4];
#pragma unroll
    for (int i = 0; i < 4; i++) v[i] = src[lane + 32 * i];
    float f[32];
#pragma unroll
    for (int i = 0; i < 4; i++) {
        f[8 * i + 0] = bf_lo(v[i].x); f[8 * i + 1] = bf_hi(v[i].x); f[8 * i + 2] = bf_lo(v[i].y); f[8 * i + 3] = bf_hi(v[i].y);
        f[8 * i + 4] = bf_lo(v[i].z); f[8 * i + 5] = bf_hi(v[i].z); f[8 * i + 6] = bf_lo(v[i].w); f[8 * i + 7] = bf_hi(v[i].w);
    }
#pragma unroll
    for (int pass = 0; pass < (TWICE ? 2 : 1); pass++) {
        float s = 0.f;
#pragma unroll
        for (int i = 0; i < 32; i++) s += f[i];
        const float mean = warp_sum(s) * (1.f / DM);
        float q = 0.f;
#pragma unroll
        for (int i = 0; i < 32; i++) { f[i] -= mean; q += f[i] * f[i]; }
        const float rstd = rsqrtf(warp_sum(q) * (1.f / DM) + 1e-5f);
#pragma unroll
        for (int i = 0; i < 32; i++) f[i] *= rstd;
    }
    uint4* dst = reinterpret_cast<uint4*>(out + (size_t)row * DM);
#pragma unroll
    for (int i = 0; i < 4; i++) {
        uint4 o;
        o.x = pack_bf16(f[8 * i + 0], f[8 * i + 1]); o.y = pack_bf16(f[8 * i + 2], f[8 * i + 3]);
        o.z = pack_bf16(f[8 * i + 4], f[8 * i + 5]); o.w = pack_bf16(f[8 * i + 6], f[8 * i + 7]);
        dst[lane + 32 * i] = o;
    }
    TL(TWICE ? 4 : 0, 3);
}

struct GemmSmem { uint32_t base, full0, empty0, aux; };

template <class C>
__device__ __forceinline__ GemmSmem gemm_setup(uint8_t* smem_raw) {
    GemmSmem s;
    s.base = smem_u32(smem_raw);
    s.full0 = s.base + C::BAR_OFF; s.empty0 = s.full0 + 8 * C::STAGES; s.aux = s.empty0 + 8 * C::STAGES;
    if (threadIdx.x == 0) {
        if (s.base & 1023) __trap();
        for (int i = 0; i < C::STAGES; i++) { mbar_init(s.full0 + 8 * i, 1); mbar_init(s.empty0 + 8 * i, 8); }
        mbar_init(s.aux, 1);
        fence_barrier_init();
    }
    __syncthreads();
    return s;
}

template <class C, class P>
__device__ __forceinline__ void gemm_producer(const GemmSmem& s, const P& p, int tm, int tn) {
#pragma unroll 1
    for (int k = 0; k < C::STAGES; k++) {
        mbar_expect_tx(s.full0 + 8 * k, C::STAGE_BYTES);
        C::load_w(p, s.base + k * C::STAGE_BYTES, s.full0 + 8 * k, k, tm, tn);
    }
    pdl_wait();
    C::load_aux(p, s, tm, tn);
#pragma unroll 1
    for (int k = 0; k < C::STAGES; k++) C::load_x(p, s.base + k * C::STAGE_BYTES, s.full0 + 8 * k, k, tm, tn);
    int st = 0; uint32_t ph = 0;
#pragma unroll 1
    for (int k = C::STAGES; k < C::KSTEPS; k++) {
        mbar_wait(s.empty0 + 8 * st, ph);
        mbar_expect_tx(s.full0 + 8 * st, C::STAGE_BYTES);
        C::load_w(p, s.base + st * C::STAGE_BYTES, s.full0 + 8 * st, k, tm, tn);
        C::load_x(p, s.base + st * C::STAGE_BYTES, s.full0 + 8 * st, k, tm, tn);
        if (++st == C::STAGES) { st = 0; ph ^= 1; }
    }
}

template <class C>
__device__ __forceinline__ void gemm_mainloop(const GemmSmem& s, int wg, float (&acc)[C::MB][C::BN / 2]) {
    const int lane = threadIdx.x & 31;
    int st = 0; uint32_t ph = 0;
    int prev = 0;
#pragma unroll
    for (int m = 0; m < C::MB; m++) fence_regs(acc[m]);
#pragma unroll 1
    for (int k = 0; k < C::KSTEPS; k++) {
        mbar_wait(s.full0 + 8 * st, ph);
        const uint32_t sb = s.base + st * C::STAGE_BYTES;
        wg_fence();
#pragma unroll
        for (int kk = 0; kk < 4; kk++) {
#pragma unroll
            for (int m = 0; m < C::MB; m++) C::mma(acc[m], C::desc_a(sb, wg, m, kk), C::desc_b(sb, kk), (k | kk) != 0);
        }
        wg_commit();
        if (k > 0) { wg_wait<1>(); if (lane == 0) mbar_arrive(s.empty0 + 8 * prev); }
        prev = st;
        if (++st == C::STAGES) { st = 0; ph ^= 1; }
    }
    wg_wait<0>();
#pragma unroll
    for (int m = 0; m < C::MB; m++) fence_regs(acc[m]);
}

struct QkvParams { CUtensorMap xn, w, out; };
struct QkvCfg {
    static constexpr int MB = 2, BN = 192, KSTEPS = 16, STAGES = 4, A_BYTES = 32768, B_BYTES = 24576;
    static constexpr int STAGE_BYTES = A_BYTES + B_BYTES, BAR_OFF = STAGES * STAGE_BYTES, SMEM = BAR_OFF + 128;
    static __device__ __forceinline__ void load_w(const QkvParams& p, uint32_t sb, uint32_t bar, int k, int tm, int tn) { tma_ld4(sb + A_BYTES, &p.w, bar, 0, k * 64, 0, tn); }
    static __device__ __forceinline__ void load_x(const QkvParams& p, uint32_t sb, uint32_t bar, int k, int tm, int tn) { tma_ld2(sb, &p.xn, bar, k * 64, tm * 256); }
    static __device__ __forceinline__ void load_aux(const QkvParams&, const GemmSmem&, int, int) {}
    static __device__ __forceinline__ uint32_t desc_a(uint32_t sb, int wg, int m, int kk) { return desc_lo(sb + (wg * 128 + m * 64) * 128 + kk * 32, 16); }
    static __device__ __forceinline__ uint32_t desc_b(uint32_t sb, int kk) { return desc_lo(sb + A_BYTES + kk * 2048, 8192); }
    static __device__ __forceinline__ void mma(float (&d)[96], uint32_t a, uint32_t b, int sc) { mma_qkv(d, a, b, sc); }
};
__global__ void __launch_bounds__(384, 1) qkv_kernel(const __grid_constant__ QkvParams p) {
    extern __shared__ __align__(1024) uint8_t smem_raw[];
    pdl_launch();
    const int tm = blockIdx.x & 7, tn = blockIdx.x >> 3;
    if (threadIdx.x == 0) { prefetch_map(&p.xn); prefetch_map(&p.w); prefetch_map(&p.out); }
    const GemmSmem s = gemm_setup<QkvCfg>(smem_raw);
    const int wgi = __shfl_sync(0xffffffffu, threadIdx.x >> 7, 0);
    if (wgi == 0) {
        reg_dealloc<40>();
        if (threadIdx.x == 0) gemm_producer<QkvCfg>(s, p, tm, tn);
    } else {
        reg_alloc<232>();
        const int wg = wgi - 1, warp = (threadIdx.x >> 5) & 3, lane = threadIdx.x & 31;
        float acc[2][96];
        pdl_wait();
        TL(1, 0);
        gemm_mainloop<QkvCfg>(s, wg, acc);
        TL(1, 1);
        named_bar(1, 256);
        const float qscale = 0.17677669529663687f * 1.4426950408889634f;
        float nmax[6];
#pragma unroll
        for (int i = 0; i < 6; i++) nmax[i] = 0.f;
#pragma unroll
        for (int m = 0; m < 2; m++) {
            const int rbase = wg * 128 + m * 64 + warp * 16;
            const int arow = rbase + ((lane >> 3) & 1) * 8 + (lane & 7);
#pragma unroll
            for (int sub = 0; sub < 6; sub++) {
                float v[16];
#pragma unroll
                for (int i = 0; i < 16; i++) v[i] = (sub < 2) ? acc[m][sub * 16 + i] * qscale : acc[m][sub * 16 + i];
                float n0 = 0.f, n1 = 0.f;
#pragma unroll
                for (int j = 0; j < 4; j++) {
                    n0 += v[4 * j] * v[4 * j] + v[4 * j + 1] * v[4 * j + 1];
                    n1 += v[4 * j + 2] * v[4 * j + 2] + v[4 * j + 3] * v[4 * j + 3];
                }
                n0 += __shfl_xor_sync(0xffffffffu, n0, 1); n1 += __shfl_xor_sync(0xffffffffu, n1, 1);
                n0 += __shfl_xor_sync(0xffffffffu, n0, 2); n1 += __shfl_xor_sync(0xffffffffu, n1, 2);
                nmax[sub] = __uint_as_float(max(max(__float_as_uint(n0), __float_as_uint(n1)), __float_as_uint(nmax[sub])));
#pragma unroll
                for (int jp = 0; jp < 2; jp++) {
                    const int chunk = jp * 2 + (lane >> 4);
                    const uint32_t addr = s.base + sub * 16384 + arow * 64 + ((chunk ^ ((arow >> 1) & 3)) << 4);
                    stmatrix_x4(addr, pack_bf16(v[8 * jp], v[8 * jp + 1]), pack_bf16(v[8 * jp + 2], v[8 * jp + 3]),
                                pack_bf16(v[8 * jp + 4], v[8 * jp + 5]), pack_bf16(v[8 * jp + 6], v[8 * jp + 7]));
                }
            }
        }
        fence_proxy_async();
        named_bar(2 + wg, 128);
        if ((threadIdx.x & 127) == 0) {
#pragma unroll
            for (int sub = 0; sub < 6; sub++)
                tma_st2(&p.out, s.base + sub * 16384 + wg * 8192, 0, (sub >> 1) * (NH * SEQ) + (tn * 2 + (sub & 1)) * SEQ + tm * 256 + wg * 128);
            tma_st_commit();
        }
#pragma unroll
        for (int sub = 0; sub < 6; sub++) {
            const uint32_t mx = __reduce_max_sync(0xffffffffu, __float_as_uint(nmax[sub]));
            if (lane == 0) atomicMax(&g_norm[(sub >> 1) * NH + tn * 2 + (sub & 1)], mx);
        }
        if ((threadIdx.x & 127) == 0) tma_st_wait();
        TL(1, 3);
    }
}

struct AttnParams { CUtensorMap kv; bf16* o; };
constexpr int AT_STAGES = 8, AT_STAGE_BYTES = 16384, AT_Q_OFF = AT_STAGES * AT_STAGE_BYTES, AT_ONES_OFF = AT_Q_OFF + 32768, AT_BAR_OFF = AT_ONES_OFF + 1024, AT_SMEM = AT_BAR_OFF + 256;
constexpr int AT_TILES = 32;

__device__ __forceinline__ float ex2_poly(float x) {
    const float magic = 12582912.f;
    const float t = x + magic;
    const float f = x - (t - magic);
    float p = fmaf(f, 0.05550410866f, 0.24022650695f);
    p = fmaf(p, f, 0.69314718056f);
    p = fmaf(p, f, 1.0f);
    return __int_as_float(__float_as_int(p) + (__float_as_int(t) << 23));
}

__device__ __forceinline__ float attn_exp(float x, int i) { return ((POLY_MASK >> (i & 7)) & 1) ? ex2_poly(x) : ex2(x); }
__device__ __forceinline__ void attn_issue_tile(const AttnParams& p, uint32_t base, uint32_t full0, int g, int head) {
    const int st = g % AT_STAGES, key0 = (g & 15) * 128;
    const uint32_t bar = full0 + 8 * st, dst = base + st * AT_STAGE_BYTES;
    mbar_expect_tx(bar, AT_STAGE_BYTES);
    tma_ld2(dst, &p.kv, bar, 0, (NH + head) * SEQ + key0);
    tma_ld2(dst + 8192, &p.kv, bar, 0, (2 * NH + head) * SEQ + key0);
}
__device__ __forceinline__ void attn_qk(float (&sacc)[32], uint32_t q_lo, uint32_t k_lo) {
    mma_qk0(sacc, q_lo, k_lo);
    mma_qk1(sacc, q_lo + 2, k_lo + 2, 1);
}
constexpr uint32_t PV_STEP = 64u - (64u << 16);
__device__ __forceinline__ void attn_pv(float (&o)[20], const uint32_t (&pr)[16], uint32_t v_lo, int first) {
#pragma unroll
    for (int kk = 0; kk < 4; kk++)
        mma_pv(o, pr[4 * kk], pr[4 * kk + 1], pr[4 * kk + 2], pr[4 * kk + 3], v_lo + kk * PV_STEP, (kk > 0) || !first);
}
__device__ __forceinline__ void attn_store_o(const float (&o)[20], const AttnParams& p, int head, int row0, int lane) {
    const float r0 = 1.f / o[16], r1 = 1.f / o[18];
    uint32_t* op = reinterpret_cast<uint32_t*>(p.o + (size_t)row0 * DM + head * HD) + (lane & 3);
#pragma unroll
    for (int j = 0; j < 4; j++) {
        op[j * 4] = pack_bf16(o[4 * j] * r0, o[4 * j + 1] * r0);
        op[j * 4 + 8 * (DM / 2)] = pack_bf16(o[4 * j + 2] * r1, o[4 * j + 3] * r1);
    }
}
__device__ __forceinline__ void attn_refill(const AttnParams& p, uint32_t base, uint32_t full0, uint32_t empty0, int g, int head) {
    if (threadIdx.x == 0 && g >= 4 && g + 4 < AT_TILES) {
        const int gp = g - 4;
        mbar_wait(empty0 + 8 * (gp % AT_STAGES), (gp / AT_STAGES) & 1);
        attn_issue_tile(p, base, full0, g + 4, head);
    }
    __syncwarp();
}

__device__ __forceinline__ void attn_fast(const AttnParams& p, uint32_t base, uint32_t full0, uint32_t empty0, int head, int qchunk) {
    const int wg = __shfl_sync(0xffffffffu, threadIdx.x >> 7, 0), warp = (threadIdx.x >> 5) & 3, lane = threadIdx.x & 31;
    const uint32_t k_lo0 = desc_lo(base, 16), v_lo0 = desc_lo(base + 8192, AT_ONES_OFF - 8192);
#pragma unroll 1
    for (int pass = 0; pass < 2; pass++) {
        const int row0 = qchunk * 512 + pass * 256 + wg * 64 + warp * 16 + (lane >> 2);
        const uint32_t q = desc_lo(base + AT_Q_OFF + (pass * 256 + wg * 64) * 64, 16);
        float o[20];
        const int g0 = pass * 16;
#pragma unroll 1
        for (int j = 0; j < 16; j++) {
            const int g = g0 + j;
            const int st = g % AT_STAGES;
            const uint32_t kb = k_lo0 + st * (AT_STAGE_BYTES >> 4), vb = v_lo0 + st * 16 * PV_STEP;
            attn_refill(p, base, full0, empty0, g, head);
            mbar_wait(full0 + 8 * st, (g / AT_STAGES) & 1);
            float sa[32], sb[32], e[32];
            uint32_t pr[16];
            wg_fence();
            attn_qk(sa, q, kb);
            wg_commit();
            attn_qk(sb, q, kb + 256);
            wg_commit();
            wg_wait<1>();
            fence_regs(sa);
            if (j > 0 && lane == 0) mbar_arrive(empty0 + 8 * ((g - 1) % AT_STAGES));
#pragma unroll
            for (int i = 0; i < 16; i++) pr[i] = pack_bf16(attn_exp(sa[2 * i], 2 * i), attn_exp(sa[2 * i + 1], 2 * i + 1));
            wg_fence();
            attn_pv(o, pr, vb, j == 0);
            wg_commit();
            wg_wait<1>();
            fence_regs(sb);
#pragma unroll
            for (int i = 0; i < 32; i++) e[i] = attn_exp(sb[i], i);
            wg_wait<0>();
#pragma unroll
            for (int i = 0; i < 16; i++) pr[i] = pack_bf16(e[2 * i], e[2 * i + 1]);
            wg_fence();
            attn_pv(o, pr, vb + 4 * PV_STEP, 0);
            wg_commit();
        }
        wg_wait<0>();
        fence_regs(o);
        if (lane == 0) mbar_arrive(empty0 + 8 * ((g0 + 15) % AT_STAGES));
        attn_store_o(o, p, head, row0, lane);
    }
}

__device__ __forceinline__ void attn_safe(const AttnParams& p, uint32_t base, uint32_t full0, uint32_t empty0, int head, int qchunk) {
    const int wg = __shfl_sync(0xffffffffu, threadIdx.x >> 7, 0), warp = (threadIdx.x >> 5) & 3, lane = threadIdx.x & 31;
    const uint32_t k_lo0 = desc_lo(base, 16), v_lo0 = desc_lo(base + 8192, AT_ONES_OFF - 8192);
#pragma unroll 1
    for (int pass = 0; pass < 2; pass++) {
        const int row0 = qchunk * 512 + pass * 256 + wg * 64 + warp * 16 + (lane >> 2);
        const uint32_t q = desc_lo(base + AT_Q_OFF + (pass * 256 + wg * 64) * 64, 16);
        float o[20];
#pragma unroll
        for (int i = 0; i < 20; i++) o[i] = 0.f;
        float m0 = -INFINITY, m1 = -INFINITY;
#pragma unroll 1
        for (int t = 0; t < 32; t++) {
            const int g = pass * 16 + (t >> 1), half = t & 1;
            const int st = g % AT_STAGES;
            const uint32_t kb = k_lo0 + st * (AT_STAGE_BYTES >> 4), vb = v_lo0 + st * 16 * PV_STEP;
            if (half == 0) { attn_refill(p, base, full0, empty0, g, head); mbar_wait(full0 + 8 * st, (g / AT_STAGES) & 1); }
            float cur[32];
            wg_fence();
            attn_qk(cur, q, kb + half * 256);
            wg_commit();
            wg_wait<0>();
            fence_regs(cur);
            float x0 = cur[0], x1 = cur[2];
#pragma unroll
            for (int i = 0; i < 8; i++) { x0 = fmaxf(x0, fmaxf(cur[4 * i], cur[4 * i + 1])); x1 = fmaxf(x1, fmaxf(cur[4 * i + 2], cur[4 * i + 3])); }
            x0 = fmaxf(x0, __shfl_xor_sync(0xffffffffu, x0, 1)); x1 = fmaxf(x1, __shfl_xor_sync(0xffffffffu, x1, 1));
            x0 = fmaxf(x0, __shfl_xor_sync(0xffffffffu, x0, 2)); x1 = fmaxf(x1, __shfl_xor_sync(0xffffffffu, x1, 2));
            const float n0 = fmaxf(m0, x0), n1 = fmaxf(m1, x1);
            const float a0 = ex2(m0 - n0), a1 = ex2(m1 - n1);
            m0 = n0; m1 = n1;
            uint32_t pr[16];
#pragma unroll
            for (int i = 0; i < 8; i++) {
                pr[2 * i] = pack_bf16(ex2(cur[4 * i] - n0), ex2(cur[4 * i + 1] - n0));
                pr[2 * i + 1] = pack_bf16(ex2(cur[4 * i + 2] - n1), ex2(cur[4 * i + 3] - n1));
            }
#pragma unroll
            for (int i = 0; i < 5; i++) { o[4 * i] *= a0; o[4 * i + 1] *= a0; o[4 * i + 2] *= a1; o[4 * i + 3] *= a1; }
            wg_fence();
            attn_pv(o, pr, vb + half * 4 * PV_STEP, 0);
            wg_commit();
            wg_wait<0>();
            fence_regs(o);
            if (half == 1 && lane == 0) mbar_arrive(empty0 + 8 * st);
        }
        attn_store_o(o, p, head, row0, lane);
    }
}

__global__ void __launch_bounds__(512, 1) attn_kernel(const __grid_constant__ AttnParams p) {
    extern __shared__ __align__(1024) uint8_t smem_raw[];
    pdl_launch();
    const uint32_t base = smem_u32(smem_raw);
    const uint32_t full0 = base + AT_BAR_OFF, empty0 = full0 + 8 * AT_STAGES;
    const int head = blockIdx.x >> 2, qchunk = blockIdx.x & 3;
    if (threadIdx.x == 0) {
        if (base & 1023) __trap();
        prefetch_map(&p.kv);
        for (int i = 0; i < AT_STAGES; i++) { mbar_init(full0 + 8 * i, 1); mbar_init(empty0 + 8 * i, 16); }
        mbar_init(empty0 + 8 * AT_STAGES, 1);
        fence_barrier_init();
    }
    if (threadIdx.x < 256) reinterpret_cast<uint32_t*>(smem_raw + AT_ONES_OFF)[threadIdx.x] = 0x3F803F80u;
    fence_proxy_async();
    __syncthreads();
    pdl_wait();
    TL(2, 0);
    if (threadIdx.x == 0) {
        const uint32_t qbar = empty0 + 8 * AT_STAGES;
        mbar_expect_tx(qbar, 32768);
        for (int i = 0; i < 4; i++) tma_ld2(base + AT_Q_OFF + i * 8192, &p.kv, qbar, 0, head * SEQ + qchunk * 512 + i * 128);
        for (int g = 0; g < AT_STAGES; g++) attn_issue_tile(p, base, full0, g, head);
    }
    __syncwarp();
    const float qn = __uint_as_float(g_norm[head]), kn = __uint_as_float(g_norm[NH + head]), vn = __uint_as_float(g_norm[2 * NH + head]);
    const bool bounded = (qn * kn <= 1.0e4f) && (vn <= 1.0e9f);
    mbar_wait(empty0 + 8 * AT_STAGES, 0);
    if (bounded) attn_fast(p, base, full0, empty0, head, qchunk);
    else attn_safe(p, base, full0, empty0, head, qchunk);
    TL(2, 3);
}

struct ResParams { CUtensorMap a, b, res, out; const bf16* bias; };
template <bool MIX2>
struct ResCfg {
    static constexpr int MB = 1, BN = 128, KSTEPS = MIX2 ? 56 : 16, STAGES = 6, A_BYTES = 16384, B_BYTES = 16384;
    static constexpr int STAGE_BYTES = A_BYTES + B_BYTES, STG_OFF = STAGES * STAGE_BYTES, BAR_OFF = STG_OFF + 32768, SMEM = BAR_OFF + 128;
    static __device__ __forceinline__ void load_w(const ResParams& p, uint32_t sb, uint32_t bar, int k, int tm, int tn) {
        if (MIX2) tma_ld3(sb, &p.a, bar, 0, k * 64, tm * 2);
        else tma_ld3(sb + A_BYTES, &p.b, bar, 0, k * 64, tn * 2);
    }
    static __device__ __forceinline__ void load_x(const ResParams& p, uint32_t sb, uint32_t bar, int k, int tm, int tn) {
        if (MIX2) tma_ld2(sb + A_BYTES, &p.b, bar, k * 64, tn * 128);
        else tma_ld2(sb, &p.a, bar, k * 64, tm * 128);
    }
    static __device__ __forceinline__ void load_aux(const ResParams& p, const GemmSmem& s, int tm, int tn) {
        mbar_expect_tx(s.aux, 32768);
        tma_ld2(s.base + STG_OFF, &p.res, s.aux, tn * 128, tm * 128);
        tma_ld2(s.base + STG_OFF + 16384, &p.res, s.aux, tn * 128 + 64, tm * 128);
    }
    static __device__ __forceinline__ uint32_t desc_a(uint32_t sb, int wg, int m, int kk) {
        return MIX2 ? desc_lo(sb + wg * 8192 + kk * 2048, 8192) : desc_lo(sb + wg * 8192 + kk * 32, 16);
    }
    static __device__ __forceinline__ uint32_t desc_b(uint32_t sb, int kk) {
        return MIX2 ? desc_lo(sb + A_BYTES + kk * 32, 16) : desc_lo(sb + A_BYTES + kk * 2048, 8192);
    }
    static __device__ __forceinline__ void mma(float (&d)[64], uint32_t a, uint32_t b, int sc) {
        if (MIX2) mma_mix2(d, a, b, sc); else mma_wo(d, a, b, sc);
    }
};
template <bool MIX2>
__global__ void __launch_bounds__(384, 1) res_gemm_kernel(const __grid_constant__ ResParams p) {
    using C = ResCfg<MIX2>;
    extern __shared__ __align__(1024) uint8_t smem_raw[];
    pdl_launch();
    const int tm = blockIdx.x & 15, tn = blockIdx.x >> 4;
    if (threadIdx.x == 0) { prefetch_map(&p.a); prefetch_map(&p.b); prefetch_map(&p.res); prefetch_map(&p.out); }
    const GemmSmem s = gemm_setup<C>(smem_raw);
    const int wgi = __shfl_sync(0xffffffffu, threadIdx.x >> 7, 0);
    if (wgi == 0) {
        reg_dealloc<40>();
        if (threadIdx.x == 0) gemm_producer<C>(s, p, tm, tn);
    } else {
        reg_alloc<232>();
        const int wg = wgi - 1, warp = (threadIdx.x >> 5) & 3, lane = threadIdx.x & 31;
        float acc[1][64];
        pdl_wait();
        TL(MIX2 ? 6 : 3, 0);
        const int r0 = wg * 64 + warp * 16 + (lane >> 2);
        float b0 = 0.f, b1 = 0.f;
        if (MIX2) { b0 = __bfloat162float(p.bias[tm * 128 + r0]); b1 = __bfloat162float(p.bias[tm * 128 + r0 + 8]); }
        gemm_mainloop<C>(s, wg, acc);
        TL(MIX2 ? 6 : 3, 1);
        mbar_wait(s.aux, 0);
        uint8_t* stg = smem_raw + C::STG_OFF;
#pragma unroll
        for (int j = 0; j < 16; j++) {
            const int off = (j >> 3) * 16384 + r0 * 128 + (((j & 7) ^ (r0 & 7)) << 4) + (lane & 3) * 4;
            uint32_t* p0 = reinterpret_cast<uint32_t*>(stg + off);
            uint32_t* p1 = reinterpret_cast<uint32_t*>(stg + off + 8 * 128);
            const uint32_t x0 = *p0, x1 = *p1;
            *p0 = pack_bf16(acc[0][4 * j] + b0 + bf_lo(x0), acc[0][4 * j + 1] + b0 + bf_hi(x0));
            *p1 = pack_bf16(acc[0][4 * j + 2] + b1 + bf_lo(x1), acc[0][4 * j + 3] + b1 + bf_hi(x1));
        }
        fence_proxy_async();
        named_bar(2 + wg, 128);
        if ((threadIdx.x & 127) == 0) {
            tma_st2(&p.out, s.base + C::STG_OFF + wg * 8192, tn * 128, tm * 128 + wg * 64);
            tma_st2(&p.out, s.base + C::STG_OFF + 16384 + wg * 8192, tn * 128 + 64, tm * 128 + wg * 64);
            tma_st_commit();
            tma_st_wait();
        }
        TL(MIX2 ? 6 : 3, 3);
    }
}

struct Mix1Params { CUtensorMap hn, w1, out; const bf16* bias; };
struct Mix1Cfg {
    static constexpr int MB = 1, BN = 224, KSTEPS = 32, STAGES = 5, A_BYTES = 16384, B_BYTES = 28672;
    static constexpr int STAGE_BYTES = A_BYTES + B_BYTES, BIAS_OFF = STAGES * STAGE_BYTES, BAR_OFF = BIAS_OFF + 1024, SMEM = BAR_OFF + 128;
    static __device__ __forceinline__ void load_w(const Mix1Params& p, uint32_t sb, uint32_t bar, int k, int tm, int tn) { tma_ld3(sb + A_BYTES, &p.w1, bar, 0, k * 64, tn * 7); }
    static __device__ __forceinline__ void load_x(const Mix1Params& p, uint32_t sb, uint32_t bar, int k, int tm, int tn) { tma_ld3(sb, &p.hn, bar, 0, k * 64, tm * 2); }
    static __device__ __forceinline__ void load_aux(const Mix1Params&, const GemmSmem&, int, int) {}
    static __device__ __forceinline__ uint32_t desc_a(uint32_t sb, int wg, int m, int kk) { return desc_lo(sb + wg * 8192 + kk * 2048, 8192); }
    static __device__ __forceinline__ uint32_t desc_b(uint32_t sb, int kk) { return desc_lo(sb + A_BYTES + kk * 1024, 4096); }
    static __device__ __forceinline__ void mma(float (&d)[112], uint32_t a, uint32_t b, int sc) { mma_mix1(d, a, b, sc); }
};
__global__ void __launch_bounds__(384, 1) mix1_kernel(const __grid_constant__ Mix1Params p) {
    using C = Mix1Cfg;
    extern __shared__ __align__(1024) uint8_t smem_raw[];
    pdl_launch();
    const int tm = blockIdx.x & 7, tn = blockIdx.x >> 3;
    if (threadIdx.x == 0) { prefetch_map(&p.hn); prefetch_map(&p.w1); prefetch_map(&p.out); }
    float* sbias = reinterpret_cast<float*>(smem_raw + C::BIAS_OFF);
    if (threadIdx.x < 224) sbias[threadIdx.x] = __bfloat162float(p.bias[tn * 224 + threadIdx.x]);
    const GemmSmem s = gemm_setup<C>(smem_raw);
    const int wgi = __shfl_sync(0xffffffffu, threadIdx.x >> 7, 0);
    if (wgi == 0) {
        reg_dealloc<40>();
        if (threadIdx.x == 0) gemm_producer<C>(s, p, tm, tn);
    } else {
        reg_alloc<232>();
        const int wg = wgi - 1, warp = (threadIdx.x >> 5) & 3, lane = threadIdx.x & 31;
        float acc[1][112];
        pdl_wait();
        TL(5, 0);
        gemm_mainloop<C>(s, wg, acc);
        TL(5, 1);
        named_bar(1, 256);
        const int arow = warp * 16 + ((lane >> 3) & 1) * 8 + (lane & 7);
        const uint32_t stg = s.base + wg * 28672;
#pragma unroll
        for (int jp = 0; jp < 14; jp++) {
            float v[8];
#pragma unroll
            for (int h = 0; h < 2; h++) {
                const float2 bb = *reinterpret_cast<const float2*>(sbias + (jp * 2 + h) * 8 + (lane & 3) * 2);
#pragma unroll
                for (int i = 0; i < 4; i++) {
                    const float x = acc[0][jp * 8 + h * 4 + i] + ((i & 1) ? bb.y : bb.x);
                    const float inner = x * fmaf(x * x, 0.0356774081363f, 0.7978845608029f);
                    const float hx = 0.5f * x;
                    v[h * 4 + i] = fmaf(hx, tanh_fast(inner), hx);
                }
            }
            const int j = jp * 2 + (lane >> 4);
            const uint32_t addr = stg + (j >> 2) * 4096 + arow * 64 + (((j & 3) ^ ((arow >> 1) & 3)) << 4);
            stmatrix_x4(addr, pack_bf16(v[0], v[1]), pack_bf16(v[2], v[3]), pack_bf16(v[4], v[5]), pack_bf16(v[6], v[7]));
        }
        fence_proxy_async();
        named_bar(2 + wg, 128);
        if ((threadIdx.x & 127) == 0) {
            tma_st3(&p.out, stg, 0, tm * 128 + wg * 64, tn * 7);
            tma_st_commit();
            tma_st_wait();
        }
        TL(5, 3);
    }
}

typedef CUresult (*EncodeFn)(CUtensorMap*, CUtensorMapDataType, cuuint32_t, void*, const cuuint64_t*, const cuuint64_t*, const cuuint32_t*,
                             const cuuint32_t*, CUtensorMapInterleave, CUtensorMapSwizzle, CUtensorMapL2promotion, CUtensorMapFloatOOBfill);
EncodeFn g_encode;

void make_map(CUtensorMap* m, const void* ptr, int rank, const uint64_t* dims, const uint64_t* strides_bytes, const uint32_t* box, CUtensorMapSwizzle swz) {
    cuuint64_t d[5], st[5]; cuuint32_t b[5], es[5];
    for (int i = 0; i < rank; i++) { d[i] = dims[i]; b[i] = box[i]; es[i] = 1; }
    for (int i = 0; i + 1 < rank; i++) st[i] = strides_bytes[i];
    CUresult r = g_encode(m, CU_TENSOR_MAP_DATA_TYPE_BFLOAT16, rank, const_cast<void*>(ptr), d, st, b, es, CU_TENSOR_MAP_INTERLEAVE_NONE, swz,
                          CU_TENSOR_MAP_L2_PROMOTION_L2_128B, CU_TENSOR_MAP_FLOAT_OOB_FILL_NONE);
    if (r != CUDA_SUCCESS) fprintf(stderr, "cuTensorMapEncodeTiled failed: %d\n", (int)r);
}
void map2d(CUtensorMap* m, const void* ptr, uint64_t cols, uint64_t rows, uint32_t bc, uint32_t br, CUtensorMapSwizzle swz) {
    uint64_t dims[2] = {cols, rows}, st[1] = {cols * 2}; uint32_t box[2] = {bc, br};
    make_map(m, ptr, 2, dims, st, box, swz);
}
void map3d(CUtensorMap* m, const void* ptr, uint64_t cols, uint64_t rows, uint32_t inner, uint32_t br, uint32_t nblk, CUtensorMapSwizzle swz) {
    uint64_t dims[3] = {inner, rows, cols / inner}, st[2] = {cols * 2, (uint64_t)inner * 2}; uint32_t box[3] = {inner, br, nblk};
    make_map(m, ptr, 3, dims, st, box, swz);
}

template <class... KArgs, class... Args>
void launch(void (*kern)(KArgs...), int grid, int block, int smem, bool pdl, Args&&... args) {
    cudaLaunchConfig_t cfg = {};
    cfg.gridDim = dim3(grid); cfg.blockDim = dim3(block); cfg.dynamicSmemBytes = smem; cfg.stream = 0;
    cudaLaunchAttribute at[1];
    at[0].id = cudaLaunchAttributeProgrammaticStreamSerialization; at[0].val.programmaticStreamSerializationAllowed = 1;
    cfg.attrs = at; cfg.numAttrs = pdl ? 1 : 0;
    cudaError_t e = cudaLaunchKernelEx(&cfg, kern, KArgs(args)...);
    if (e != cudaSuccess) fprintf(stderr, "launch failed: %s\n", cudaGetErrorString(e));
}

struct HostState {
    bool ready;
    const void* key[9];
    QkvParams qkv; AttnParams attn; ResParams wo, mix2; Mix1Params mix1;
    bf16 *xn, *qkvp, *o, *h, *hn, *u;
};
HostState g_hs;

}

#define USE_PDL 1

extern "C" void kernel_launch(void* const* d_in, const int* in_sizes, int n_in, void* d_out, int out_size) {
    const bf16* x = (const bf16*)d_in[0];
    const bf16* wqkv = (const bf16*)d_in[1];
    const bf16* wo = (const bf16*)d_in[2];
    const bf16* w1 = (const bf16*)d_in[4];
    const bf16* b1 = (const bf16*)d_in[5];
    const bf16* w2 = (const bf16*)d_in[6];
    const bf16* b2 = (const bf16*)d_in[7];
    HostState& hs = g_hs;
    bool same = hs.ready;
    for (int i = 0; i < 8 && same; i++) same = (hs.key[i] == d_in[i]);
    same = same && hs.key[8] == d_out;
    if (!same) {
        if (!g_encode) {
            void* fn = nullptr; cudaDriverEntryPointQueryResult qr;
            cudaGetDriverEntryPoint("cuTensorMapEncodeTiled", &fn, cudaEnableDefault, &qr);
            g_encode = (EncodeFn)fn;
            cudaFuncSetAttribute(qkv_kernel, cudaFuncAttributeMaxDynamicSharedMemorySize, QkvCfg::SMEM);
            cudaFuncSetAttribute(attn_kernel, cudaFuncAttributeMaxDynamicSharedMemorySize, AT_SMEM);
            cudaFuncSetAttribute(res_gemm_kernel<false>, cudaFuncAttributeMaxDynamicSharedMemorySize, ResCfg<false>::SMEM);
            cudaFuncSetAttribute(res_gemm_kernel<true>, cudaFuncAttributeMaxDynamicSharedMemorySize, ResCfg<true>::SMEM);
            cudaFuncSetAttribute(mix1_kernel, cudaFuncAttributeMaxDynamicSharedMemorySize, Mix1Cfg::SMEM);
        }
        cudaGetSymbolAddress((void**)&hs.xn, g_xn); cudaGetSymbolAddress((void**)&hs.qkvp, g_qkv); cudaGetSymbolAddress((void**)&hs.o, g_o);
        cudaGetSymbolAddress((void**)&hs.h, g_h); cudaGetSymbolAddress((void**)&hs.hn, g_hn); cudaGetSymbolAddress((void**)&hs.u, g_u);
        const CUtensorMapSwizzle S128 = CU_TENSOR_MAP_SWIZZLE_128B, S64 = CU_TENSOR_MAP_SWIZZLE_64B;
        map2d(&hs.qkv.xn, hs.xn, DM, SEQ, 64, 256, S128);
        {
            uint64_t dims[4] = {64, (uint64_t)DM, 3, 16}, st[3] = {3 * DM * 2, DM * 2, 128}; uint32_t box[4] = {64, 64, 3, 1};
            make_map(&hs.qkv.w, wqkv, 4, dims, st, box, S128);
        }
        map2d(&hs.qkv.out, hs.qkvp, HD, 3 * NH * SEQ, 32, 128, S64);
        hs.attn.kv = hs.qkv.out; hs.attn.o = hs.o;
        map2d(&hs.wo.a, hs.o, DM, SEQ, 64, 128, S128);
        map3d(&hs.wo.b, wo, DM, DM, 64, 64, 2, S128);
        map2d(&hs.wo.res, x, DM, SEQ, 64, 128, S128);
        map2d(&hs.wo.out, hs.h, DM, SEQ, 64, 64, S128);
        hs.wo.bias = nullptr;
        map3d(&hs.mix1.hn, hs.hn, DM, SEQ, 64, 64, 2, S128);
        map3d(&hs.mix1.w1, w1, FF, SEQ, 32, 64, 7, S64);
        map3d(&hs.mix1.out, hs.u, FF, DM, 32, 64, 7, S64);
        hs.mix1.bias = b1;
        map3d(&hs.mix2.a, w2, SEQ, FF, 64, 64, 2, S128);
        map2d(&hs.mix2.b, hs.u, FF, DM, 64, 128, S128);
        map2d(&hs.mix2.res, hs.h, DM, SEQ, 64, 128, S128);
        map2d(&hs.mix2.out, d_out, DM, SEQ, 64, 64, S128);
        hs.mix2.bias = b2;
        for (int i = 0; i < 8; i++) hs.key[i] = d_in[i];
        hs.key[8] = d_out;
        hs.ready = true;
    }
    const bool pdl = USE_PDL;
    launch(ln_kernel<false>, SEQ / 8, 256, 0, false, x, hs.xn);
    launch(qkv_kernel, 128, 384, QkvCfg::SMEM, pdl, hs.qkv);
    launch(attn_kernel, 128, 512, AT_SMEM, pdl, hs.attn);
    launch(res_gemm_kernel<false>, 128, 384, ResCfg<false>::SMEM, pdl, hs.wo);
    launch(ln_kernel<true>, SEQ / 8, 256, 0, pdl, (const bf16*)hs.h, hs.hn);
    launch(mix1_kernel, 128, 384, Mix1Cfg::SMEM, pdl, hs.mix1);
    launch(res_gemm_kernel<true>, 128, 384, ResCfg<true>::SMEM, pdl, hs.mix2);
}
```

```cpp
#include <cuda_runtime.h>
#include <cuda_bf16.h>
#include <cuda.h>
#include <stdint.h>
#include <stdio.h>

typedef __nv_bfloat16 bf16;

namespace {

#define SKEW 0
#define POLY_MASK 0x12492449u
constexpr int SEQ = 2048, DM = 1024, NH = 32, HD = 32, FF = 3584;

__device__ __align__(1024) bf16 g_xn[SEQ * DM];
__device__ __align__(1024) bf16 g_qkv[3 * NH * SEQ * HD];
__device__ __align__(1024) bf16 g_o[SEQ * DM];
__device__ __align__(1024) bf16 g_h[SEQ * DM];
__device__ __align__(1024) bf16 g_hn[SEQ * DM];
__device__ __align__(1024) bf16 g_u[DM * FF];
__device__ uint32_t g_norm[3 * NH];

#define TL(kern, slot)

__device__ __forceinline__ uint32_t smem_u32(const void* p) { return (uint32_t)__cvta_generic_to_shared(p); }
__device__ __forceinline__ void mbar_init(uint32_t bar, uint32_t cnt) { asm volatile("mbarrier.init.shared::cta.b64 [%0], %1;" :: "r"(bar), "r"(cnt) : "memory"); }
__device__ __forceinline__ void mbar_expect_tx(uint32_t bar, uint32_t bytes) { asm volatile("mbarrier.arrive.expect_tx.shared::cta.b64 _, [%0], %1;" :: "r"(bar), "r"(bytes) : "memory"); }
__device__ __forceinline__ void mbar_arrive(uint32_t bar) { asm volatile("mbarrier.arrive.shared::cta.b64 _, [%0];" :: "r"(bar) : "memory"); }
__device__ __forceinline__ void mbar_wait(uint32_t bar, uint32_t parity) {
    asm volatile("{\n.reg .pred p;\nWAIT_%=:\nmbarrier.try_wait.parity.shared::cta.b64 p, [%0], %1;\n@p bra DONE_%=;\nbra WAIT_%=;\nDONE_%=:\n}" :: "r"(bar), "r"(parity) : "memory");
}
__device__ __forceinline__ void fence_barrier_init() { asm volatile("fence.mbarrier_init.release.cluster;" ::: "memory"); }
__device__ __forceinline__ void fence_proxy_async() { asm volatile("fence.proxy.async.shared::cta;" ::: "memory"); }
__device__ __forceinline__ void pdl_launch() { asm volatile("griddepcontrol.launch_dependents;" ::: "memory"); }
__device__ __forceinline__ void pdl_wait() { asm volatile("griddepcontrol.wait;" ::: "memory"); }
__device__ __forceinline__ void named_bar(int id, int n) { asm volatile("bar.sync %0, %1;" :: "r"(id), "r"(n) : "memory"); }
__device__ __forceinline__ void prefetch_map(const CUtensorMap* m) { asm volatile("prefetch.tensormap [%0];" :: "l"(m) : "memory"); }

__device__ __forceinline__ void tma_ld2(uint32_t dst, const CUtensorMap* m, uint32_t bar, int c0, int c1) {
    asm volatile("cp.async.bulk.tensor.2d.shared::cluster.global.mbarrier::complete_tx::bytes [%0], [%1, {%3, %4}], [%2];"
                 :: "r"(dst), "l"(m), "r"(bar), "r"(c0), "r"(c1) : "memory");
}
__device__ __forceinline__ void tma_ld3(uint32_t dst, const CUtensorMap* m, uint32_t bar, int c0, int c1, int c2) {
    asm volatile("cp.async.bulk.tensor.3d.shared::cluster.global.mbarrier::complete_tx::bytes [%0], [%1, {%3, %4, %5}], [%2];"
                 :: "r"(dst), "l"(m), "r"(bar), "r"(c0), "r"(c1), "r"(c2) : "memory");
}
__device__ __forceinline__ void tma_ld4(uint32_t dst, const CUtensorMap* m, uint32_t bar, int c0, int c1, int c2, int c3) {
    asm volatile("cp.async.bulk.tensor.4d.shared::cluster.global.mbarrier::complete_tx::bytes [%0], [%1, {%3, %4, %5, %6}], [%2];"
                 :: "r"(dst), "l"(m), "r"(bar), "r"(c0), "r"(c1), "r"(c2), "r"(c3) : "memory");
}
__device__ __forceinline__ void tma_st2(const CUtensorMap* m, uint32_t src, int c0, int c1) {
    asm volatile("cp.async.bulk.tensor.2d.global.shared::cta.bulk_group [%0, {%2, %3}], [%1];" :: "l"(m), "r"(src), "r"(c0), "r"(c1) : "memory");
}
__device__ __forceinline__ void tma_st3(const CUtensorMap* m, uint32_t src, int c0, int c1, int c2) {
    asm volatile("cp.async.bulk.tensor.3d.global.shared::cta.bulk_group [%0, {%2, %3, %4}], [%1];" :: "l"(m), "r"(src), "r"(c0), "r"(c1), "r"(c2) : "memory");
}
__device__ __forceinline__ void tma_st_commit() { asm volatile("cp.async.bulk.commit_group;" ::: "memory"); }
__device__ __forceinline__ void tma_st_wait() { asm volatile("cp.async.bulk.wait_group.read 0;" ::: "memory"); }

__device__ __forceinline__ void wg_fence() { asm volatile("wgmma.fence.sync.aligned;" ::: "memory"); }
__device__ __forceinline__ void wg_commit() { asm volatile("wgmma.commit_group.sync.aligned;" ::: "memory"); }
template <int N> __device__ __forceinline__ void wg_wait() { asm volatile("wgmma.wait_group.sync.aligned %0;" :: "n"(N) : "memory"); }
template <int R> __device__ __forceinline__ void reg_alloc() { asm volatile("setmaxnreg.inc.sync.aligned.u32 %0;" :: "n"(R)); }
template <int R> __device__ __forceinline__ void reg_dealloc() { asm volatile("setmaxnreg.dec.sync.aligned.u32 %0;" :: "n"(R)); }
template <int N> __device__ __forceinline__ void fence_regs(float (&d)[N]) {
#pragma unroll
    for (int i = 0; i < N; i++) asm volatile("" : "+f"(d[i]) :: "memory");
}

__device__ __forceinline__ uint32_t desc_lo(uint32_t addr, uint32_t lbo) { return (addr >> 4) | ((lbo >> 4) << 16); }
__device__ __forceinline__ uint32_t pack_bf16(float lo, float hi) { uint32_t d; asm("cvt.rn.bf16x2.f32 %0, %1, %2;" : "=r"(d) : "f"(hi), "f"(lo)); return d; }
__device__ __forceinline__ float bf_lo(uint32_t v) { return __uint_as_float(v << 16); }
__device__ __forceinline__ float bf_hi(uint32_t v) { return __uint_as_float(v & 0xFFFF0000u); }
__device__ __forceinline__ void stmatrix_x4(uint32_t addr, uint32_t r0, uint32_t r1, uint32_t r2, uint32_t r3) {
    asm volatile("stmatrix.sync.aligned.m8n8.x4.shared.b16 [%0], {%1, %2, %3, %4};" :: "r"(addr), "r"(r0), "r"(r1), "r"(r2), "r"(r3) : "memory");
}
__device__ __forceinline__ float ex2(float x) { float y; asm("ex2.approx.ftz.f32 %0, %1;" : "=f"(y) : "f"(x)); return y; }
__device__ __forceinline__ float tanh_fast(float x) { float y; asm("tanh.approx.f32 %0, %1;" : "=f"(y) : "f"(x)); return y; }

__device__ __forceinline__ void mma_qkv(float (&d)[96], uint32_t alo, uint32_t blo, int scale_d) {
    asm volatile("{\n.reg .pred p;\n.reg .b64 da, db;\nsetp.ne.b32 p, %98, 0;\nmov.b64 da, {%96, 0x40000040};\nmov.b64 db, {%97, 0x40000040};\n"
        "wgmma.mma_async.sync.aligned.m64n192k16.f32.bf16.bf16 {"
        "%0, %1, %2, %3, %4, %5, %6, %7, %8, %9, %10, %11, %12, %13, %14, %15, %16, %17, %18, %19, %20, %21, %22, %23, %24, %25, %26, %27, %28, %29, %30, %31,  "
        "%32, %33, %34, %35, %36, %37, %38, %39, %40, %41, %42, %43, %44, %45, %46, %47, %48, %49, %50, %51, %52, %53, %54, %55, %56, %57, %58, %59, %60, %61,  "
        "%62, %63, %64, %65, %66, %67, %68, %69, %70, %71, %72, %73, %74, %75, %76, %77, %78, %79, %80, %81, %82, %83, %84, %85, %86, %87, %88, %89, %90, %91,  "
        "%92, %93, %94, %95 "
        "}, da, db, p, 1, 1, 0, 1;\n}\n"
        : "+f"(d[0]), "+f"(d[1]), "+f"(d[2]), "+f"(d[3]), "+f"(d[4]), "+f"(d[5]), "+f"(d[6]), "+f"(d[7]), "+f"(d[8]), "+f"(d[9]), "+f"(d[10]), "+f"(d[11]),
          "+f"(d[12]), "+f"(d[13]), "+f"(d[14]), "+f"(d[15]), "+f"(d[16]), "+f"(d[17]), "+f"(d[18]), "+f"(d[19]), "+f"(d[20]), "+f"(d[21]), "+f"(d[22]),
          "+f"(d[23]), "+f"(d[24]), "+f"(d[25]), "+f"(d[26]), "+f"(d[27]), "+f"(d[28]), "+f"(d[29]), "+f"(d[30]), "+f"(d[31]), "+f"(d[32]), "+f"(d[33]),
          "+f"(d[34]), "+f"(d[35]), "+f"(d[36]), "+f"(d[37]), "+f"(d[38]), "+f"(d[39]), "+f"(d[40]), "+f"(d[41]), "+f"(d[42]), "+f"(d[43]), "+f"(d[44]),
          "+f"(d[45]), "+f"(d[46]), "+f"(d[47]), "+f"(d[48]), "+f"(d[49]), "+f"(d[50]), "+f"(d[51]), "+f"(d[52]), "+f"(d[53]), "+f"(d[54]), "+f"(d[55]),
          "+f"(d[56]), "+f"(d[57]), "+f"(d[58]), "+f"(d[59]), "+f"(d[60]), "+f"(d[61]), "+f"(d[62]), "+f"(d[63]), "+f"(d[64]), "+f"(d[65]), "+f"(d[66]),
          "+f"(d[67]), "+f"(d[68]), "+f"(d[69]), "+f"(d[70]), "+f"(d[71]), "+f"(d[72]), "+f"(d[73]), "+f"(d[74]), "+f"(d[75]), "+f"(d[76]), "+f"(d[77]),
          "+f"(d[78]), "+f"(d[79]), "+f"(d[80]), "+f"(d[81]), "+f"(d[82]), "+f"(d[83]), "+f"(d[84]), "+f"(d[85]), "+f"(d[86]), "+f"(d[87]), "+f"(d[88]),
          "+f"(d[89]), "+f"(d[90]), "+f"(d[91]), "+f"(d[92]), "+f"(d[93]), "+f"(d[94]), "+f"(d[95])
        : "r"(alo), "r"(blo), "r"(scale_d));
}
__device__ __forceinline__ void mma_wo(float (&d)[64], uint32_t alo, uint32_t blo, int scale_d) {
    asm volatile("{\n.reg .pred p;\n.reg .b64 da, db;\nsetp.ne.b32 p, %66, 0;\nmov.b64 da, {%64, 0x40000040};\nmov.b64 db, {%65, 0x40000040};\n"
        "wgmma.mma_async.sync.aligned.m64n128k16.f32.bf16.bf16 {"
        "%0, %1, %2, %3, %4, %5, %6, %7, %8, %9, %10, %11, %12, %13, %14, %15, %16, %17, %18, %19, %20, %21, %22, %23, %24, %25, %26, %27, %28, %29, %30, %31,  "
        "%32, %33, %34, %35, %36, %37, %38, %39, %40, %41, %42, %43, %44, %45, %46, %47, %48, %49, %50, %51, %52, %53, %54, %55, %56, %57, %58, %59, %60, %61,  "
        "%62, %63 "
        "}, da, db, p, 1, 1, 0, 1;\n}\n"
        : "+f"(d[0]), "+f"(d[1]), "+f"(d[2]), "+f"(d[3]), "+f"(d[4]), "+f"(d[5]), "+f"(d[6]), "+f"(d[7]), "+f"(d[8]), "+f"(d[9]), "+f"(d[10]), "+f"(d[11]),
          "+f"(d[12]), "+f"(d[13]), "+f"(d[14]), "+f"(d[15]), "+f"(d[16]), "+f"(d[17]), "+f"(d[18]), "+f"(d[19]), "+f"(d[20]), "+f"(d[21]), "+f"(d[22]),
          "+f"(d[23]), "+f"(d[24]), "+f"(d[25]), "+f"(d[26]), "+f"(d[27]), "+f"(d[28]), "+f"(d[29]), "+f"(d[30]), "+f"(d[31]), "+f"(d[32]), "+f"(d[33]),
          "+f"(d[34]), "+f"(d[35]), "+f"(d[36]), "+f"(d[37]), "+f"(d[38]), "+f"(d[39]), "+f"(d[40]), "+f"(d[41]), "+f"(d[42]), "+f"(d[43]), "+f"(d[44]),
          "+f"(d[45]), "+f"(d[46]), "+f"(d[47]), "+f"(d[48]), "+f"(d[49]), "+f"(d[50]), "+f"(d[51]), "+f"(d[52]), "+f"(d[53]), "+f"(d[54]), "+f"(d[55]),
          "+f"(d[56]), "+f"(d[57]), "+f"(d[58]), "+f"(d[59]), "+f"(d[60]), "+f"(d[61]), "+f"(d[62]), "+f"(d[63])
        : "r"(alo), "r"(blo), "r"(scale_d));
}
__device__ __forceinline__ void mma_mix2(float (&d)[64], uint32_t alo, uint32_t blo, int scale_d) {
    asm volatile("{\n.reg .pred p;\n.reg .b64 da, db;\nsetp.ne.b32 p, %66, 0;\nmov.b64 da, {%64, 0x40000040};\nmov.b64 db, {%65, 0x40000040};\n"
        "wgmma.mma_async.sync.aligned.m64n128k16.f32.bf16.bf16 {"
        "%0, %1, %2, %3, %4, %5, %6, %7, %8, %9, %10, %11, %12, %13, %14, %15, %16, %17, %18, %19, %20, %21, %22, %23, %24, %25, %26, %27, %28, %29, %30, %31,  "
        "%32, %33, %34, %35, %36, %37, %38, %39, %40, %41, %42, %43, %44, %45, %46, %47, %48, %49, %50, %51, %52, %53, %54, %55, %56, %57, %58, %59, %60, %61,  "
        "%62, %63 "
        "}, da, db, p, 1, 1, 1, 0;\n}\n"
        : "+f"(d[0]), "+f"(d[1]), "+f"(d[2]), "+f"(d[3]), "+f"(d[4]), "+f"(d[5]), "+f"(d[6]), "+f"(d[7]), "+f"(d[8]), "+f"(d[9]), "+f"(d[10]), "+f"(d[11]),
          "+f"(d[12]), "+f"(d[13]), "+f"(d[14]), "+f"(d[15]), "+f"(d[16]), "+f"(d[17]), "+f"(d[18]), "+f"(d[19]), "+f"(d[20]), "+f"(d[21]), "+f"(d[22]),
          "+f"(d[23]), "+f"(d[24]), "+f"(d[25]), "+f"(d[26]), "+f"(d[27]), "+f"(d[28]), "+f"(d[29]), "+f"(d[30]), "+f"(d[31]), "+f"(d[32]), "+f"(d[33]),
          "+f"(d[34]), "+f"(d[35]), "+f"(d[36]), "+f"(d[37]), "+f"(d[38]), "+f"(d[39]), "+f"(d[40]), "+f"(d[41]), "+f"(d[42]), "+f"(d[43]), "+f"(d[44]),
          "+f"(d[45]), "+f"(d[46]), "+f"(d[47]), "+f"(d[48]), "+f"(d[49]), "+f"(d[50]), "+f"(d[51]), "+f"(d[52]), "+f"(d[53]), "+f"(d[54]), "+f"(d[55]),
          "+f"(d[56]), "+f"(d[57]), "+f"(d[58]), "+f"(d[59]), "+f"(d[60]), "+f"(d[61]), "+f"(d[62]), "+f"(d[63])
        : "r"(alo), "r"(blo), "r"(scale_d));
}
__device__ __forceinline__ void mma_mix1(float (&d)[112], uint32_t alo, uint32_t blo, int scale_d) {
    asm volatile("{\n.reg .pred p;\n.reg .b64 da, db;\nsetp.ne.b32 p, %114, 0;\nmov.b64 da, {%112, 0x40000040};\nmov.b64 db, {%113, 0x80000020};\n"
        "wgmma.mma_async.sync.aligned.m64n224k16.f32.bf16.bf16 {"
        "%0, %1, %2, %3, %4, %5, %6, %7, %8, %9, %10, %11, %12, %13, %14, %15, %16, %17, %18, %19, %20, %21, %22, %23, %24, %25, %26, %27, %28, %29, %30, %31,  "
        "%32, %33, %34, %35, %36, %37, %38, %39, %40, %41, %42, %43, %44, %45, %46, %47, %48, %49, %50, %51, %52, %53, %54, %55, %56, %57, %58, %59, %60, %61,  "
        "%62, %63, %64, %65, %66, %67, %68, %69, %70, %71, %72, %73, %74, %75, %76, %77, %78, %79, %80, %81, %82, %83, %84, %85, %86, %87, %88, %89, %90, %91,  "
        "%92, %93, %94, %95, %96, %97, %98, %99, %100, %101, %102, %103, %104, %105, %106, %107, %108, %109, %110, %111 "
        "}, da, db, p, 1, 1, 1, 1;\n}\n"
        : "+f"(d[0]), "+f"(d[1]), "+f"(d[2]), "+f"(d[3]), "+f"(d[4]), "+f"(d[5]), "+f"(d[6]), "+f"(d[7]), "+f"(d[8]), "+f"(d[9]), "+f"(d[10]), "+f"(d[11]),
          "+f"(d[12]), "+f"(d[13]), "+f"(d[14]), "+f"(d[15]), "+f"(d[16]), "+f"(d[17]), "+f"(d[18]), "+f"(d[19]), "+f"(d[20]), "+f"(d[21]), "+f"(d[22]),
          "+f"(d[23]), "+f"(d[24]), "+f"(d[25]), "+f"(d[26]), "+f"(d[27]), "+f"(d[28]), "+f"(d[29]), "+f"(d[30]), "+f"(d[31]), "+f"(d[32]), "+f"(d[33]),
          "+f"(d[34]), "+f"(d[35]), "+f"(d[36]), "+f"(d[37]), "+f"(d[38]), "+f"(d[39]), "+f"(d[40]), "+f"(d[41]), "+f"(d[42]), "+f"(d[43]), "+f"(d[44]),
          "+f"(d[45]), "+f"(d[46]), "+f"(d[47]), "+f"(d[48]), "+f"(d[49]), "+f"(d[50]), "+f"(d[51]), "+f"(d[52]), "+f"(d[53]), "+f"(d[54]), "+f"(d[55]),
          "+f"(d[56]), "+f"(d[57]), "+f"(d[58]), "+f"(d[59]), "+f"(d[60]), "+f"(d[61]), "+f"(d[62]), "+f"(d[63]), "+f"(d[64]), "+f"(d[65]), "+f"(d[66]),
          "+f"(d[67]), "+f"(d[68]), "+f"(d[69]), "+f"(d[70]), "+f"(d[71]), "+f"(d[72]), "+f"(d[73]), "+f"(d[74]), "+f"(d[75]), "+f"(d[76]), "+f"(d[77]),
          "+f"(d[78]), "+f"(d[79]), "+f"(d[80]), "+f"(d[81]), "+f"(d[82]), "+f"(d[83]), "+f"(d[84]), "+f"(d[85]), "+f"(d[86]), "+f"(d[87]), "+f"(d[88]),
          "+f"(d[89]), "+f"(d[90]), "+f"(d[91]), "+f"(d[92]), "+f"(d[93]), "+f"(d[94]), "+f"(d[95]), "+f"(d[96]), "+f"(d[97]), "+f"(d[98]), "+f"(d[99]),
          "+f"(d[100]), "+f"(d[101]), "+f"(d[102]), "+f"(d[103]), "+f"(d[104]), "+f"(d[105]), "+f"(d[106]), "+f"(d[107]), "+f"(d[108]), "+f"(d[109]),
          "+f"(d[110]), "+f"(d[111])
        : "r"(alo), "r"(blo), "r"(scale_d));
}
__device__ __forceinline__ void mma_qk0(float (&d)[32], uint32_t alo, uint32_t blo) {
    asm volatile("{\n.reg .pred p;\n.reg .b64 da, db;\nsetp.ne.b32 p, 0, 0;\nmov.b64 da, {%32, 0x80000020};\nmov.b64 db, {%33, 0x80000020};\n"
        "wgmma.mma_async.sync.aligned.m64n64k16.f32.bf16.bf16 {"
        "%0, %1, %2, %3, %4, %5, %6, %7, %8, %9, %10, %11, %12, %13, %14, %15, %16, %17, %18, %19, %20, %21, %22, %23, %24, %25, %26, %27, %28, %29, %30, %31 "
        "}, da, db, p, 1, 1, 0, 0;\n}\n"
        : "=f"(d[0]), "=f"(d[1]), "=f"(d[2]), "=f"(d[3]), "=f"(d[4]), "=f"(d[5]), "=f"(d[6]), "=f"(d[7]), "=f"(d[8]), "=f"(d[9]), "=f"(d[10]), "=f"(d[11]),
          "=f"(d[12]), "=f"(d[13]), "=f"(d[14]), "=f"(d[15]), "=f"(d[16]), "=f"(d[17]), "=f"(d[18]), "=f"(d[19]), "=f"(d[20]), "=f"(d[21]), "=f"(d[22]),
          "=f"(d[23]), "=f"(d[24]), "=f"(d[25]), "=f"(d[26]), "=f"(d[27]), "=f"(d[28]), "=f"(d[29]), "=f"(d[30]), "=f"(d[31])
        : "r"(alo), "r"(blo));
}
__device__ __forceinline__ void mma_qk1(float (&d)[32], uint32_t alo, uint32_t blo, int scale_d) {
    asm volatile("{\n.reg .pred p;\n.reg .b64 da, db;\nsetp.ne.b32 p, %34, 0;\nmov.b64 da, {%32, 0x80000020};\nmov.b64 db, {%33, 0x80000020};\n"
        "wgmma.mma_async.sync.aligned.m64n64k16.f32.bf16.bf16 {"
        "%0, %1, %2, %3, %4, %5, %6, %7, %8, %9, %10, %11, %12, %13, %14, %15, %16, %17, %18, %19, %20, %21, %22, %23, %24, %25, %26, %27, %28, %29, %30, %31 "
        "}, da, db, p, 1, 1, 0, 0;\n}\n"
        : "+f"(d[0]), "+f"(d[1]), "+f"(d[2]), "+f"(d[3]), "+f"(d[4]), "+f"(d[5]), "+f"(d[6]), "+f"(d[7]), "+f"(d[8]), "+f"(d[9]), "+f"(d[10]), "+f"(d[11]),
          "+f"(d[12]), "+f"(d[13]), "+f"(d[14]), "+f"(d[15]), "+f"(d[16]), "+f"(d[17]), "+f"(d[18]), "+f"(d[19]), "+f"(d[20]), "+f"(d[21]), "+f"(d[22]),
          "+f"(d[23]), "+f"(d[24]), "+f"(d[25]), "+f"(d[26]), "+f"(d[27]), "+f"(d[28]), "+f"(d[29]), "+f"(d[30]), "+f"(d[31])
        : "r"(alo), "r"(blo), "r"(scale_d));
}
__device__ __forceinline__ void mma_qkw0(float (&d)[64], uint32_t alo, uint32_t blo) {
    asm volatile("{\n.reg .pred p;\n.reg .b64 da, db;\nsetp.ne.b32 p, 0, 0;\nmov.b64 da, {%64, 0x80000020};\nmov.b64 db, {%65, 0x80000020};\n"
        "wgmma.mma_async.sync.aligned.m64n128k16.f32.bf16.bf16 {"
        "%0, %1, %2, %3, %4, %5, %6, %7, %8, %9, %10, %11, %12, %13, %14, %15, %16, %17, %18, %19, %20, %21, %22, %23, %24, %25, %26, %27, %28, %29, %30, %31,  "
        "%32, %33, %34, %35, %36, %37, %38, %39, %40, %41, %42, %43, %44, %45, %46, %47, %48, %49, %50, %51, %52, %53, %54, %55, %56, %57, %58, %59, %60, %61,  "
        "%62, %63 "
        "}, da, db, p, 1, 1, 0, 0;\n}\n"
        : "=f"(d[0]), "=f"(d[1]), "=f"(d[2]), "=f"(d[3]), "=f"(d[4]), "=f"(d[5]), "=f"(d[6]), "=f"(d[7]), "=f"(d[8]), "=f"(d[9]), "=f"(d[10]), "=f"(d[11]),
          "=f"(d[12]), "=f"(d[13]), "=f"(d[14]), "=f"(d[15]), "=f"(d[16]), "=f"(d[17]), "=f"(d[18]), "=f"(d[19]), "=f"(d[20]), "=f"(d[21]), "=f"(d[22]),
          "=f"(d[23]), "=f"(d[24]), "=f"(d[25]), "=f"(d[26]), "=f"(d[27]), "=f"(d[28]), "=f"(d[29]), "=f"(d[30]), "=f"(d[31]), "=f"(d[32]), "=f"(d[33]),
          "=f"(d[34]), "=f"(d[35]), "=f"(d[36]), "=f"(d[37]), "=f"(d[38]), "=f"(d[39]), "=f"(d[40]), "=f"(d[41]), "=f"(d[42]), "=f"(d[43]), "=f"(d[44]),
          "=f"(d[45]), "=f"(d[46]), "=f"(d[47]), "=f"(d[48]), "=f"(d[49]), "=f"(d[50]), "=f"(d[51]), "=f"(d[52]), "=f"(d[53]), "=f"(d[54]), "=f"(d[55]),
          "=f"(d[56]), "=f"(d[57]), "=f"(d[58]), "=f"(d[59]), "=f"(d[60]), "=f"(d[61]), "=f"(d[62]), "=f"(d[63])
        : "r"(alo), "r"(blo));
}
__device__ __forceinline__ void mma_qkw1(float (&d)[64], uint32_t alo, uint32_t blo, int scale_d) {
    asm volatile("{\n.reg .pred p;\n.reg .b64 da, db;\nsetp.ne.b32 p, %66, 0;\nmov.b64 da, {%64, 0x80000020};\nmov.b64 db, {%65, 0x80000020};\n"
        "wgmma.mma_async.sync.aligned.m64n128k16.f32.bf16.bf16 {"
        "%0, %1, %2, %3, %4, %5, %6, %7, %8, %9, %10, %11, %12, %13, %14, %15, %16, %17, %18, %19, %20, %21, %22, %23, %24, %25, %26, %27, %28, %29, %30, %31,  "
        "%32, %33, %34, %35, %36, %37, %38, %39, %40, %41, %42, %43, %44, %45, %46, %47, %48, %49, %50, %51, %52, %53, %54, %55, %56, %57, %58, %59, %60, %61,  "
        "%62, %63 "
        "}, da, db, p, 1, 1, 0, 0;\n}\n"
        : "+f"(d[0]), "+f"(d[1]), "+f"(d[2]), "+f"(d[3]), "+f"(d[4]), "+f"(d[5]), "+f"(d[6]), "+f"(d[7]), "+f"(d[8]), "+f"(d[9]), "+f"(d[10]), "+f"(d[11]),
          "+f"(d[12]), "+f"(d[13]), "+f"(d[14]), "+f"(d[15]), "+f"(d[16]), "+f"(d[17]), "+f"(d[18]), "+f"(d[19]), "+f"(d[20]), "+f"(d[21]), "+f"(d[22]),
          "+f"(d[23]), "+f"(d[24]), "+f"(d[25]), "+f"(d[26]), "+f"(d[27]), "+f"(d[28]), "+f"(d[29]), "+f"(d[30]), "+f"(d[31]), "+f"(d[32]), "+f"(d[33]),
          "+f"(d[34]), "+f"(d[35]), "+f"(d[36]), "+f"(d[37]), "+f"(d[38]), "+f"(d[39]), "+f"(d[40]), "+f"(d[41]), "+f"(d[42]), "+f"(d[43]), "+f"(d[44]),
          "+f"(d[45]), "+f"(d[46]), "+f"(d[47]), "+f"(d[48]), "+f"(d[49]), "+f"(d[50]), "+f"(d[51]), "+f"(d[52]), "+f"(d[53]), "+f"(d[54]), "+f"(d[55]),
          "+f"(d[56]), "+f"(d[57]), "+f"(d[58]), "+f"(d[59]), "+f"(d[60]), "+f"(d[61]), "+f"(d[62]), "+f"(d[63])
        : "r"(alo), "r"(blo), "r"(scale_d));
}
__device__ __forceinline__ void mma_pv(float (&d)[20], uint32_t a0, uint32_t a1, uint32_t a2, uint32_t a3, uint32_t blo, int scale_d) {
    asm volatile("{\n.reg .pred p;\n.reg .b64 da, db;\nsetp.ne.b32 p, %25, 0;\nmov.b64 db, {%24, 0x80000020};\n"
        "wgmma.mma_async.sync.aligned.m64n40k16.f32.bf16.bf16 {"
        "%0, %1, %2, %3, %4, %5, %6, %7, %8, %9, %10, %11, %12, %13, %14, %15, %16, %17, %18, %19 "
        "}, {%20, %21, %22, %23}, db, p, 1, 1, 1;\n}\n"
        : "+f"(d[0]), "+f"(d[1]), "+f"(d[2]), "+f"(d[3]), "+f"(d[4]), "+f"(d[5]), "+f"(d[6]), "+f"(d[7]), "+f"(d[8]), "+f"(d[9]), "+f"(d[10]), "+f"(d[11]),
          "+f"(d[12]), "+f"(d[13]), "+f"(d[14]), "+f"(d[15]), "+f"(d[16]), "+f"(d[17]), "+f"(d[18]), "+f"(d[19])
        : "r"(a0), "r"(a1), "r"(a2), "r"(a3), "r"(blo), "r"(scale_d));
}

__device__ __forceinline__ float warp_sum(float v) {
#pragma unroll
    for (int o = 16; o > 0; o >>= 1) v += __shfl_xor_sync(0xffffffffu, v, o);
    return v;
}
template <bool TWICE>
__global__ void __launch_bounds__(256) ln_kernel(const bf16* __restrict__ in, bf16* __restrict__ out) {
    pdl_launch();
    if (TWICE) pdl_wait();
    if (!TWICE && blockIdx.x == 0 && threadIdx.x < 3 * NH) g_norm[threadIdx.x] = 0u;
    TL(TWICE ? 4 : 0, 0);
    const int row = blockIdx.x * 8 + (threadIdx.x >> 5), lane = threadIdx.x & 31;
    const uint4* src = reinterpret_cast<const uint4*>(in + (size_t)row * DM);
    uint4 v[4];
#pragma unroll
    for (int i = 0; i < 4; i++) v[i] = src[lane + 32 * i];
    float f[32];
#pragma unroll
    for (int i = 0; i < 4; i++) {
        f[8 * i + 0] = bf_lo(v[i].x); f[8 * i + 1] = bf_hi(v[i].x); f[8 * i + 2] = bf_lo(v[i].y); f[8 * i + 3] = bf_hi(v[i].y);
        f[8 * i + 4] = bf_lo(v[i].z); f[8 * i + 5] = bf_hi(v[i].z); f[8 * i + 6] = bf_lo(v[i].w); f[8 * i + 7] = bf_hi(v[i].w);
    }
#pragma unroll
    for (int pass = 0; pass < (TWICE ? 2 : 1); pass++) {
        float s = 0.f;
#pragma unroll
        for (int i = 0; i < 32; i++) s += f[i];
        const float mean = warp_sum(s) * (1.f / DM);
        float q = 0.f;
#pragma unroll
        for (int i = 0; i < 32; i++) { f[i] -= mean; q += f[i] * f[i]; }
        const float rstd = rsqrtf(warp_sum(q) * (1.f / DM) + 1e-5f);
#pragma unroll
        for (int i = 0; i < 32; i++) f[i] *= rstd;
    }
    uint4* dst = reinterpret_cast<uint4*>(out + (size_t)row * DM);
#pragma unroll
    for (int i = 0; i < 4; i++) {
        uint4 o;
        o.x = pack_bf16(f[8 * i + 0], f[8 * i + 1]); o.y = pack_bf16(f[8 * i + 2], f[8 * i + 3]);
        o.z = pack_bf16(f[8 * i + 4], f[8 * i + 5]); o.w = pack_bf16(f[8 * i + 6], f[8 * i + 7]);
        dst[lane + 32 * i] = o;
    }
    TL(TWICE ? 4 : 0, 3);
}

struct GemmSmem { uint32_t base, full0, empty0, aux; };

template <class C>
__device__ __forceinline__ GemmSmem gemm_setup(uint8_t* smem_raw) {
    GemmSmem s;
    s.base = smem_u32(smem_raw);
    s.full0 = s.base + C::BAR_OFF; s.empty0 = s.full0 + 8 * C::STAGES; s.aux = s.empty0 + 8 * C::STAGES;
    if (threadIdx.x == 0) {
        if (s.base & 1023) __trap();
        for (int i = 0; i < C::STAGES; i++) { mbar_init(s.full0 + 8 * i, 1); mbar_init(s.empty0 + 8 * i, 8); }
        mbar_init(s.aux, 1);
        fence_barrier_init();
    }
    __syncthreads();
    return s;
}

template <class C, class P>
__device__ __forceinline__ void gemm_producer(const GemmSmem& s, const P& p, int tm, int tn) {
#pragma unroll 1
    for (int k = 0; k < C::STAGES; k++) {
        mbar_expect_tx(s.full0 + 8 * k, C::STAGE_BYTES);
        C::load_w(p, s.base + k * C::STAGE_BYTES, s.full0 + 8 * k, k, tm, tn);
    }
    pdl_wait();
    C::load_aux(p, s, tm, tn);
#pragma unroll 1
    for (int k = 0; k < C::STAGES; k++) C::load_x(p, s.base + k * C::STAGE_BYTES, s.full0 + 8 * k, k, tm, tn);
    int st = 0; uint32_t ph = 0;
#pragma unroll 1
    for (int k = C::STAGES; k < C::KSTEPS; k++) {
        mbar_wait(s.empty0 + 8 * st, ph);
        mbar_expect_tx(s.full0 + 8 * st, C::STAGE_BYTES);
        C::load_w(p, s.base + st * C::STAGE_BYTES, s.full0 + 8 * st, k, tm, tn);
        C::load_x(p, s.base + st * C::STAGE_BYTES, s.full0 + 8 * st, k, tm, tn);
        if (++st == C::STAGES) { st = 0; ph ^= 1; }
    }
}

template <class C>
__device__ __forceinline__ void gemm_mainloop(const GemmSmem& s, int wg, float (&acc)[C::MB][C::BN / 2]) {
    const int lane = threadIdx.x & 31;
    int st = 0; uint32_t ph = 0;
    int prev = 0;
#pragma unroll
    for (int m = 0; m < C::MB; m++) fence_regs(acc[m]);
#pragma unroll 1
    for (int k = 0; k < C::KSTEPS; k++) {
        mbar_wait(s.full0 + 8 * st, ph);
        const uint32_t sb = s.base + st * C::STAGE_BYTES;
        wg_fence();
#pragma unroll
        for (int kk = 0; kk < 4; kk++) {
#pragma unroll
            for (int m = 0; m < C::MB; m++) C::mma(acc[m], C::desc_a(sb, wg, m, kk), C::desc_b(sb, kk), (k | kk) != 0);
        }
        wg_commit();
        if (k > 0) { wg_wait<1>(); if (lane == 0) mbar_arrive(s.empty0 + 8 * prev); }
        prev = st;
        if (++st == C::STAGES) { st = 0; ph ^= 1; }
    }
    wg_wait<0>();
#pragma unroll
    for (int m = 0; m < C::MB; m++) fence_regs(acc[m]);
}

struct QkvParams { CUtensorMap xn, w, out; };
struct QkvCfg {
    static constexpr int MB = 2, BN = 192, KSTEPS = 16, STAGES = 4, A_BYTES = 32768, B_BYTES = 24576;
    static constexpr int STAGE_BYTES = A_BYTES + B_BYTES, BAR_OFF = STAGES * STAGE_BYTES, SMEM = BAR_OFF + 128;
    static __device__ __forceinline__ void load_w(const QkvParams& p, uint32_t sb, uint32_t bar, int k, int tm, int tn) { tma_ld4(sb + A_BYTES, &p.w, bar, 0, k * 64, 0, tn); }
    static __device__ __forceinline__ void load_x(const QkvParams& p, uint32_t sb, uint32_t bar, int k, int tm, int tn) { tma_ld2(sb, &p.xn, bar, k * 64, tm * 256); }
    static __device__ __forceinline__ void load_aux(const QkvParams&, const GemmSmem&, int, int) {}
    static __device__ __forceinline__ uint32_t desc_a(uint32_t sb, int wg, int m, int kk) { return desc_lo(sb + (wg * 128 + m * 64) * 128 + kk * 32, 16); }
    static __device__ __forceinline__ uint32_t desc_b(uint32_t sb, int kk) { return desc_lo(sb + A_BYTES + kk * 2048, 8192); }
    static __device__ __forceinline__ void mma(float (&d)[96], uint32_t a, uint32_t b, int sc) { mma_qkv(d, a, b, sc); }
};
__global__ void __launch_bounds__(384, 1) qkv_kernel(const __grid_constant__ QkvParams p) {
    extern __shared__ __align__(1024) uint8_t smem_raw[];
    pdl_launch();
    const int tm = blockIdx.x & 7, tn = blockIdx.x >> 3;
    if (threadIdx.x == 0) { prefetch_map(&p.xn); prefetch_map(&p.w); prefetch_map(&p.out); }
    const GemmSmem s = gemm_setup<QkvCfg>(smem_raw);
    const int wgi = __shfl_sync(0xffffffffu, threadIdx.x >> 7, 0);
    if (wgi == 0) {
        reg_dealloc<40>();
        if (threadIdx.x == 0) gemm_producer<QkvCfg>(s, p, tm, tn);
    } else {
        reg_alloc<232>();
        const int wg = wgi - 1, warp = (threadIdx.x >> 5) & 3, lane = threadIdx.x & 31;
        float acc[2][96];
        pdl_wait();
        TL(1, 0);
        gemm_mainloop<QkvCfg>(s, wg, acc);
        TL(1, 1);
        named_bar(1, 256);
        const float qscale = 0.17677669529663687f * 1.4426950408889634f;
        float nmax[6];
#pragma unroll
        for (int i = 0; i < 6; i++) nmax[i] = 0.f;
#pragma unroll
        for (int m = 0; m < 2; m++) {
            const int rbase = wg * 128 + m * 64 + warp * 16;
            const int arow = rbase + ((lane >> 3) & 1) * 8 + (lane & 7);
#pragma unroll
            for (int sub = 0; sub < 6; sub++) {
                float v[16];
#pragma unroll
                for (int i = 0; i < 16; i++) v[i] = (sub < 2) ? acc[m][sub * 16 + i] * qscale : acc[m][sub * 16 + i];
                float n0 = 0.f, n1 = 0.f;
#pragma unroll
                for (int j = 0; j < 4; j++) {
                    n0 += v[4 * j] * v[4 * j] + v[4 * j + 1] * v[4 * j + 1];
                    n1 += v[4 * j + 2] * v[4 * j + 2] + v[4 * j + 3] * v[4 * j + 3];
                }
                n0 += __shfl_xor_sync(0xffffffffu, n0, 1); n1 += __shfl_xor_sync(0xffffffffu, n1, 1);
                n0 += __shfl_xor_sync(0xffffffffu, n0, 2); n1 += __shfl_xor_sync(0xffffffffu, n1, 2);
                nmax[sub] = __uint_as_float(max(max(__float_as_uint(n0), __float_as_uint(n1)), __float_as_uint(nmax[sub])));
#pragma unroll
                for (int jp = 0; jp < 2; jp++) {
                    const int chunk = jp * 2 + (lane >> 4);
                    const uint32_t addr = s.base + sub * 16384 + arow * 64 + ((chunk ^ ((arow >> 1) & 3)) << 4);
                    stmatrix_x4(addr, pack_bf16(v[8 * jp], v[8 * jp + 1]), pack_bf16(v[8 * jp + 2], v[8 * jp + 3]),
                                pack_bf16(v[8 * jp + 4], v[8 * jp + 5]), pack_bf16(v[8 * jp + 6], v[8 * jp + 7]));
                }
            }
        }
        fence_proxy_async();
        named_bar(2 + wg, 128);
        if ((threadIdx.x & 127) == 0) {
#pragma unroll
            for (int sub = 0; sub < 6; sub++)
                tma_st2(&p.out, s.base + sub * 16384 + wg * 8192, 0, (sub >> 1) * (NH * SEQ) + (tn * 2 + (sub & 1)) * SEQ + tm * 256 + wg * 128);
            tma_st_commit();
        }
#pragma unroll
        for (int sub = 0; sub < 6; sub++) {
            const uint32_t mx = __reduce_max_sync(0xffffffffu, __float_as_uint(nmax[sub]));
            if (lane == 0) atomicMax(&g_norm[(sub >> 1) * NH + tn * 2 + (sub & 1)], mx);
        }
        if ((threadIdx.x & 127) == 0) tma_st_wait();
        TL(1, 3);
    }
}

struct AttnParams { CUtensorMap kv; bf16* o; };
constexpr int AT_STAGES = 8, AT_STAGE_BYTES = 16384, AT_Q_OFF = AT_STAGES * AT_STAGE_BYTES, AT_ONES_OFF = AT_Q_OFF + 32768, AT_BAR_OFF = AT_ONES_OFF + 1024, AT_SMEM = AT_BAR_OFF + 256;
constexpr int AT_TILES = 32;

__device__ __forceinline__ float ex2_poly(float x) {
    const float magic = 12582912.f;
    const float t = x + magic;
    const float f = x - (t - magic);
    float p = fmaf(f, 0.05550410866f, 0.24022650695f);
    p = fmaf(p, f, 0.69314718056f);
    p = fmaf(p, f, 1.0f);
    return __int_as_float(__float_as_int(p) + (__float_as_int(t) << 23));
}

__device__ __forceinline__ float attn_exp(float x, int i) { return ((POLY_MASK >> (i & 31)) & 1) ? ex2_poly(x) : ex2(x); }
__device__ __forceinline__ void attn_issue_tile(const AttnParams& p, uint32_t base, uint32_t full0, int g, int head) {
    const int st = g % AT_STAGES, key0 = (g & 15) * 128;
    const uint32_t bar = full0 + 8 * st, dst = base + st * AT_STAGE_BYTES;
    mbar_expect_tx(bar, AT_STAGE_BYTES);
    tma_ld2(dst, &p.kv, bar, 0, (NH + head) * SEQ + key0);
    tma_ld2(dst + 8192, &p.kv, bar, 0, (2 * NH + head) * SEQ + key0);
}
__device__ __forceinline__ void attn_qk(float (&sacc)[32], uint32_t q_lo, uint32_t k_lo) {
    mma_qk0(sacc, q_lo, k_lo);
    mma_qk1(sacc, q_lo + 2, k_lo + 2, 1);
}
constexpr uint32_t PV_STEP = 64u - (64u << 16);
__device__ __forceinline__ void attn_pv(float (&o)[20], const uint32_t (&pr)[16], uint32_t v_lo, int first) {
#pragma unroll
    for (int kk = 0; kk < 4; kk++)
        mma_pv(o, pr[4 * kk], pr[4 * kk + 1], pr[4 * kk + 2], pr[4 * kk + 3], v_lo + kk * PV_STEP, (kk > 0) || !first);
}
__device__ __forceinline__ void attn_store_o(const float (&o)[20], const AttnParams& p, int head, int row0, int lane) {
    const float r0 = 1.f / o[16], r1 = 1.f / o[18];
    uint32_t* op = reinterpret_cast<uint32_t*>(p.o + (size_t)row0 * DM + head * HD) + (lane & 3);
#pragma unroll
    for (int j = 0; j < 4; j++) {
        op[j * 4] = pack_bf16(o[4 * j] * r0, o[4 * j + 1] * r0);
        op[j * 4 + 8 * (DM / 2)] = pack_bf16(o[4 * j + 2] * r1, o[4 * j + 3] * r1);
    }
}
__device__ __forceinline__ void attn_refill(const AttnParams& p, uint32_t base, uint32_t full0, uint32_t empty0, int g, int head) {
    if (threadIdx.x == 0 && g >= 4 && g + 4 < AT_TILES) {
        const int gp = g - 4;
        mbar_wait(empty0 + 8 * (gp % AT_STAGES), (gp / AT_STAGES) & 1);
        attn_issue_tile(p, base, full0, g + 4, head);
    }
    __syncwarp();
}

__device__ __forceinline__ void attn_fast(const AttnParams& p, uint32_t base, uint32_t full0, uint32_t empty0, int head, int qchunk) {
    const int wg = __shfl_sync(0xffffffffu, threadIdx.x >> 7, 0), warp = (threadIdx.x >> 5) & 3, lane = threadIdx.x & 31;
    const bool is_producer_warp = __shfl_sync(0xffffffffu, threadIdx.x >> 5, 0) == 0;
    const uint32_t k_lo0 = desc_lo(base, 16), v_lo0 = desc_lo(base + 8192, AT_ONES_OFF - 8192);
    const uint32_t q_lo0 = desc_lo(base + AT_Q_OFF + wg * 64 * 64, 16);
#pragma unroll 1
    for (int pass = 0; pass < 2; pass++) {
    const uint32_t q = q_lo0 + pass * (256 * 64 >> 4);
    float o[20];
#pragma unroll
    for (int i = 0; i < 20; i++) o[i] = 0.f;
#pragma unroll 1
    for (uint32_t par = 0; par < 2; par++) {
        const int rev = pass * 2 + par;
#pragma unroll
        for (int st = 0; st < AT_STAGES; st++) {
            if (is_producer_warp) {
                const int g = rev * AT_STAGES + st;
                if (lane == 0 && g >= 4 && g + 4 < AT_TILES) {
                    mbar_wait(empty0 + 8 * ((st + 4) % AT_STAGES), (st >= 4) ? par : (par ^ 1));
                    attn_issue_tile(p, base, full0, g + 4, head);
                }
                __syncwarp();
            }
            mbar_wait(full0 + 8 * st, par);
            float sc[64];
            uint32_t pa[16], pb[16];
            wg_fence();
            mma_qkw0(sc, q, k_lo0 + st * (AT_STAGE_BYTES >> 4));
            mma_qkw1(sc, q + 2, k_lo0 + st * (AT_STAGE_BYTES >> 4) + 2, 1);
            wg_commit();
            wg_wait<0>();
            fence_regs(sc);
            if (lane == 0 && (st > 0 || rev > 0)) mbar_arrive(empty0 + 8 * ((st + AT_STAGES - 1) % AT_STAGES));
#pragma unroll
            for (int i = 0; i < 16; i++) pa[i] = pack_bf16(attn_exp(sc[2 * i], 2 * i), attn_exp(sc[2 * i + 1], 2 * i + 1));
            wg_fence();
            attn_pv(o, pa, v_lo0 + st * 16 * PV_STEP, 0);
            wg_commit();
#pragma unroll
            for (int i = 0; i < 16; i++) pb[i] = pack_bf16(attn_exp(sc[32 + 2 * i], 2 * i), attn_exp(sc[32 + 2 * i + 1], 2 * i + 1));
            wg_wait<0>();
            wg_fence();
            attn_pv(o, pb, v_lo0 + (st * 16 + 4) * PV_STEP, 0);
            wg_commit();
        }
    }
    wg_wait<0>();
    fence_regs(o);
    const int row0 = qchunk * 512 + pass * 256 + wg * 64 + warp * 16 + (lane >> 2);
    attn_store_o(o, p, head, row0, lane);
    }
}

__device__ __forceinline__ void attn_safe(const AttnParams& p, uint32_t base, uint32_t full0, uint32_t empty0, int head, int qchunk) {
    const int wg = __shfl_sync(0xffffffffu, threadIdx.x >> 7, 0), warp = (threadIdx.x >> 5) & 3, lane = threadIdx.x & 31;
    const uint32_t k_lo0 = desc_lo(base, 16), v_lo0 = desc_lo(base + 8192, AT_ONES_OFF - 8192);
#pragma unroll 1
    for (int pass = 0; pass < 2; pass++) {
        const int row0 = qchunk * 512 + pass * 256 + wg * 64 + warp * 16 + (lane >> 2);
        const uint32_t q = desc_lo(base + AT_Q_OFF + (pass * 256 + wg * 64) * 64, 16);
        float o[20];
#pragma unroll
        for (int i = 0; i < 20; i++) o[i] = 0.f;
        float m0 = -INFINITY, m1 = -INFINITY;
#pragma unroll 1
        for (int t = 0; t < 32; t++) {
            const int g = pass * 16 + (t >> 1), half = t & 1;
            const int st = g % AT_STAGES;
            const uint32_t kb = k_lo0 + st * (AT_STAGE_BYTES >> 4), vb = v_lo0 + st * 16 * PV_STEP;
            if (half == 0) { attn_refill(p, base, full0, empty0, g, head); mbar_wait(full0 + 8 * st, (g / AT_STAGES) & 1); }
            float cur[32];
            wg_fence();
            attn_qk(cur, q, kb + half * 256);
            wg_commit();
            wg_wait<0>();
            fence_regs(cur);
            float x0 = cur[0], x1 = cur[2];
#pragma unroll
            for (int i = 0; i < 8; i++) { x0 = fmaxf(x0, fmaxf(cur[4 * i], cur[4 * i + 1])); x1 = fmaxf(x1, fmaxf(cur[4 * i + 2], cur[4 * i + 3])); }
            x0 = fmaxf(x0, __shfl_xor_sync(0xffffffffu, x0, 1)); x1 = fmaxf(x1, __shfl_xor_sync(0xffffffffu, x1, 1));
            x0 = fmaxf(x0, __shfl_xor_sync(0xffffffffu, x0, 2)); x1 = fmaxf(x1, __shfl_xor_sync(0xffffffffu, x1, 2));
            const float n0 = fmaxf(m0, x0), n1 = fmaxf(m1, x1);
            const float a0 = ex2(m0 - n0), a1 = ex2(m1 - n1);
            m0 = n0; m1 = n1;
            uint32_t pr[16];
#pragma unroll
            for (int i = 0; i < 8; i++) {
                pr[2 * i] = pack_bf16(ex2(cur[4 * i] - n0), ex2(cur[4 * i + 1] - n0));
                pr[2 * i + 1] = pack_bf16(ex2(cur[4 * i + 2] - n1), ex2(cur[4 * i + 3] - n1));
            }
#pragma unroll
            for (int i = 0; i < 5; i++) { o[4 * i] *= a0; o[4 * i + 1] *= a0; o[4 * i + 2] *= a1; o[4 * i + 3] *= a1; }
            wg_fence();
            attn_pv(o, pr, vb + half * 4 * PV_STEP, 0);
            wg_commit();
            wg_wait<0>();
            fence_regs(o);
            if (half == 1 && lane == 0) mbar_arrive(empty0 + 8 * st);
        }
        attn_store_o(o, p, head, row0, lane);
    }
}

__global__ void __launch_bounds__(512, 1) attn_kernel(const __grid_constant__ AttnParams p) {
    extern __shared__ __align__(1024) uint8_t smem_raw[];
    pdl_launch();
    const uint32_t base = smem_u32(smem_raw);
    const uint32_t full0 = base + AT_BAR_OFF, empty0 = full0 + 8 * AT_STAGES;
    const int head = blockIdx.x >> 2, qchunk = blockIdx.x & 3;
    if (threadIdx.x == 0) {
        if (base & 1023) __trap();
        prefetch_map(&p.kv);
        for (int i = 0; i < AT_STAGES; i++) { mbar_init(full0 + 8 * i, 1); mbar_init(empty0 + 8 * i, 16); }
        mbar_init(empty0 + 8 * AT_STAGES, 1);
        fence_barrier_init();
    }
    if (threadIdx.x < 256) reinterpret_cast<uint32_t*>(smem_raw + AT_ONES_OFF)[threadIdx.x] = 0x3F803F80u;
    fence_proxy_async();
    __syncthreads();
    pdl_wait();
    TL(2, 0);
    if (threadIdx.x == 0) {
        const uint32_t qbar = empty0 + 8 * AT_STAGES;
        mbar_expect_tx(qbar, 32768);
        for (int i = 0; i < 4; i++) tma_ld2(base + AT_Q_OFF + i * 8192, &p.kv, qbar, 0, head * SEQ + qchunk * 512 + i * 128);
        for (int g = 0; g < AT_STAGES; g++) attn_issue_tile(p, base, full0, g, head);
    }
    __syncwarp();
    const float qn = __uint_as_float(g_norm[head]), kn = __uint_as_float(g_norm[NH + head]), vn = __uint_as_float(g_norm[2 * NH + head]);
    const bool bounded = (qn * kn <= 1.0e4f) && (vn <= 1.0e9f);
    mbar_wait(empty0 + 8 * AT_STAGES, 0);
    if (bounded) attn_fast(p, base, full0, empty0, head, qchunk);
    else attn_safe(p, base, full0, empty0, head, qchunk);
    TL(2, 3);
}

struct ResParams { CUtensorMap a, b, res, out; const bf16* bias; };
template <bool MIX2>
struct ResCfg {
    static constexpr int MB = 1, BN = 128, KSTEPS = MIX2 ? 56 : 16, STAGES = 6, A_BYTES = 16384, B_BYTES = 16384;
    static constexpr int STAGE_BYTES = A_BYTES + B_BYTES, STG_OFF = STAGES * STAGE_BYTES, BAR_OFF = STG_OFF + 32768, SMEM = BAR_OFF + 128;
    static __device__ __forceinline__ void load_w(const ResParams& p, uint32_t sb, uint32_t bar, int k, int tm, int tn) {
        if (MIX2) tma_ld3(sb, &p.a, bar, 0, k * 64, tm * 2);
        else tma_ld3(sb + A_BYTES, &p.b, bar, 0, k * 64, tn * 2);
    }
    static __device__ __forceinline__ void load_x(const ResParams& p, uint32_t sb, uint32_t bar, int k, int tm, int tn) {
        if (MIX2) tma_ld2(sb + A_BYTES, &p.b, bar, k * 64, tn * 128);
        else tma_ld2(sb, &p.a, bar, k * 64, tm * 128);
    }
    static __device__ __forceinline__ void load_aux(const ResParams& p, const GemmSmem& s, int tm, int tn) {
        mbar_expect_tx(s.aux, 32768);
        tma_ld2(s.base + STG_OFF, &p.res, s.aux, tn * 128, tm * 128);
        tma_ld2(s.base + STG_OFF + 16384, &p.res, s.aux, tn * 128 + 64, tm * 128);
    }
    static __device__ __forceinline__ uint32_t desc_a(uint32_t sb, int wg, int m, int kk) {
        return MIX2 ? desc_lo(sb + wg * 8192 + kk * 2048, 8192) : desc_lo(sb + wg * 8192 + kk * 32, 16);
    }
    static __device__ __forceinline__ uint32_t desc_b(uint32_t sb, int kk) {
        return MIX2 ? desc_lo(sb + A_BYTES + kk * 32, 16) : desc_lo(sb + A_BYTES + kk * 2048, 8192);
    }
    static __device__ __forceinline__ void mma(float (&d)[64], uint32_t a, uint32_t b, int sc) {
        if (MIX2) mma_mix2(d, a, b, sc); else mma_wo(d, a, b, sc);
    }
};
template <bool MIX2>
__global__ void __launch_bounds__(384, 1) res_gemm_kernel(const __grid_constant__ ResParams p) {
    using C = ResCfg<MIX2>;
    extern __shared__ __align__(1024) uint8_t smem_raw[];
    pdl_launch();
    const int tm = blockIdx.x & 15, tn = blockIdx.x >> 4;
    if (threadIdx.x == 0) { prefetch_map(&p.a); prefetch_map(&p.b); prefetch_map(&p.res); prefetch_map(&p.out); }
    const GemmSmem s = gemm_setup<C>(smem_raw);
    const int wgi = __shfl_sync(0xffffffffu, threadIdx.x >> 7, 0);
    if (wgi == 0) {
        reg_dealloc<40>();
        if (threadIdx.x == 0) gemm_producer<C>(s, p, tm, tn);
    } else {
        reg_alloc<232>();
        const int wg = wgi - 1, warp = (threadIdx.x >> 5) & 3, lane = threadIdx.x & 31;
        float acc[1][64];
        pdl_wait();
        TL(MIX2 ? 6 : 3, 0);
        const int r0 = wg * 64 + warp * 16 + (lane >> 2);
        float b0 = 0.f, b1 = 0.f;
        if (MIX2) { b0 = __bfloat162float(p.bias[tm * 128 + r0]); b1 = __bfloat162float(p.bias[tm * 128 + r0 + 8]); }
        gemm_mainloop<C>(s, wg, acc);
        TL(MIX2 ? 6 : 3, 1);
        mbar_wait(s.aux, 0);
        uint8_t* stg = smem_raw + C::STG_OFF;
#pragma unroll
        for (int j = 0; j < 16; j++) {
            const int off = (j >> 3) * 16384 + r0 * 128 + (((j & 7) ^ (r0 & 7)) << 4) + (lane & 3) * 4;
            uint32_t* p0 = reinterpret_cast<uint32_t*>(stg + off);
            uint32_t* p1 = reinterpret_cast<uint32_t*>(stg + off + 8 * 128);
            const uint32_t x0 = *p0, x1 = *p1;
            *p0 = pack_bf16(acc[0][4 * j] + b0 + bf_lo(x0), acc[0][4 * j + 1] + b0 + bf_hi(x0));
            *p1 = pack_bf16(acc[0][4 * j + 2] + b1 + bf_lo(x1), acc[0][4 * j + 3] + b1 + bf_hi(x1));
        }
        fence_proxy_async();
        named_bar(2 + wg, 128);
        if ((threadIdx.x & 127) == 0) {
            tma_st2(&p.out, s.base + C::STG_OFF + wg * 8192, tn * 128, tm * 128 + wg * 64);
            tma_st2(&p.out, s.base + C::STG_OFF + 16384 + wg * 8192, tn * 128 + 64, tm * 128 + wg * 64);
            tma_st_commit();
            tma_st_wait();
        }
        TL(MIX2 ? 6 : 3, 3);
    }
}

struct Mix1Params { CUtensorMap hn, w1, out; const bf16* bias; };
struct Mix1Cfg {
    static constexpr int MB = 1, BN = 224, KSTEPS = 32, STAGES = 5, A_BYTES = 16384, B_BYTES = 28672;
    static constexpr int STAGE_BYTES = A_BYTES + B_BYTES, BIAS_OFF = STAGES * STAGE_BYTES, BAR_OFF = BIAS_OFF + 1024, SMEM = BAR_OFF + 128;
    static __device__ __forceinline__ void load_w(const Mix1Params& p, uint32_t sb, uint32_t bar, int k, int tm, int tn) { tma_ld3(sb + A_BYTES, &p.w1, bar, 0, k * 64, tn * 7); }
    static __device__ __forceinline__ void load_x(const Mix1Params& p, uint32_t sb, uint32_t bar, int k, int tm, int tn) { tma_ld3(sb, &p.hn, bar, 0, k * 64, tm * 2); }
    static __device__ __forceinline__ void load_aux(const Mix1Params&, const GemmSmem&, int, int) {}
    static __device__ __forceinline__ uint32_t desc_a(uint32_t sb, int wg, int m, int kk) { return desc_lo(sb + wg * 8192 + kk * 2048, 8192); }
    static __device__ __forceinline__ uint32_t desc_b(uint32_t sb, int kk) { return desc_lo(sb + A_BYTES + kk * 1024, 4096); }
    static __device__ __forceinline__ void mma(float (&d)[112], uint32_t a, uint32_t b, int sc) { mma_mix1(d, a, b, sc); }
};
__global__ void __launch_bounds__(384, 1) mix1_kernel(const __grid_constant__ Mix1Params p) {
    using C = Mix1Cfg;
    extern __shared__ __align__(1024) uint8_t smem_raw[];
    pdl_launch();
    const int tm = blockIdx.x & 7, tn = blockIdx.x >> 3;
    if (threadIdx.x == 0) { prefetch_map(&p.hn); prefetch_map(&p.w1); prefetch_map(&p.out); }
    float* sbias = reinterpret_cast<float*>(smem_raw + C::BIAS_OFF);
    if (threadIdx.x < 224) sbias[threadIdx.x] = __bfloat162float(p.bias[tn * 224 + threadIdx.x]);
    const GemmSmem s = gemm_setup<C>(smem_raw);
    const int wgi = __shfl_sync(0xffffffffu, threadIdx.x >> 7, 0);
    if (wgi == 0) {
        reg_dealloc<40>();
        if (threadIdx.x == 0) gemm_producer<C>(s, p, tm, tn);
    } else {
        reg_alloc<232>();
        const int wg = wgi - 1, warp = (threadIdx.x >> 5) & 3, lane = threadIdx.x & 31;
        float acc[1][112];
        pdl_wait();
        TL(5, 0);
        gemm_mainloop<C>(s, wg, acc);
        TL(5, 1);
        named_bar(1, 256);
        const int arow = warp * 16 + ((lane >> 3) & 1) * 8 + (lane & 7);
        const uint32_t stg = s.base + wg * 28672;
#pragma unroll
        for (int jp = 0; jp < 14; jp++) {
            float v[8];
#pragma unroll
            for (int h = 0; h < 2; h++) {
                const float2 bb = *reinterpret_cast<const float2*>(sbias + (jp * 2 + h) * 8 + (lane & 3) * 2);
#pragma unroll
                for (int i = 0; i < 4; i++) {
                    const float x = acc[0][jp * 8 + h * 4 + i] + ((i & 1) ? bb.y : bb.x);
                    const float inner = x * fmaf(x * x, 0.0356774081363f, 0.7978845608029f);
                    const float hx = 0.5f * x;
                    v[h * 4 + i] = fmaf(hx, tanh_fast(inner), hx);
                }
            }
            const int j = jp * 2 + (lane >> 4);
            const uint32_t addr = stg + (j >> 2) * 4096 + arow * 64 + (((j & 3) ^ ((arow >> 1) & 3)) << 4);
            stmatrix_x4(addr, pack_bf16(v[0], v[1]), pack_bf16(v[2], v[3]), pack_bf16(v[4], v[5]), pack_bf16(v[6], v[7]));
        }
        fence_proxy_async();
        named_bar(2 + wg, 128);
        if ((threadIdx.x & 127) == 0) {
            tma_st3(&p.out, stg, 0, tm * 128 + wg * 64, tn * 7);
            tma_st_commit();
            tma_st_wait();
        }
        TL(5, 3);
    }
}

typedef CUresult (*EncodeFn)(CUtensorMap*, CUtensorMapDataType, cuuint32_t, void*, const cuuint64_t*, const cuuint64_t*, const cuuint32_t*,
                             const cuuint32_t*, CUtensorMapInterleave, CUtensorMapSwizzle, CUtensorMapL2promotion, CUtensorMapFloatOOBfill);
EncodeFn g_encode;

void make_map(CUtensorMap* m, const void* ptr, int rank, const uint64_t* dims, const uint64_t* strides_bytes, const uint32_t* box, CUtensorMapSwizzle swz) {
    cuuint64_t d[5], st[5]; cuuint32_t b[5], es[5];
    for (int i = 0; i < rank; i++) { d[i] = dims[i]; b[i] = box[i]; es[i] = 1; }
    for (int i = 0; i + 1 < rank; i++) st[i] = strides_bytes[i];
    CUresult r = g_encode(m, CU_TENSOR_MAP_DATA_TYPE_BFLOAT16, rank, const_cast<void*>(ptr), d, st, b, es, CU_TENSOR_MAP_INTERLEAVE_NONE, swz,
                          CU_TENSOR_MAP_L2_PROMOTION_L2_128B, CU_TENSOR_MAP_FLOAT_OOB_FILL_NONE);
    if (r != CUDA_SUCCESS) fprintf(stderr, "cuTensorMapEncodeTiled failed: %d\n", (int)r);
}
void map2d(CUtensorMap* m, const void* ptr, uint64_t cols, uint64_t rows, uint32_t bc, uint32_t br, CUtensorMapSwizzle swz) {
    uint64_t dims[2] = {cols, rows}, st[1] = {cols * 2}; uint32_t box[2] = {bc, br};
    make_map(m, ptr, 2, dims, st, box, swz);
}
void map3d(CUtensorMap* m, const void* ptr, uint64_t cols, uint64_t rows, uint32_t inner, uint32_t br, uint32_t nblk, CUtensorMapSwizzle swz) {
    uint64_t dims[3] = {inner, rows, cols / inner}, st[2] = {cols * 2, (uint64_t)inner * 2}; uint32_t box[3] = {inner, br, nblk};
    make_map(m, ptr, 3, dims, st, box, swz);
}

template <class... KArgs, class... Args>
void launch(void (*kern)(KArgs...), int grid, int block, int smem, bool pdl, Args&&... args) {
    cudaLaunchConfig_t cfg = {};
    cfg.gridDim = dim3(grid); cfg.blockDim = dim3(block); cfg.dynamicSmemBytes = smem; cfg.stream = 0;
    cudaLaunchAttribute at[1];
    at[0].id = cudaLaunchAttributeProgrammaticStreamSerialization; at[0].val.programmaticStreamSerializationAllowed = 1;
    cfg.attrs = at; cfg.numAttrs = pdl ? 1 : 0;
    cudaError_t e = cudaLaunchKernelEx(&cfg, kern, KArgs(args)...);
    if (e != cudaSuccess) fprintf(stderr, "launch failed: %s\n", cudaGetErrorString(e));
}

struct HostState {
    bool ready;
    const void* key[9];
    QkvParams qkv; AttnParams attn; ResParams wo, mix2; Mix1Params mix1;
    bf16 *xn, *qkvp, *o, *h, *hn, *u;
};
HostState g_hs;

}

#define USE_PDL 1

extern "C" void kernel_launch(void* const* d_in, const int* in_sizes, int n_in, void* d_out, int out_size) {
    const bf16* x = (const bf16*)d_in[0];
    const bf16* wqkv = (const bf16*)d_in[1];
    const bf16* wo = (const bf16*)d_in[2];
    const bf16* w1 = (const bf16*)d_in[4];
    const bf16* b1 = (const bf16*)d_in[5];
    const bf16* w2 = (const bf16*)d_in[6];
    const bf16* b2 = (const bf16*)d_in[7];
    HostState& hs = g_hs;
    bool same = hs.ready;
    for (int i = 0; i < 8 && same; i++) same = (hs.key[i] == d_in[i]);
    same = same && hs.key[8] == d_out;
    if (!same) {
        if (!g_encode) {
            void* fn = nullptr; cudaDriverEntryPointQueryResult qr;
            cudaGetDriverEntryPoint("cuTensorMapEncodeTiled", &fn, cudaEnableDefault, &qr);
            g_encode = (EncodeFn)fn;
            cudaFuncSetAttribute(qkv_kernel, cudaFuncAttributeMaxDynamicSharedMemorySize, QkvCfg::SMEM);
            cudaFuncSetAttribute(attn_kernel, cudaFuncAttributeMaxDynamicSharedMemorySize, AT_SMEM);
            cudaFuncSetAttribute(res_gemm_kernel<false>, cudaFuncAttributeMaxDynamicSharedMemorySize, ResCfg<false>::SMEM);
            cudaFuncSetAttribute(res_gemm_kernel<true>, cudaFuncAttributeMaxDynamicSharedMemorySize, ResCfg<true>::SMEM);
            cudaFuncSetAttribute(mix1_kernel, cudaFuncAttributeMaxDynamicSharedMemorySize, Mix1Cfg::SMEM);
        }
        cudaGetSymbolAddress((void**)&hs.xn, g_xn); cudaGetSymbolAddress((void**)&hs.qkvp, g_qkv); cudaGetSymbolAddress((void**)&hs.o, g_o);
        cudaGetSymbolAddress((void**)&hs.h, g_h); cudaGetSymbolAddress((void**)&hs.hn, g_hn); cudaGetSymbolAddress((void**)&hs.u, g_u);
        const CUtensorMapSwizzle S128 = CU_TENSOR_MAP_SWIZZLE_128B, S64 = CU_TENSOR_MAP_SWIZZLE_64B;
        map2d(&hs.qkv.xn, hs.xn, DM, SEQ, 64, 256, S128);
        {
            uint64_t dims[4] = {64, (uint64_t)DM, 3, 16}, st[3] = {3 * DM * 2, DM * 2, 128}; uint32_t box[4] = {64, 64, 3, 1};
            make_map(&hs.qkv.w, wqkv, 4, dims, st, box, S128);
        }
        map2d(&hs.qkv.out, hs.qkvp, HD, 3 * NH * SEQ, 32, 128, S64);
        hs.attn.kv = hs.qkv.out; hs.attn.o = hs.o;
        map2d(&hs.wo.a, hs.o, DM, SEQ, 64, 128, S128);
        map3d(&hs.wo.b, wo, DM, DM, 64, 64, 2, S128);
        map2d(&hs.wo.res, x, DM, SEQ, 64, 128, S128);
        map2d(&hs.wo.out, hs.h, DM, SEQ, 64, 64, S128);
        hs.wo.bias = nullptr;
        map3d(&hs.mix1.hn, hs.hn, DM, SEQ, 64, 64, 2, S128);
        map3d(&hs.mix1.w1, w1, FF, SEQ, 32, 64, 7, S64);
        map3d(&hs.mix1.out, hs.u, FF, DM, 32, 64, 7, S64);
        hs.mix1.bias = b1;
        map3d(&hs.mix2.a, w2, SEQ, FF, 64, 64, 2, S128);
        map2d(&hs.mix2.b, hs.u, FF, DM, 64, 128, S128);
        map2d(&hs.mix2.res, hs.h, DM, SEQ, 64, 128, S128);
        map2d(&hs.mix2.out, d_out, DM, SEQ, 64, 64, S128);
        hs.mix2.bias = b2;
        for (int i = 0; i < 8; i++) hs.key[i] = d_in[i];
        hs.key[8] = d_out;
        hs.ready = true;
    }
    const bool pdl = USE_PDL;
    launch(ln_kernel<false>, SEQ / 8, 256, 0, false, x, hs.xn);
    launch(qkv_kernel, 128, 384, QkvCfg::SMEM, pdl, hs.qkv);
    launch(attn_kernel, 128, 512, AT_SMEM, pdl, hs.attn);
    launch(res_gemm_kernel<false>, 128, 384, ResCfg<false>::SMEM, pdl, hs.wo);
    launch(ln_kernel<true>, SEQ / 8, 256, 0, pdl, (const bf16*)hs.h, hs.hn);
    launch(mix1_kernel, 128, 384, Mix1Cfg::SMEM, pdl, hs.mix1);
    launch(res_gemm_kernel<true>, 128, 384, ResCfg<true>::SMEM, pdl, hs.mix2);
}
```

```cpp
#include <cuda_runtime.h>
#include <cuda_bf16.h>
#include <cuda.h>
#include <stdint.h>
#include <stdio.h>

typedef __nv_bfloat16 bf16;

namespace {

#define SKEW 0
#define POLY_MASK_B POLY_MASK
#define POLY_MASK 0x12492449u
constexpr int SEQ = 2048, DM = 1024, NH = 32, HD = 32, FF = 3584;

__device__ __align__(1024) bf16 g_qkv[3 * NH * SEQ * HD];
__device__ __align__(1024) bf16 g_o[SEQ * DM];
__device__ __align__(1024) bf16 g_h[SEQ * DM];
__device__ __align__(1024) bf16 g_hn[SEQ * DM];
__device__ __align__(1024) bf16 g_u[DM * FF];
__device__ uint32_t g_norm[3 * NH * 16];
__device__ float2 g_rowstat[SEQ];
__device__ float g_colsum[8 * 3 * DM];
__device__ float2 g_hpart[SEQ * 8];
__device__ uint32_t g_cnt_ln[32];
__device__ uint32_t g_cnt_row[8], g_cnt_col[16];

#define TL(kern, slot)
#define AT(slot)

__device__ __forceinline__ uint32_t smem_u32(const void* p) { return (uint32_t)__cvta_generic_to_shared(p); }
__device__ __forceinline__ void mbar_init(uint32_t bar, uint32_t cnt) { asm volatile("mbarrier.init.shared::cta.b64 [%0], %1;" :: "r"(bar), "r"(cnt) : "memory"); }
__device__ __forceinline__ void mbar_expect_tx(uint32_t bar, uint32_t bytes) { asm volatile("mbarrier.arrive.expect_tx.shared::cta.b64 _, [%0], %1;" :: "r"(bar), "r"(bytes) : "memory"); }
__device__ __forceinline__ void mbar_arrive(uint32_t bar) { asm volatile("mbarrier.arrive.shared::cta.b64 _, [%0];" :: "r"(bar) : "memory"); }
__device__ __forceinline__ void mbar_wait(uint32_t bar, uint32_t parity) {
    asm volatile("{\n.reg .pred p;\nWAIT_%=:\nmbarrier.try_wait.parity.shared::cta.b64 p, [%0], %1;\n@p bra DONE_%=;\nbra WAIT_%=;\nDONE_%=:\n}" :: "r"(bar), "r"(parity) : "memory");
}
__device__ __forceinline__ void fence_barrier_init() { asm volatile("fence.mbarrier_init.release.cluster;" ::: "memory"); }
__device__ __forceinline__ void fence_proxy_async() { asm volatile("fence.proxy.async.shared::cta;" ::: "memory"); }
__device__ __forceinline__ void pdl_launch() { asm volatile("griddepcontrol.launch_dependents;" ::: "memory"); }
__device__ __forceinline__ void pdl_wait() { asm volatile("griddepcontrol.wait;" ::: "memory"); }
__device__ __forceinline__ void named_bar(int id, int n) { asm volatile("bar.sync %0, %1;" :: "r"(id), "r"(n) : "memory"); }
__device__ __forceinline__ void prefetch_map(const CUtensorMap* m) { asm volatile("prefetch.tensormap [%0];" :: "l"(m) : "memory"); }

__device__ __forceinline__ void tma_ld2(uint32_t dst, const CUtensorMap* m, uint32_t bar, int c0, int c1) {
    asm volatile("cp.async.bulk.tensor.2d.shared::cluster.global.mbarrier::complete_tx::bytes [%0], [%1, {%3, %4}], [%2];"
                 :: "r"(dst), "l"(m), "r"(bar), "r"(c0), "r"(c1) : "memory");
}
__device__ __forceinline__ void tma_ld3(uint32_t dst, const CUtensorMap* m, uint32_t bar, int c0, int c1, int c2) {
    asm volatile("cp.async.bulk.tensor.3d.shared::cluster.global.mbarrier::complete_tx::bytes [%0], [%1, {%3, %4, %5}], [%2];"
                 :: "r"(dst), "l"(m), "r"(bar), "r"(c0), "r"(c1), "r"(c2) : "memory");
}
__device__ __forceinline__ void tma_ld4(uint32_t dst, const CUtensorMap* m, uint32_t bar, int c0, int c1, int c2, int c3) {
    asm volatile("cp.async.bulk.tensor.4d.shared::cluster.global.mbarrier::complete_tx::bytes [%0], [%1, {%3, %4, %5, %6}], [%2];"
                 :: "r"(dst), "l"(m), "r"(bar), "r"(c0), "r"(c1), "r"(c2), "r"(c3) : "memory");
}
__device__ __forceinline__ void tma_st2(const CUtensorMap* m, uint32_t src, int c0, int c1) {
    asm volatile("cp.async.bulk.tensor.2d.global.shared::cta.bulk_group [%0, {%2, %3}], [%1];" :: "l"(m), "r"(src), "r"(c0), "r"(c1) : "memory");
}
__device__ __forceinline__ void tma_st3(const CUtensorMap* m, uint32_t src, int c0, int c1, int c2) {
    asm volatile("cp.async.bulk.tensor.3d.global.shared::cta.bulk_group [%0, {%2, %3, %4}], [%1];" :: "l"(m), "r"(src), "r"(c0), "r"(c1), "r"(c2) : "memory");
}
__device__ __forceinline__ void tma_st_commit() { asm volatile("cp.async.bulk.commit_group;" ::: "memory"); }
__device__ __forceinline__ void tma_st_wait() { asm volatile("cp.async.bulk.wait_group.read 0;" ::: "memory"); }

__device__ __forceinline__ void wg_fence() { asm volatile("wgmma.fence.sync.aligned;" ::: "memory"); }
__device__ __forceinline__ void wg_commit() { asm volatile("wgmma.commit_group.sync.aligned;" ::: "memory"); }
template <int N> __device__ __forceinline__ void wg_wait() { asm volatile("wgmma.wait_group.sync.aligned %0;" :: "n"(N) : "memory"); }
template <int R> __device__ __forceinline__ void reg_alloc() { asm volatile("setmaxnreg.inc.sync.aligned.u32 %0;" :: "n"(R)); }
template <int R> __device__ __forceinline__ void reg_dealloc() { asm volatile("setmaxnreg.dec.sync.aligned.u32 %0;" :: "n"(R)); }
template <int N> __device__ __forceinline__ void fence_regs(float (&d)[N]) {
#pragma unroll
    for (int i = 0; i < N; i++) asm volatile("" : "+f"(d[i]) :: "memory");
}

__device__ __forceinline__ uint32_t desc_lo(uint32_t addr, uint32_t lbo) { return (addr >> 4) | ((lbo >> 4) << 16); }
__device__ __forceinline__ uint32_t pack_bf16(float lo, float hi) { uint32_t d; asm("cvt.rn.bf16x2.f32 %0, %1, %2;" : "=r"(d) : "f"(hi), "f"(lo)); return d; }
__device__ __forceinline__ float bf_lo(uint32_t v) { return __uint_as_float(v << 16); }
__device__ __forceinline__ float bf_hi(uint32_t v) { return __uint_as_float(v & 0xFFFF0000u); }
__device__ __forceinline__ void stmatrix_x4(uint32_t addr, uint32_t r0, uint32_t r1, uint32_t r2, uint32_t r3) {
    asm volatile("stmatrix.sync.aligned.m8n8.x4.shared.b16 [%0], {%1, %2, %3, %4};" :: "r"(addr), "r"(r0), "r"(r1), "r"(r2), "r"(r3) : "memory");
}
__device__ __forceinline__ float ex2(float x) { float y; asm("ex2.approx.ftz.f32 %0, %1;" : "=f"(y) : "f"(x)); return y; }
__device__ __forceinline__ float tanh_fast(float x) { float y; asm("tanh.approx.f32 %0, %1;" : "=f"(y) : "f"(x)); return y; }

__device__ __forceinline__ void mma_qkv(float (&d)[96], uint32_t alo, uint32_t blo, int scale_d) {
    asm volatile("{\n.reg .pred p;\n.reg .b64 da, db;\nsetp.ne.b32 p, %98, 0;\nmov.b64 da, {%96, 0x40000040};\nmov.b64 db, {%97, 0x40000040};\n"
        "wgmma.mma_async.sync.aligned.m64n192k16.f32.bf16.bf16 {"
        "%0, %1, %2, %3, %4, %5, %6, %7, %8, %9, %10, %11, %12, %13, %14, %15, %16, %17, %18, %19, %20, %21, %22, %23, %24, %25, %26, %27, %28, %29, %30, %31,  "
        "%32, %33, %34, %35, %36, %37, %38, %39, %40, %41, %42, %43, %44, %45, %46, %47, %48, %49, %50, %51, %52, %53, %54, %55, %56, %57, %58, %59, %60, %61,  "
        "%62, %63, %64, %65, %66, %67, %68, %69, %70, %71, %72, %73, %74, %75, %76, %77, %78, %79, %80, %81, %82, %83, %84, %85, %86, %87, %88, %89, %90, %91,  "
        "%92, %93, %94, %95 "
        "}, da, db, p, 1, 1, 0, 1;\n}\n"
        : "+f"(d[0]), "+f"(d[1]), "+f"(d[2]), "+f"(d[3]), "+f"(d[4]), "+f"(d[5]), "+f"(d[6]), "+f"(d[7]), "+f"(d[8]), "+f"(d[9]), "+f"(d[10]), "+f"(d[11]),
          "+f"(d[12]), "+f"(d[13]), "+f"(d[14]), "+f"(d[15]), "+f"(d[16]), "+f"(d[17]), "+f"(d[18]), "+f"(d[19]), "+f"(d[20]), "+f"(d[21]), "+f"(d[22]),
          "+f"(d[23]), "+f"(d[24]), "+f"(d[25]), "+f"(d[26]), "+f"(d[27]), "+f"(d[28]), "+f"(d[29]), "+f"(d[30]), "+f"(d[31]), "+f"(d[32]), "+f"(d[33]),
          "+f"(d[34]), "+f"(d[35]), "+f"(d[36]), "+f"(d[37]), "+f"(d[38]), "+f"(d[39]), "+f"(d[40]), "+f"(d[41]), "+f"(d[42]), "+f"(d[43]), "+f"(d[44]),
          "+f"(d[45]), "+f"(d[46]), "+f"(d[47]), "+f"(d[48]), "+f"(d[49]), "+f"(d[50]), "+f"(d[51]), "+f"(d[52]), "+f"(d[53]), "+f"(d[54]), "+f"(d[55]),
          "+f"(d[56]), "+f"(d[57]), "+f"(d[58]), "+f"(d[59]), "+f"(d[60]), "+f"(d[61]), "+f"(d[62]), "+f"(d[63]), "+f"(d[64]), "+f"(d[65]), "+f"(d[66]),
          "+f"(d[67]), "+f"(d[68]), "+f"(d[69]), "+f"(d[70]), "+f"(d[71]), "+f"(d[72]), "+f"(d[73]), "+f"(d[74]), "+f"(d[75]), "+f"(d[76]), "+f"(d[77]),
          "+f"(d[78]), "+f"(d[79]), "+f"(d[80]), "+f"(d[81]), "+f"(d[82]), "+f"(d[83]), "+f"(d[84]), "+f"(d[85]), "+f"(d[86]), "+f"(d[87]), "+f"(d[88]),
          "+f"(d[89]), "+f"(d[90]), "+f"(d[91]), "+f"(d[92]), "+f"(d[93]), "+f"(d[94]), "+f"(d[95])
        : "r"(alo), "r"(blo), "r"(scale_d));
}
__device__ __forceinline__ void mma_wo(float (&d)[64], uint32_t alo, uint32_t blo, int scale_d) {
    asm volatile("{\n.reg .pred p;\n.reg .b64 da, db;\nsetp.ne.b32 p, %66, 0;\nmov.b64 da, {%64, 0x40000040};\nmov.b64 db, {%65, 0x40000040};\n"
        "wgmma.mma_async.sync.aligned.m64n128k16.f32.bf16.bf16 {"
        "%0, %1, %2, %3, %4, %5, %6, %7, %8, %9, %10, %11, %12, %13, %14, %15, %16, %17, %18, %19, %20, %21, %22, %23, %24, %25, %26, %27, %28, %29, %30, %31,  "
        "%32, %33, %34, %35, %36, %37, %38, %39, %40, %41, %42, %43, %44, %45, %46, %47, %48, %49, %50, %51, %52, %53, %54, %55, %56, %57, %58, %59, %60, %61,  "
        "%62, %63 "
        "}, da, db, p, 1, 1, 0, 1;\n}\n"
        : "+f"(d[0]), "+f"(d[1]), "+f"(d[2]), "+f"(d[3]), "+f"(d[4]), "+f"(d[5]), "+f"(d[6]), "+f"(d[7]), "+f"(d[8]), "+f"(d[9]), "+f"(d[10]), "+f"(d[11]),
          "+f"(d[12]), "+f"(d[13]), "+f"(d[14]), "+f"(d[15]), "+f"(d[16]), "+f"(d[17]), "+f"(d[18]), "+f"(d[19]), "+f"(d[20]), "+f"(d[21]), "+f"(d[22]),
          "+f"(d[23]), "+f"(d[24]), "+f"(d[25]), "+f"(d[26]), "+f"(d[27]), "+f"(d[28]), "+f"(d[29]), "+f"(d[30]), "+f"(d[31]), "+f"(d[32]), "+f"(d[33]),
          "+f"(d[34]), "+f"(d[35]), "+f"(d[36]), "+f"(d[37]), "+f"(d[38]), "+f"(d[39]), "+f"(d[40]), "+f"(d[41]), "+f"(d[42]), "+f"(d[43]), "+f"(d[44]),
          "+f"(d[45]), "+f"(d[46]), "+f"(d[47]), "+f"(d[48]), "+f"(d[49]), "+f"(d[50]), "+f"(d[51]), "+f"(d[52]), "+f"(d[53]), "+f"(d[54]), "+f"(d[55]),
          "+f"(d[56]), "+f"(d[57]), "+f"(d[58]), "+f"(d[59]), "+f"(d[60]), "+f"(d[61]), "+f"(d[62]), "+f"(d[63])
        : "r"(alo), "r"(blo), "r"(scale_d));
}
__device__ __forceinline__ void mma_mix2(float (&d)[64], uint32_t alo, uint32_t blo, int scale_d) {
    asm volatile("{\n.reg .pred p;\n.reg .b64 da, db;\nsetp.ne.b32 p, %66, 0;\nmov.b64 da, {%64, 0x40000040};\nmov.b64 db, {%65, 0x40000040};\n"
        "wgmma.mma_async.sync.aligned.m64n128k16.f32.bf16.bf16 {"
        "%0, %1, %2, %3, %4, %5, %6, %7, %8, %9, %10, %11, %12, %13, %14, %15, %16, %17, %18, %19, %20, %21, %22, %23, %24, %25, %26, %27, %28, %29, %30, %31,  "
        "%32, %33, %34, %35, %36, %37, %38, %39, %40, %41, %42, %43, %44, %45, %46, %47, %48, %49, %50, %51, %52, %53, %54, %55, %56, %57, %58, %59, %60, %61,  "
        "%62, %63 "
        "}, da, db, p, 1, 1, 1, 0;\n}\n"
        : "+f"(d[0]), "+f"(d[1]), "+f"(d[2]), "+f"(d[3]), "+f"(d[4]), "+f"(d[5]), "+f"(d[6]), "+f"(d[7]), "+f"(d[8]), "+f"(d[9]), "+f"(d[10]), "+f"(d[11]),
          "+f"(d[12]), "+f"(d[13]), "+f"(d[14]), "+f"(d[15]), "+f"(d[16]), "+f"(d[17]), "+f"(d[18]), "+f"(d[19]), "+f"(d[20]), "+f"(d[21]), "+f"(d[22]),
          "+f"(d[23]), "+f"(d[24]), "+f"(d[25]), "+f"(d[26]), "+f"(d[27]), "+f"(d[28]), "+f"(d[29]), "+f"(d[30]), "+f"(d[31]), "+f"(d[32]), "+f"(d[33]),
          "+f"(d[34]), "+f"(d[35]), "+f"(d[36]), "+f"(d[37]), "+f"(d[38]), "+f"(d[39]), "+f"(d[40]), "+f"(d[41]), "+f"(d[42]), "+f"(d[43]), "+f"(d[44]),
          "+f"(d[45]), "+f"(d[46]), "+f"(d[47]), "+f"(d[48]), "+f"(d[49]), "+f"(d[50]), "+f"(d[51]), "+f"(d[52]), "+f"(d[53]), "+f"(d[54]), "+f"(d[55]),
          "+f"(d[56]), "+f"(d[57]), "+f"(d[58]), "+f"(d[59]), "+f"(d[60]), "+f"(d[61]), "+f"(d[62]), "+f"(d[63])
        : "r"(alo), "r"(blo), "r"(scale_d));
}
__device__ __forceinline__ void mma_mix1(float (&d)[112], uint32_t alo, uint32_t blo, int scale_d) {
    asm volatile("{\n.reg .pred p;\n.reg .b64 da, db;\nsetp.ne.b32 p, %114, 0;\nmov.b64 da, {%112, 0x40000040};\nmov.b64 db, {%113, 0x80000020};\n"
        "wgmma.mma_async.sync.aligned.m64n224k16.f32.bf16.bf16 {"
        "%0, %1, %2, %3, %4, %5, %6, %7, %8, %9, %10, %11, %12, %13, %14, %15, %16, %17, %18, %19, %20, %21, %22, %23, %24, %25, %26, %27, %28, %29, %30, %31,  "
        "%32, %33, %34, %35, %36, %37, %38, %39, %40, %41, %42, %43, %44, %45, %46, %47, %48, %49, %50, %51, %52, %53, %54, %55, %56, %57, %58, %59, %60, %61,  "
        "%62, %63, %64, %65, %66, %67, %68, %69, %70, %71, %72, %73, %74, %75, %76, %77, %78, %79, %80, %81, %82, %83, %84, %85, %86, %87, %88, %89, %90, %91,  "
        "%92, %93, %94, %95, %96, %97, %98, %99, %100, %101, %102, %103, %104, %105, %106, %107, %108, %109, %110, %111 "
        "}, da, db, p, 1, 1, 1, 1;\n}\n"
        : "+f"(d[0]), "+f"(d[1]), "+f"(d[2]), "+f"(d[3]), "+f"(d[4]), "+f"(d[5]), "+f"(d[6]), "+f"(d[7]), "+f"(d[8]), "+f"(d[9]), "+f"(d[10]), "+f"(d[11]),
          "+f"(d[12]), "+f"(d[13]), "+f"(d[14]), "+f"(d[15]), "+f"(d[16]), "+f"(d[17]), "+f"(d[18]), "+f"(d[19]), "+f"(d[20]), "+f"(d[21]), "+f"(d[22]),
          "+f"(d[23]), "+f"(d[24]), "+f"(d[25]), "+f"(d[26]), "+f"(d[27]), "+f"(d[28]), "+f"(d[29]), "+f"(d[30]), "+f"(d[31]), "+f"(d[32]), "+f"(d[33]),
          "+f"(d[34]), "+f"(d[35]), "+f"(d[36]), "+f"(d[37]), "+f"(d[38]), "+f"(d[39]), "+f"(d[40]), "+f"(d[41]), "+f"(d[42]), "+f"(d[43]), "+f"(d[44]),
          "+f"(d[45]), "+f"(d[46]), "+f"(d[47]), "+f"(d[48]), "+f"(d[49]), "+f"(d[50]), "+f"(d[51]), "+f"(d[52]), "+f"(d[53]), "+f"(d[54]), "+f"(d[55]),
          "+f"(d[56]), "+f"(d[57]), "+f"(d[58]), "+f"(d[59]), "+f"(d[60]), "+f"(d[61]), "+f"(d[62]), "+f"(d[63]), "+f"(d[64]), "+f"(d[65]), "+f"(d[66]),
          "+f"(d[67]), "+f"(d[68]), "+f"(d[69]), "+f"(d[70]), "+f"(d[71]), "+f"(d[72]), "+f"(d[73]), "+f"(d[74]), "+f"(d[75]), "+f"(d[76]), "+f"(d[77]),
          "+f"(d[78]), "+f"(d[79]), "+f"(d[80]), "+f"(d[81]), "+f"(d[82]), "+f"(d[83]), "+f"(d[84]), "+f"(d[85]), "+f"(d[86]), "+f"(d[87]), "+f"(d[88]),
          "+f"(d[89]), "+f"(d[90]), "+f"(d[91]), "+f"(d[92]), "+f"(d[93]), "+f"(d[94]), "+f"(d[95]), "+f"(d[96]), "+f"(d[97]), "+f"(d[98]), "+f"(d[99]),
          "+f"(d[100]), "+f"(d[101]), "+f"(d[102]), "+f"(d[103]), "+f"(d[104]), "+f"(d[105]), "+f"(d[106]), "+f"(d[107]), "+f"(d[108]), "+f"(d[109]),
          "+f"(d[110]), "+f"(d[111])
        : "r"(alo), "r"(blo), "r"(scale_d));
}
__device__ __forceinline__ void mma_qk0(float (&d)[32], uint32_t alo, uint32_t blo) {
    asm volatile("{\n.reg .pred p;\n.reg .b64 da, db;\nsetp.ne.b32 p, 0, 0;\nmov.b64 da, {%32, 0x80000020};\nmov.b64 db, {%33, 0x80000020};\n"
        "wgmma.mma_async.sync.aligned.m64n64k16.f32.bf16.bf16 {"
        "%0, %1, %2, %3, %4, %5, %6, %7, %8, %9, %10, %11, %12, %13, %14, %15, %16, %17, %18, %19, %20, %21, %22, %23, %24, %25, %26, %27, %28, %29, %30, %31 "
        "}, da, db, p, 1, 1, 0, 0;\n}\n"
        : "=f"(d[0]), "=f"(d[1]), "=f"(d[2]), "=f"(d[3]), "=f"(d[4]), "=f"(d[5]), "=f"(d[6]), "=f"(d[7]), "=f"(d[8]), "=f"(d[9]), "=f"(d[10]), "=f"(d[11]),
          "=f"(d[12]), "=f"(d[13]), "=f"(d[14]), "=f"(d[15]), "=f"(d[16]), "=f"(d[17]), "=f"(d[18]), "=f"(d[19]), "=f"(d[20]), "=f"(d[21]), "=f"(d[22]),
          "=f"(d[23]), "=f"(d[24]), "=f"(d[25]), "=f"(d[26]), "=f"(d[27]), "=f"(d[28]), "=f"(d[29]), "=f"(d[30]), "=f"(d[31])
        : "r"(alo), "r"(blo));
}
__device__ __forceinline__ void mma_qk1(float (&d)[32], uint32_t alo, uint32_t blo, int scale_d) {
    asm volatile("{\n.reg .pred p;\n.reg .b64 da, db;\nsetp.ne.b32 p, %34, 0;\nmov.b64 da, {%32, 0x80000020};\nmov.b64 db, {%33, 0x80000020};\n"
        "wgmma.mma_async.sync.aligned.m64n64k16.f32.bf16.bf16 {"
        "%0, %1, %2, %3, %4, %5, %6, %7, %8, %9, %10, %11, %12, %13, %14, %15, %16, %17, %18, %19, %20, %21, %22, %23, %24, %25, %26, %27, %28, %29, %30, %31 "
        "}, da, db, p, 1, 1, 0, 0;\n}\n"
        : "+f"(d[0]), "+f"(d[1]), "+f"(d[2]), "+f"(d[3]), "+f"(d[4]), "+f"(d[5]), "+f"(d[6]), "+f"(d[7]), "+f"(d[8]), "+f"(d[9]), "+f"(d[10]), "+f"(d[11]),
          "+f"(d[12]), "+f"(d[13]), "+f"(d[14]), "+f"(d[15]), "+f"(d[16]), "+f"(d[17]), "+f"(d[18]), "+f"(d[19]), "+f"(d[20]), "+f"(d[21]), "+f"(d[22]),
          "+f"(d[23]), "+f"(d[24]), "+f"(d[25]), "+f"(d[26]), "+f"(d[27]), "+f"(d[28]), "+f"(d[29]), "+f"(d[30]), "+f"(d[31])
        : "r"(alo), "r"(blo), "r"(scale_d));
}
__device__ __forceinline__ void mma_qkw0(float (&d)[64], uint32_t alo, uint32_t blo) {
    asm volatile("{\n.reg .pred p;\n.reg .b64 da, db;\nsetp.ne.b32 p, 0, 0;\nmov.b64 da, {%64, 0x80000020};\nmov.b64 db, {%65, 0x80000020};\n"
        "wgmma.mma_async.sync.aligned.m64n128k16.f32.bf16.bf16 {"
        "%0, %1, %2, %3, %4, %5, %6, %7, %8, %9, %10, %11, %12, %13, %14, %15, %16, %17, %18, %19, %20, %21, %22, %23, %24, %25, %26, %27, %28, %29, %30, %31,  "
        "%32, %33, %34, %35, %36, %37, %38, %39, %40, %41, %42, %43, %44, %45, %46, %47, %48, %49, %50, %51, %52, %53, %54, %55, %56, %57, %58, %59, %60, %61,  "
        "%62, %63 "
        "}, da, db, p, 1, 1, 0, 0;\n}\n"
        : "=f"(d[0]), "=f"(d[1]), "=f"(d[2]), "=f"(d[3]), "=f"(d[4]), "=f"(d[5]), "=f"(d[6]), "=f"(d[7]), "=f"(d[8]), "=f"(d[9]), "=f"(d[10]), "=f"(d[11]),
          "=f"(d[12]), "=f"(d[13]), "=f"(d[14]), "=f"(d[15]), "=f"(d[16]), "=f"(d[17]), "=f"(d[18]), "=f"(d[19]), "=f"(d[20]), "=f"(d[21]), "=f"(d[22]),
          "=f"(d[23]), "=f"(d[24]), "=f"(d[25]), "=f"(d[26]), "=f"(d[27]), "=f"(d[28]), "=f"(d[29]), "=f"(d[30]), "=f"(d[31]), "=f"(d[32]), "=f"(d[33]),
          "=f"(d[34]), "=f"(d[35]), "=f"(d[36]), "=f"(d[37]), "=f"(d[38]), "=f"(d[39]), "=f"(d[40]), "=f"(d[41]), "=f"(d[42]), "=f"(d[43]), "=f"(d[44]),
          "=f"(d[45]), "=f"(d[46]), "=f"(d[47]), "=f"(d[48]), "=f"(d[49]), "=f"(d[50]), "=f"(d[51]), "=f"(d[52]), "=f"(d[53]), "=f"(d[54]), "=f"(d[55]),
          "=f"(d[56]), "=f"(d[57]), "=f"(d[58]), "=f"(d[59]), "=f"(d[60]), "=f"(d[61]), "=f"(d[62]), "=f"(d[63])
        : "r"(alo), "r"(blo));
}
__device__ __forceinline__ void mma_qkw1(float (&d)[64], uint32_t alo, uint32_t blo, int scale_d) {
    asm volatile("{\n.reg .pred p;\n.reg .b64 da, db;\nsetp.ne.b32 p, %66, 0;\nmov.b64 da, {%64, 0x80000020};\nmov.b64 db, {%65, 0x80000020};\n"
        "wgmma.mma_async.sync.aligned.m64n128k16.f32.bf16.bf16 {"
        "%0, %1, %2, %3, %4, %5, %6, %7, %8, %9, %10, %11, %12, %13, %14, %15, %16, %17, %18, %19, %20, %21, %22, %23, %24, %25, %26, %27, %28, %29, %30, %31,  "
        "%32, %33, %34, %35, %36, %37, %38, %39, %40, %41, %42, %43, %44, %45, %46, %47, %48, %49, %50, %51, %52, %53, %54, %55, %56, %57, %58, %59, %60, %61,  "
        "%62, %63 "
        "}, da, db, p, 1, 1, 0, 0;\n}\n"
        : "+f"(d[0]), "+f"(d[1]), "+f"(d[2]), "+f"(d[3]), "+f"(d[4]), "+f"(d[5]), "+f"(d[6]), "+f"(d[7]), "+f"(d[8]), "+f"(d[9]), "+f"(d[10]), "+f"(d[11]),
          "+f"(d[12]), "+f"(d[13]), "+f"(d[14]), "+f"(d[15]), "+f"(d[16]), "+f"(d[17]), "+f"(d[18]), "+f"(d[19]), "+f"(d[20]), "+f"(d[21]), "+f"(d[22]),
          "+f"(d[23]), "+f"(d[24]), "+f"(d[25]), "+f"(d[26]), "+f"(d[27]), "+f"(d[28]), "+f"(d[29]), "+f"(d[30]), "+f"(d[31]), "+f"(d[32]), "+f"(d[33]),
          "+f"(d[34]), "+f"(d[35]), "+f"(d[36]), "+f"(d[37]), "+f"(d[38]), "+f"(d[39]), "+f"(d[40]), "+f"(d[41]), "+f"(d[42]), "+f"(d[43]), "+f"(d[44]),
          "+f"(d[45]), "+f"(d[46]), "+f"(d[47]), "+f"(d[48]), "+f"(d[49]), "+f"(d[50]), "+f"(d[51]), "+f"(d[52]), "+f"(d[53]), "+f"(d[54]), "+f"(d[55]),
          "+f"(d[56]), "+f"(d[57]), "+f"(d[58]), "+f"(d[59]), "+f"(d[60]), "+f"(d[61]), "+f"(d[62]), "+f"(d[63])
        : "r"(alo), "r"(blo), "r"(scale_d));
}
__device__ __forceinline__ void mma_pv(float (&d)[20], uint32_t a0, uint32_t a1, uint32_t a2, uint32_t a3, uint32_t blo, int scale_d) {
    asm volatile("{\n.reg .pred p;\n.reg .b64 da, db;\nsetp.ne.b32 p, %25, 0;\nmov.b64 db, {%24, 0x80000020};\n"
        "wgmma.mma_async.sync.aligned.m64n40k16.f32.bf16.bf16 {"
        "%0, %1, %2, %3, %4, %5, %6, %7, %8, %9, %10, %11, %12, %13, %14, %15, %16, %17, %18, %19 "
        "}, {%20, %21, %22, %23}, db, p, 1, 1, 1;\n}\n"
        : "+f"(d[0]), "+f"(d[1]), "+f"(d[2]), "+f"(d[3]), "+f"(d[4]), "+f"(d[5]), "+f"(d[6]), "+f"(d[7]), "+f"(d[8]), "+f"(d[9]), "+f"(d[10]), "+f"(d[11]),
          "+f"(d[12]), "+f"(d[13]), "+f"(d[14]), "+f"(d[15]), "+f"(d[16]), "+f"(d[17]), "+f"(d[18]), "+f"(d[19])
        : "r"(a0), "r"(a1), "r"(a2), "r"(a3), "r"(blo), "r"(scale_d));
}

__device__ __forceinline__ float warp_sum(float v) {
#pragma unroll
    for (int o = 16; o > 0; o >>= 1) v += __shfl_xor_sync(0xffffffffu, v, o);
    return v;
}

struct GemmSmem { uint32_t base, full0, empty0, aux; };

template <class C>
__device__ __forceinline__ GemmSmem gemm_setup(uint8_t* smem_raw) {
    GemmSmem s;
    s.base = smem_u32(smem_raw);
    s.full0 = s.base + C::BAR_OFF; s.empty0 = s.full0 + 8 * C::STAGES; s.aux = s.empty0 + 8 * C::STAGES;
    if (threadIdx.x == 0) {
        if (s.base & 1023) __trap();
        for (int i = 0; i < C::STAGES; i++) { mbar_init(s.full0 + 8 * i, 1); mbar_init(s.empty0 + 8 * i, 8); }
        mbar_init(s.aux, C::AUX_COUNT);
        fence_barrier_init();
    }
    __syncthreads();
    return s;
}

template <class C, class P>
__device__ __forceinline__ void gemm_producer(const GemmSmem& s, const P& p, int tm, int tn) {
#pragma unroll 1
    for (int k = 0; k < C::STAGES; k++) {
        mbar_expect_tx(s.full0 + 8 * k, C::STAGE_BYTES);
        C::load_w(p, s.base + k * C::STAGE_BYTES, s.full0 + 8 * k, k, tm, tn);
    }
    pdl_wait();
    C::load_aux(p, s, tm, tn);
#pragma unroll 1
    for (int k = 0; k < C::STAGES; k++) C::load_x(p, s.base + k * C::STAGE_BYTES, s.full0 + 8 * k, k, tm, tn);
    int st = 0; uint32_t ph = 0;
#pragma unroll 1
    for (int k = C::STAGES; k < C::KSTEPS; k++) {
        mbar_wait(s.empty0 + 8 * st, ph);
        mbar_expect_tx(s.full0 + 8 * st, C::STAGE_BYTES);
        C::load_w(p, s.base + st * C::STAGE_BYTES, s.full0 + 8 * st, k, tm, tn);
        C::load_x(p, s.base + st * C::STAGE_BYTES, s.full0 + 8 * st, k, tm, tn);
        if (++st == C::STAGES) { st = 0; ph ^= 1; }
    }
}

template <class C>
__device__ __forceinline__ void gemm_mainloop(const GemmSmem& s, int wg, float (&acc)[C::MB][C::BN / 2], int tlk = 0) {
    const int lane = threadIdx.x & 31;
    int st = 0; uint32_t ph = 0;
    int prev = 0;
#pragma unroll
    for (int m = 0; m < C::MB; m++) fence_regs(acc[m]);
#pragma unroll 1
    for (int k = 0; k < C::KSTEPS; k++) {
        mbar_wait(s.full0 + 8 * st, ph);
        const uint32_t sb = s.base + st * C::STAGE_BYTES;
        wg_fence();
#pragma unroll
        for (int kk = 0; kk < 4; kk++) {
#pragma unroll
            for (int m = 0; m < C::MB; m++) C::mma(acc[m], C::desc_a(sb, wg, m, kk), C::desc_b(sb, kk), (k | kk) != 0);
        }
        wg_commit();
        if (k > 0) { wg_wait<1>(); if (lane == 0) mbar_arrive(s.empty0 + 8 * prev); }
        prev = st;
        if (++st == C::STAGES) { st = 0; ph ^= 1; }
    }
    wg_wait<0>();
#pragma unroll
    for (int m = 0; m < C::MB; m++) fence_regs(acc[m]);
}

struct QkvParams { CUtensorMap x, w, out; const bf16* xp; const bf16* wp; };
struct QkvCfg {
    static constexpr int MB = 2, BN = 192, KSTEPS = 16, STAGES = 4, A_BYTES = 32768, B_BYTES = 24576;
    static constexpr int STAGE_BYTES = A_BYTES + B_BYTES, BAR_OFF = STAGES * STAGE_BYTES, AUX_OFF = BAR_OFF + 128, SMEM = AUX_OFF + 2816;
    static constexpr int AUX_COUNT = 3;
    static __device__ __forceinline__ void load_w(const QkvParams& p, uint32_t sb, uint32_t bar, int k, int tm, int tn) { tma_ld4(sb + A_BYTES, &p.w, bar, 0, k * 64, 0, tn); }
    static __device__ __forceinline__ void load_x(const QkvParams& p, uint32_t sb, uint32_t bar, int k, int tm, int tn) { tma_ld2(sb, &p.x, bar, k * 64, tm * 256); }
    static __device__ __forceinline__ void load_aux(const QkvParams&, const GemmSmem&, int, int) {}
    static __device__ __forceinline__ uint32_t desc_a(uint32_t sb, int wg, int m, int kk) { return desc_lo(sb + (wg * 128 + m * 64) * 128 + kk * 32, 16); }
    static __device__ __forceinline__ uint32_t desc_b(uint32_t sb, int kk) { return desc_lo(sb + A_BYTES + kk * 2048, 8192); }
    static __device__ __forceinline__ void mma(float (&d)[96], uint32_t a, uint32_t b, int sc) { mma_qkv(d, a, b, sc); }
};

__device__ __forceinline__ void spin_until(const uint32_t* cnt, uint32_t target) {
    uint32_t v; int it = 0;
    do {
        asm volatile("ld.acquire.gpu.global.u32 %0, [%1];" : "=r"(v) : "l"(cnt) : "memory");
        if (++it > (1 << 22)) __trap();
    } while (v < target);
}
__device__ __forceinline__ void publish(uint32_t* cnt) { asm volatile("red.release.gpu.global.add.u32 [%0], 1;" :: "l"(cnt) : "memory"); }

__device__ __forceinline__ void qkv_aux(const QkvParams& p, uint8_t* smem_raw, const GemmSmem& s, int tm, int tn, int w, int lane) {
    for (int r = w; r < 16; r += 3) {
        const int row = tm * 256 + tn * 16 + r;
        const uint4* src = reinterpret_cast<const uint4*>(p.xp + (size_t)row * DM);
        uint32_t v[16];
#pragma unroll
        for (int i = 0; i < 4; i++) { const uint4 t = __ldg(src + lane + 32 * i); v[4 * i] = t.x; v[4 * i + 1] = t.y; v[4 * i + 2] = t.z; v[4 * i + 3] = t.w; }
        float sum = 0.f;
#pragma unroll
        for (int i = 0; i < 16; i++) sum += bf_lo(v[i]) + bf_hi(v[i]);
        const float mean = warp_sum(sum) * (1.f / DM);
        float q = 0.f;
#pragma unroll
        for (int i = 0; i < 16; i++) { const float a = bf_lo(v[i]) - mean, b = bf_hi(v[i]) - mean; q += a * a + b * b; }
        const float rstd = rsqrtf(warp_sum(q) * (1.f / DM) + 1e-5f);
        if (lane == 0) g_rowstat[row] = make_float2(mean, rstd);
    }
    __syncwarp();
    if (lane == 0) publish(&g_cnt_row[tm]);
    {
        const uint4* src = reinterpret_cast<const uint4*>(p.wp + (size_t)(tm * 128 + (lane >> 3)) * (3 * DM) + w * DM + tn * 64) + (lane & 7);
        float a[8];
#pragma unroll
        for (int i = 0; i < 8; i++) a[i] = 0.f;
#pragma unroll 1
        for (int j = 0; j < 32; j += 8) {
            uint4 t[8];
#pragma unroll
            for (int i = 0; i < 8; i++) t[i] = __ldg(src + (size_t)(j + i) * 4 * (3 * DM / 8));
#pragma unroll
            for (int i = 0; i < 8; i++) {
                a[0] += bf_lo(t[i].x); a[1] += bf_hi(t[i].x); a[2] += bf_lo(t[i].y); a[3] += bf_hi(t[i].y);
                a[4] += bf_lo(t[i].z); a[5] += bf_hi(t[i].z); a[6] += bf_lo(t[i].w); a[7] += bf_hi(t[i].w);
            }
        }
#pragma unroll
        for (int i = 0; i < 8; i++) { a[i] += __shfl_xor_sync(0xffffffffu, a[i], 8); a[i] += __shfl_xor_sync(0xffffffffu, a[i], 16); }
        if (lane < 8) {
            float4* dst = reinterpret_cast<float4*>(g_colsum + tm * (3 * DM) + tn * 192 + w * 64 + lane * 8);
            dst[0] = make_float4(a[0], a[1], a[2], a[3]); dst[1] = make_float4(a[4], a[5], a[6], a[7]);
        }
        __syncwarp();
        if (lane == 0) publish(&g_cnt_col[tn]);
    }
    float* scs = reinterpret_cast<float*>(smem_raw + QkvCfg::AUX_OFF);
    float2* sst = reinterpret_cast<float2*>(smem_raw + QkvCfg::AUX_OFF + 768);
    const int t = w * 32 + lane;
    spin_until(&g_cnt_row[tm], 16 * 3);
    for (int r = t; r < 256; r += 96) sst[r] = __ldcg(&g_rowstat[tm * 256 + r]);
    spin_until(&g_cnt_col[tn], 8 * 3);
    {
        float2 c = make_float2(0.f, 0.f);
#pragma unroll
        for (int i = 0; i < 8; i++) { const float2 u = __ldcg(reinterpret_cast<const float2*>(g_colsum + i * (3 * DM) + tn * 192) + t); c.x += u.x; c.y += u.y; }
        reinterpret_cast<float2*>(scs)[t] = c;
    }
    __syncwarp();
    if (lane == 0) mbar_arrive(s.aux);
}

__global__ void __launch_bounds__(384, 1) qkv_kernel(const __grid_constant__ QkvParams p) {
    extern __shared__ __align__(1024) uint8_t smem_raw[];
    TL(1, 4);
    pdl_launch();
    const int tm = blockIdx.x & 7, tn = blockIdx.x >> 3;
    if (threadIdx.x == 0) { prefetch_map(&p.x); prefetch_map(&p.w); prefetch_map(&p.out); }
    const GemmSmem s = gemm_setup<QkvCfg>(smem_raw);
    const int wgi = __shfl_sync(0xffffffffu, threadIdx.x >> 7, 0);
    if (wgi == 0) {
        reg_dealloc<56>();
        if (threadIdx.x == 0) gemm_producer<QkvCfg>(s, p, tm, tn);
        else if (threadIdx.x >= 32) qkv_aux(p, smem_raw, s, tm, tn, (threadIdx.x >> 5) - 1, threadIdx.x & 31);
    } else {
        reg_alloc<224>();
        const int wg = wgi - 1, warp = (threadIdx.x >> 5) & 3, lane = threadIdx.x & 31;
        float acc[2][96];
        TL(1, 0);
        gemm_mainloop<QkvCfg>(s, wg, acc, 1);
        TL(1, 1);
        mbar_wait(s.aux, 0);
        named_bar(1, 256);
        const float qscale = 0.17677669529663687f * 1.4426950408889634f;
        const float2* scs = reinterpret_cast<const float2*>(smem_raw + QkvCfg::AUX_OFF);
        const float2* sst = reinterpret_cast<const float2*>(smem_raw + QkvCfg::AUX_OFF + 768);
        float mean[4], rstd[4];
#pragma unroll
        for (int i = 0; i < 4; i++) { const float2 t = sst[wg * 128 + (i >> 1) * 64 + warp * 16 + (i & 1) * 8 + (lane >> 2)]; mean[i] = -t.x; rstd[i] = t.y; }
        uint32_t* snorm = reinterpret_cast<uint32_t*>(smem_raw + 6 * 16384) + wg * 32;
#pragma unroll
        for (int sub = 0; sub < 6; sub++) {
            float nrm[4];
#pragma unroll
            for (int m = 0; m < 2; m++) {
                const int arow = wg * 128 + m * 64 + warp * 16 + ((lane >> 3) & 1) * 8 + (lane & 7);
                const float r0 = (sub < 2) ? rstd[2 * m] * qscale : rstd[2 * m], r1 = (sub < 2) ? rstd[2 * m + 1] * qscale : rstd[2 * m + 1];
                float v[16];
#pragma unroll
                for (int j = 0; j < 4; j++) {
                    const float2 cs = scs[(sub * 4 + j) * 4 + (lane & 3)];
                    v[4 * j] = fmaf(mean[2 * m], cs.x, acc[m][sub * 16 + 4 * j]) * r0;
                    v[4 * j + 1] = fmaf(mean[2 * m], cs.y, acc[m][sub * 16 + 4 * j + 1]) * r0;
                    v[4 * j + 2] = fmaf(mean[2 * m + 1], cs.x, acc[m][sub * 16 + 4 * j + 2]) * r1;
                    v[4 * j + 3] = fmaf(mean[2 * m + 1], cs.y, acc[m][sub * 16 + 4 * j + 3]) * r1;
                }
                float n0 = 0.f, n1 = 0.f;
#pragma unroll
                for (int j = 0; j < 4; j++) {
                    n0 = fmaf(v[4 * j], v[4 * j], fmaf(v[4 * j + 1], v[4 * j + 1], n0));
                    n1 = fmaf(v[4 * j + 2], v[4 * j + 2], fmaf(v[4 * j + 3], v[4 * j + 3], n1));
                }
                nrm[2 * m] = n0; nrm[2 * m + 1] = n1;
#pragma unroll
                for (int jp = 0; jp < 2; jp++) {
                    const int chunk = jp * 2 + (lane >> 4);
                    const uint32_t addr = s.base + sub * 16384 + arow * 64 + ((chunk ^ ((arow >> 1) & 3)) << 4);
                    stmatrix_x4(addr, pack_bf16(v[8 * jp], v[8 * jp + 1]), pack_bf16(v[8 * jp + 2], v[8 * jp + 3]),
                                pack_bf16(v[8 * jp + 4], v[8 * jp + 5]), pack_bf16(v[8 * jp + 6], v[8 * jp + 7]));
                }
            }
            const bool odd = lane & 1, up = lane & 2;
            const float s0 = (odd ? nrm[2] : nrm[0]) + __shfl_xor_sync(0xffffffffu, odd ? nrm[0] : nrm[2], 1);
            const float s1 = (odd ? nrm[3] : nrm[1]) + __shfl_xor_sync(0xffffffffu, odd ? nrm[1] : nrm[3], 1);
            const float full = (up ? s1 : s0) + __shfl_xor_sync(0xffffffffu, up ? s0 : s1, 2);
            const uint32_t mx = __reduce_max_sync(0xffffffffu, __float_as_uint(full));
            if (lane == 0) snorm[warp * 8 + sub] = mx;
        }
        TL(1, 5);
        fence_proxy_async();
        named_bar(2 + wg, 128);
        if ((threadIdx.x & 127) == 0) {
#pragma unroll
            for (int sub = 0; sub < 6; sub++)
                tma_st2(&p.out, s.base + sub * 16384 + wg * 8192, 0, (sub >> 1) * (NH * SEQ) + (tn * 2 + (sub & 1)) * SEQ + tm * 256 + wg * 128);
            tma_st_commit();
            tma_st_wait();
        } else if ((threadIdx.x & 127) >= 32 && (threadIdx.x & 127) < 38) {
            const int sub = (threadIdx.x & 127) - 32;
            g_norm[((sub >> 1) * NH + tn * 2 + (sub & 1)) * 16 + tm * 2 + wg] = max(max(snorm[sub], snorm[8 + sub]), max(snorm[16 + sub], snorm[24 + sub]));
        }
        TL(1, 3);
    }
}

struct AttnParams { CUtensorMap kv, kv2; bf16* o; };
constexpr int AT_STAGES = 8, AT_STAGE_BYTES = 16384, AT_Q_OFF = AT_STAGES * AT_STAGE_BYTES, AT_ONES_OFF = AT_Q_OFF + 32768, AT_BAR_OFF = AT_ONES_OFF + 1024, AT_SMEM = AT_BAR_OFF + 256;
constexpr int AT_TILES = 32;

__device__ __forceinline__ float ex2_poly(float x) {
    const float magic = 12582912.f;
    const float t = x + magic;
    const float f = x - (t - magic);
    float p = fmaf(f, 0.05550410866f, 0.24022650695f);
    p = fmaf(p, f, 0.69314718056f);
    p = fmaf(p, f, 1.0f);
    return __int_as_float(__float_as_int(p) + (__float_as_int(t) << 23));
}

template <uint32_t MASK> __device__ __forceinline__ float attn_exp(float x, int i) { return ((MASK >> (i & 31)) & 1) ? ex2_poly(x) : ex2(x); }
__device__ __forceinline__ void attn_issue_tile(const AttnParams& p, uint32_t base, uint32_t full0, int g, int head) {
    const int st = g % AT_STAGES, key0 = (g & 15) * 128;
    const uint32_t bar = full0 + 8 * st, dst = base + st * AT_STAGE_BYTES;
    mbar_expect_tx(bar, AT_STAGE_BYTES);
    tma_ld3(dst, &p.kv2, bar, 0, head * SEQ + key0, 1);
}
__device__ __forceinline__ void attn_qk(float (&sacc)[32], uint32_t q_lo, uint32_t k_lo) {
    mma_qk0(sacc, q_lo, k_lo);
    mma_qk1(sacc, q_lo + 2, k_lo + 2, 1);
}
constexpr uint32_t PV_STEP = 64u - (64u << 16);
__device__ __forceinline__ void attn_pv(float (&o)[20], const uint32_t (&pr)[16], uint32_t v_lo, int first) {
#pragma unroll
    for (int kk = 0; kk < 4; kk++)
        mma_pv(o, pr[4 * kk], pr[4 * kk + 1], pr[4 * kk + 2], pr[4 * kk + 3], v_lo + kk * PV_STEP, (kk > 0) || !first);
}
__device__ __forceinline__ void attn_store_o(const float (&o)[20], const AttnParams& p, int head, int row0, int lane) {
    const float r0 = 1.f / o[16], r1 = 1.f / o[18];
    uint32_t* op = reinterpret_cast<uint32_t*>(p.o + (size_t)row0 * DM + head * HD) + (lane & 3);
#pragma unroll
    for (int j = 0; j < 4; j++) {
        op[j * 4] = pack_bf16(o[4 * j] * r0, o[4 * j + 1] * r0);
        op[j * 4 + 8 * (DM / 2)] = pack_bf16(o[4 * j + 2] * r1, o[4 * j + 3] * r1);
    }
}
__device__ __forceinline__ void attn_refill(const AttnParams& p, uint32_t base, uint32_t full0, uint32_t empty0, int g, int head) {
    if (threadIdx.x == 0 && g >= 4 && g + 4 < AT_TILES) {
        const int gp = g - 4;
        mbar_wait(empty0 + 8 * (gp % AT_STAGES), (gp / AT_STAGES) & 1);
        attn_issue_tile(p, base, full0, g + 4, head);
    }
    __syncwarp();
}

__device__ __forceinline__ void attn_fast(const AttnParams& p, uint32_t base, uint32_t full0, uint32_t empty0, int head, int qchunk) {
    const int wg = __shfl_sync(0xffffffffu, threadIdx.x >> 7, 0), warp = (threadIdx.x >> 5) & 3, lane = threadIdx.x & 31;
    const int warp_id = __shfl_sync(0xffffffffu, threadIdx.x >> 5, 0);
    const uint32_t k_lo0 = desc_lo(base, 16), v_lo0 = desc_lo(base + 8192, AT_ONES_OFF - 8192);
    const uint32_t q_lo0 = desc_lo(base + AT_Q_OFF + wg * 64 * 64, 16);
#pragma unroll 1
    for (int pass = 0; pass < 2; pass++) {
    const uint32_t q = q_lo0 + pass * (256 * 64 >> 4);
    float o[20];
#pragma unroll
    for (int i = 0; i < 20; i++) o[i] = 0.f;
#pragma unroll 1
    for (uint32_t par = 0; par < 2; par++) {
        const int rev = pass * 2 + par;
#pragma unroll
        for (int st = 0; st < AT_STAGES; st++) {
            if (warp_id == (st & 3) * 5) {
                const int g = rev * AT_STAGES + st;
                if (lane == 0 && g >= 4 && g + 4 < AT_TILES) {
                    mbar_wait(empty0 + 8 * ((st + 4) % AT_STAGES), (st >= 4) ? par : (par ^ 1));
                    attn_issue_tile(p, base, full0, g + 4, head);
                }
                __syncwarp();
            }
            mbar_wait(full0 + 8 * st, par);
            float sc[64];
            uint32_t pa[16], pb[16];
            AT(0);
            wg_fence();
            mma_qkw0(sc, q, k_lo0 + st * (AT_STAGE_BYTES >> 4));
            mma_qkw1(sc, q + 2, k_lo0 + st * (AT_STAGE_BYTES >> 4) + 2, 1);
            wg_commit();
            wg_wait<0>();
            fence_regs(sc);
            AT(1);
            if (lane == 0 && (st > 0 || rev > 0)) mbar_arrive(empty0 + 8 * ((st + AT_STAGES - 1) % AT_STAGES));
#pragma unroll
            for (int i = 0; i < 16; i++) pa[i] = pack_bf16(attn_exp<POLY_MASK>(sc[2 * i], 2 * i), attn_exp<POLY_MASK>(sc[2 * i + 1], 2 * i + 1));
            wg_fence();
            attn_pv(o, pa, v_lo0 + st * 16 * PV_STEP, 0);
            wg_commit();
            AT(2);
#pragma unroll
            for (int i = 0; i < 16; i++) pb[i] = pack_bf16(attn_exp<POLY_MASK_B>(sc[32 + 2 * i], 2 * i), attn_exp<POLY_MASK_B>(sc[32 + 2 * i + 1], 2 * i + 1));
            wg_wait<0>();
            wg_fence();
            attn_pv(o, pb, v_lo0 + (st * 16 + 4) * PV_STEP, 0);
            wg_commit();
            AT(3);
        }
    }
    wg_wait<0>();
    fence_regs(o);
    const int row0 = qchunk * 512 + pass * 256 + wg * 64 + warp * 16 + (lane >> 2);
    attn_store_o(o, p, head, row0, lane);
    }
}

__device__ __forceinline__ void attn_safe(const AttnParams& p, uint32_t base, uint32_t full0, uint32_t empty0, int head, int qchunk) {
    const int wg = __shfl_sync(0xffffffffu, threadIdx.x >> 7, 0), warp = (threadIdx.x >> 5) & 3, lane = threadIdx.x & 31;
    const uint32_t k_lo0 = desc_lo(base, 16), v_lo0 = desc_lo(base + 8192, AT_ONES_OFF - 8192);
#pragma unroll 1
    for (int pass = 0; pass < 2; pass++) {
        const int row0 = qchunk * 512 + pass * 256 + wg * 64 + warp * 16 + (lane >> 2);
        const uint32_t q = desc_lo(base + AT_Q_OFF + (pass * 256 + wg * 64) * 64, 16);
        float o[20];
#pragma unroll
        for (int i = 0; i < 20; i++) o[i] = 0.f;
        float m0 = -INFINITY, m1 = -INFINITY;
#pragma unroll 1
        for (int t = 0; t < 32; t++) {
            const int g = pass * 16 + (t >> 1), half = t & 1;
            const int st = g % AT_STAGES;
            const uint32_t kb = k_lo0 + st * (AT_STAGE_BYTES >> 4), vb = v_lo0 + st * 16 * PV_STEP;
            if (half == 0) { attn_refill(p, base, full0, empty0, g, head); mbar_wait(full0 + 8 * st, (g / AT_STAGES) & 1); }
            float cur[32];
            wg_fence();
            attn_qk(cur, q, kb + half * 256);
            wg_commit();
            wg_wait<0>();
            fence_regs(cur);
            float x0 = cur[0], x1 = cur[2];
#pragma unroll
            for (int i = 0; i < 8; i++) { x0 = fmaxf(x0, fmaxf(cur[4 * i], cur[4 * i + 1])); x1 = fmaxf(x1, fmaxf(cur[4 * i + 2], cur[4 * i + 3])); }
            x0 = fmaxf(x0, __shfl_xor_sync(0xffffffffu, x0, 1)); x1 = fmaxf(x1, __shfl_xor_sync(0xffffffffu, x1, 1));
            x0 = fmaxf(x0, __shfl_xor_sync(0xffffffffu, x0, 2)); x1 = fmaxf(x1, __shfl_xor_sync(0xffffffffu, x1, 2));
            const float n0 = fmaxf(m0, x0), n1 = fmaxf(m1, x1);
            const float a0 = ex2(m0 - n0), a1 = ex2(m1 - n1);
            m0 = n0; m1 = n1;
            uint32_t pr[16];
#pragma unroll
            for (int i = 0; i < 8; i++) {
                pr[2 * i] = pack_bf16(ex2(cur[4 * i] - n0), ex2(cur[4 * i + 1] - n0));
                pr[2 * i + 1] = pack_bf16(ex2(cur[4 * i + 2] - n1), ex2(cur[4 * i + 3] - n1));
            }
#pragma unroll
            for (int i = 0; i < 5; i++) { o[4 * i] *= a0; o[4 * i + 1] *= a0; o[4 * i + 2] *= a1; o[4 * i + 3] *= a1; }
            wg_fence();
            attn_pv(o, pr, vb + half * 4 * PV_STEP, 0);
            wg_commit();
            wg_wait<0>();
            fence_regs(o);
            if (half == 1 && lane == 0) mbar_arrive(empty0 + 8 * st);
        }
        attn_store_o(o, p, head, row0, lane);
    }
}

__global__ void __launch_bounds__(512, 1) attn_kernel(const __grid_constant__ AttnParams p) {
    extern __shared__ __align__(1024) uint8_t smem_raw[];
    TL(2, 4);
    pdl_launch();
    const uint32_t base = smem_u32(smem_raw);
    const uint32_t full0 = base + AT_BAR_OFF, empty0 = full0 + 8 * AT_STAGES;
    const int head = blockIdx.x >> 2, qchunk = blockIdx.x & 3;
    if (threadIdx.x == 0) {
        if (base & 1023) __trap();
        prefetch_map(&p.kv);
        for (int i = 0; i < AT_STAGES; i++) { mbar_init(full0 + 8 * i, 1); mbar_init(empty0 + 8 * i, 16); }
        mbar_init(empty0 + 8 * AT_STAGES, 1);
        fence_barrier_init();
    }
    if (threadIdx.x < 256) reinterpret_cast<uint32_t*>(smem_raw + AT_ONES_OFF)[threadIdx.x] = 0x3F803F80u;
    fence_proxy_async();
    __syncthreads();
    pdl_wait();
    TL(2, 0);
    if (threadIdx.x == 0) {
        const uint32_t qbar = empty0 + 8 * AT_STAGES;
        mbar_expect_tx(qbar, 32768);
        for (int i = 0; i < 4; i++) tma_ld2(base + AT_Q_OFF + i * 8192, &p.kv, qbar, 0, head * SEQ + qchunk * 512 + i * 128);
        for (int g = 0; g < AT_STAGES; g++) attn_issue_tile(p, base, full0, g, head);
    }
    __syncwarp();
    const int l16 = threadIdx.x & 15;
    const float qn = __uint_as_float(__reduce_max_sync(0xffffffffu, __ldcg(&g_norm[head * 16 + l16])));
    const float kn = __uint_as_float(__reduce_max_sync(0xffffffffu, __ldcg(&g_norm[(NH + head) * 16 + l16])));
    const float vn = __uint_as_float(__reduce_max_sync(0xffffffffu, __ldcg(&g_norm[(2 * NH + head) * 16 + l16])));
    if (blockIdx.x == 0 && threadIdx.x >= 64 && threadIdx.x < 64 + 24) {
        const int i = threadIdx.x - 64;
        if (i < 8) g_cnt_row[i] = 0; else g_cnt_col[i - 8] = 0;
    }
    const bool bounded = (qn * kn <= 1.0e4f) && (vn <= 1.0e9f);
    mbar_wait(empty0 + 8 * AT_STAGES, 0);
    if (bounded) attn_fast(p, base, full0, empty0, head, qchunk);
    else attn_safe(p, base, full0, empty0, head, qchunk);
    TL(2, 3);
}

struct ResParams { CUtensorMap a, b, res, out, out2; const bf16* bias; };
template <bool MIX2>
struct ResCfg {
    static constexpr int MB = 1, BN = 128, KSTEPS = MIX2 ? 56 : 16, STAGES = 6, A_BYTES = 16384, B_BYTES = 16384;
    static constexpr int STAGE_BYTES = A_BYTES + B_BYTES, STG_OFF = STAGES * STAGE_BYTES, BAR_OFF = STG_OFF + 32768, SMEM = BAR_OFF + 128;
    static constexpr int AUX_COUNT = 1;
    static __device__ __forceinline__ void load_w(const ResParams& p, uint32_t sb, uint32_t bar, int k, int tm, int tn) {
        if (MIX2) tma_ld3(sb, &p.a, bar, 0, k * 64, tm * 2);
        else tma_ld3(sb + A_BYTES, &p.b, bar, 0, k * 64, tn * 2);
    }
    static __device__ __forceinline__ void load_x(const ResParams& p, uint32_t sb, uint32_t bar, int k, int tm, int tn) {
        if (MIX2) tma_ld2(sb + A_BYTES, &p.b, bar, k * 64, tn * 128);
        else tma_ld2(sb, &p.a, bar, k * 64, tm * 128);
    }
    static __device__ __forceinline__ void load_aux(const ResParams& p, const GemmSmem& s, int tm, int tn) {
        mbar_expect_tx(s.aux, 32768);
        tma_ld2(s.base + STG_OFF, &p.res, s.aux, tn * 128, tm * 128);
        tma_ld2(s.base + STG_OFF + 16384, &p.res, s.aux, tn * 128 + 64, tm * 128);
    }
    static __device__ __forceinline__ uint32_t desc_a(uint32_t sb, int wg, int m, int kk) {
        return MIX2 ? desc_lo(sb + wg * 8192 + kk * 2048, 8192) : desc_lo(sb + wg * 8192 + kk * 32, 16);
    }
    static __device__ __forceinline__ uint32_t desc_b(uint32_t sb, int kk) {
        return MIX2 ? desc_lo(sb + A_BYTES + kk * 32, 16) : desc_lo(sb + A_BYTES + kk * 2048, 8192);
    }
    static __device__ __forceinline__ void mma(float (&d)[64], uint32_t a, uint32_t b, int sc) {
        if (MIX2) mma_mix2(d, a, b, sc); else mma_wo(d, a, b, sc);
    }
};
template <bool MIX2>
__global__ void __launch_bounds__(384, 1) res_gemm_kernel(const __grid_constant__ ResParams p) {
    using C = ResCfg<MIX2>;
    extern __shared__ __align__(1024) uint8_t smem_raw[];
    TL(MIX2 ? 6 : 3, 4);
    pdl_launch();
    const int tm = blockIdx.x & 15, tn = blockIdx.x >> 4;
    if (threadIdx.x == 0) { prefetch_map(&p.a); prefetch_map(&p.b); prefetch_map(&p.res); prefetch_map(&p.out); }
    const GemmSmem s = gemm_setup<C>(smem_raw);
    const int wgi = __shfl_sync(0xffffffffu, threadIdx.x >> 7, 0);
    if (wgi == 0) {
        reg_dealloc<40>();
        if (threadIdx.x == 0) gemm_producer<C>(s, p, tm, tn);
    } else {
        reg_alloc<232>();
        const int wg = wgi - 1, warp = (threadIdx.x >> 5) & 3, lane = threadIdx.x & 31;
        float acc[1][64];
        pdl_wait();
        TL(MIX2 ? 6 : 3, 0);
        const int r0 = wg * 64 + warp * 16 + (lane >> 2);
        float b0 = 0.f, b1 = 0.f;
        if (MIX2) { b0 = __bfloat162float(p.bias[tm * 128 + r0]); b1 = __bfloat162float(p.bias[tm * 128 + r0 + 8]); }
        gemm_mainloop<C>(s, wg, acc, MIX2 ? 6 : 3);
        TL(MIX2 ? 6 : 3, 1);
        mbar_wait(s.aux, 0);
        uint8_t* stg = smem_raw + C::STG_OFF;
        uint32_t hp[32];
#pragma unroll
        for (int j = 0; j < 16; j++) {
            const int off = (j >> 3) * 16384 + r0 * 128 + (((j & 7) ^ (r0 & 7)) << 4) + (lane & 3) * 4;
            uint32_t* p0 = reinterpret_cast<uint32_t*>(stg + off);
            uint32_t* p1 = reinterpret_cast<uint32_t*>(stg + off + 8 * 128);
            const uint32_t x0 = *p0, x1 = *p1;
            hp[2 * j] = pack_bf16(acc[0][4 * j] + b0 + bf_lo(x0), acc[0][4 * j + 1] + b0 + bf_hi(x0));
            hp[2 * j + 1] = pack_bf16(acc[0][4 * j + 2] + b1 + bf_lo(x1), acc[0][4 * j + 3] + b1 + bf_hi(x1));
            *p0 = hp[2 * j];
            *p1 = hp[2 * j + 1];
        }
        if (!MIX2) {
            float s0 = 0.f, s1 = 0.f;
#pragma unroll
            for (int j = 0; j < 16; j++) { s0 += bf_lo(hp[2 * j]) + bf_hi(hp[2 * j]); s1 += bf_lo(hp[2 * j + 1]) + bf_hi(hp[2 * j + 1]); }
            s0 += __shfl_xor_sync(0xffffffffu, s0, 1); s1 += __shfl_xor_sync(0xffffffffu, s1, 1);
            s0 += __shfl_xor_sync(0xffffffffu, s0, 2); s1 += __shfl_xor_sync(0xffffffffu, s1, 2);
            const float m0 = s0 * (1.f / 128), m1 = s1 * (1.f / 128);
            float q0 = 0.f, q1 = 0.f;
#pragma unroll
            for (int j = 0; j < 16; j++) {
                const float a = bf_lo(hp[2 * j]) - m0, b = bf_hi(hp[2 * j]) - m0, c = bf_lo(hp[2 * j + 1]) - m1, d = bf_hi(hp[2 * j + 1]) - m1;
                q0 = fmaf(a, a, fmaf(b, b, q0)); q1 = fmaf(c, c, fmaf(d, d, q1));
            }
            q0 += __shfl_xor_sync(0xffffffffu, q0, 1); q1 += __shfl_xor_sync(0xffffffffu, q1, 1);
            q0 += __shfl_xor_sync(0xffffffffu, q0, 2); q1 += __shfl_xor_sync(0xffffffffu, q1, 2);
            if ((lane & 3) == 0) {
                g_hpart[(tm * 128 + r0) * 8 + tn] = make_float2(m0, q0);
                g_hpart[(tm * 128 + r0 + 8) * 8 + tn] = make_float2(m1, q1);
            }
        }
        TL(MIX2 ? 6 : 3, 5);
        fence_proxy_async();
        named_bar(2 + wg, 128);
        if ((threadIdx.x & 127) == 0) {
            if (!MIX2) publish(&g_cnt_ln[tm * 2 + wg]);
            tma_st2(&p.out, s.base + C::STG_OFF + wg * 8192, tn * 128, tm * 128 + wg * 64);
            tma_st2(&p.out, s.base + C::STG_OFF + 16384 + wg * 8192, tn * 128 + 64, tm * 128 + wg * 64);
            tma_st_commit();
            if (!MIX2) spin_until(&g_cnt_ln[tm * 2 + wg], 8);
        }
        if (!MIX2) {
            named_bar(1, 256);
            float mean[2], scale[2];
#pragma unroll
            for (int i = 0; i < 2; i++) {
                const float4 t = __ldcg(reinterpret_cast<const float4*>(g_hpart + (tm * 128 + r0 + 8 * i) * 8) + (lane & 3));
                float m = t.x + t.z;
                m += __shfl_xor_sync(0xffffffffu, m, 1); m += __shfl_xor_sync(0xffffffffu, m, 2);
                m *= 0.125f;
                float q = t.y + t.w + 128.f * ((t.x - m) * (t.x - m) + (t.z - m) * (t.z - m));
                q += __shfl_xor_sync(0xffffffffu, q, 1); q += __shfl_xor_sync(0xffffffffu, q, 2);
                const float var = q * (1.f / DM);
                const float r1 = rsqrtf(var + 1e-5f);
                const float r2 = rsqrtf(var * r1 * r1 + 1e-5f);
                mean[i] = m; scale[i] = r1 * r2;
            }
#pragma unroll
            for (int j = 0; j < 16; j++) {
                const int off = (j >> 3) * 16384 + r0 * 128 + (((j & 7) ^ (r0 & 7)) << 4) + (lane & 3) * 4;
                *reinterpret_cast<uint32_t*>(smem_raw + off) = pack_bf16((bf_lo(hp[2 * j]) - mean[0]) * scale[0], (bf_hi(hp[2 * j]) - mean[0]) * scale[0]);
                *reinterpret_cast<uint32_t*>(smem_raw + off + 8 * 128) = pack_bf16((bf_lo(hp[2 * j + 1]) - mean[1]) * scale[1], (bf_hi(hp[2 * j + 1]) - mean[1]) * scale[1]);
            }
            fence_proxy_async();
            named_bar(2 + wg, 128);
            if ((threadIdx.x & 127) == 0) {
                tma_st2(&p.out2, s.base + wg * 8192, tn * 128, tm * 128 + wg * 64);
                tma_st2(&p.out2, s.base + 16384 + wg * 8192, tn * 128 + 64, tm * 128 + wg * 64);
                tma_st_commit();
            }
        }
        if ((threadIdx.x & 127) == 0) tma_st_wait();
        TL(MIX2 ? 6 : 3, 3);
    }
}

struct Mix1Params { CUtensorMap hn, w1, out; const bf16* bias; };
struct Mix1Cfg {
    static constexpr int MB = 1, BN = 224, KSTEPS = 32, STAGES = 5, A_BYTES = 16384, B_BYTES = 28672;
    static constexpr int STAGE_BYTES = A_BYTES + B_BYTES, BIAS_OFF = STAGES * STAGE_BYTES, BAR_OFF = BIAS_OFF + 1024, SMEM = BAR_OFF + 128;
    static constexpr int AUX_COUNT = 1;
    static __device__ __forceinline__ void load_w(const Mix1Params& p, uint32_t sb, uint32_t bar, int k, int tm, int tn) { tma_ld3(sb + A_BYTES, &p.w1, bar, 0, k * 64, tn * 7); }
    static __device__ __forceinline__ void load_x(const Mix1Params& p, uint32_t sb, uint32_t bar, int k, int tm, int tn) { tma_ld3(sb, &p.hn, bar, 0, k * 64, tm * 2); }
    static __device__ __forceinline__ void load_aux(const Mix1Params&, const GemmSmem&, int, int) {}
    static __device__ __forceinline__ uint32_t desc_a(uint32_t sb, int wg, int m, int kk) { return desc_lo(sb + wg * 8192 + kk * 2048, 8192); }
    static __device__ __forceinline__ uint32_t desc_b(uint32_t sb, int kk) { return desc_lo(sb + A_BYTES + kk * 1024, 4096); }
    static __device__ __forceinline__ void mma(float (&d)[112], uint32_t a, uint32_t b, int sc) { mma_mix1(d, a, b, sc); }
};
__global__ void __launch_bounds__(384, 1) mix1_kernel(const __grid_constant__ Mix1Params p) {
    using C = Mix1Cfg;
    extern __shared__ __align__(1024) uint8_t smem_raw[];
    TL(5, 4);
    pdl_launch();
    const int tm = blockIdx.x & 7, tn = blockIdx.x >> 3;
    if (threadIdx.x == 0) { prefetch_map(&p.hn); prefetch_map(&p.w1); prefetch_map(&p.out); }
    float* sbias = reinterpret_cast<float*>(smem_raw + C::BIAS_OFF);
    if (threadIdx.x < 224) sbias[threadIdx.x] = __bfloat162float(p.bias[tn * 224 + threadIdx.x]);
    const GemmSmem s = gemm_setup<C>(smem_raw);
    const int wgi = __shfl_sync(0xffffffffu, threadIdx.x >> 7, 0);
    if (wgi == 0) {
        reg_dealloc<40>();
        if (threadIdx.x == 0) gemm_producer<C>(s, p, tm, tn);
    } else {
        reg_alloc<232>();
        const int wg = wgi - 1, warp = (threadIdx.x >> 5) & 3, lane = threadIdx.x & 31;
        float acc[1][112];
        pdl_wait();
        if (blockIdx.x == 0 && threadIdx.x >= 128 && threadIdx.x < 160) g_cnt_ln[threadIdx.x - 128] = 0;
        TL(5, 0);
        gemm_mainloop<C>(s, wg, acc, 5);
        TL(5, 1);
        named_bar(1, 256);
        const int arow = warp * 16 + ((lane >> 3) & 1) * 8 + (lane & 7);
        const uint32_t stg = s.base + wg * 28672;
#pragma unroll
        for (int jp = 0; jp < 14; jp++) {
            float v[8];
#pragma unroll
            for (int h = 0; h < 2; h++) {
                const float2 bb = *reinterpret_cast<const float2*>(sbias + (jp * 2 + h) * 8 + (lane & 3) * 2);
#pragma unroll
                for (int i = 0; i < 4; i++) {
                    const float x = acc[0][jp * 8 + h * 4 + i] + ((i & 1) ? bb.y : bb.x);
                    const float inner = x * fmaf(x * x, 0.0356774081363f, 0.7978845608029f);
                    const float hx = 0.5f * x;
                    v[h * 4 + i] = fmaf(hx, tanh_fast(inner), hx);
                }
            }
            const int j = jp * 2 + (lane >> 4);
            const uint32_t addr = stg + (j >> 2) * 4096 + arow * 64 + (((j & 3) ^ ((arow >> 1) & 3)) << 4);
            stmatrix_x4(addr, pack_bf16(v[0], v[1]), pack_bf16(v[2], v[3]), pack_bf16(v[4], v[5]), pack_bf16(v[6], v[7]));
        }
        TL(5, 5);
        fence_proxy_async();
        named_bar(2 + wg, 128);
        if ((threadIdx.x & 127) == 0) {
            tma_st3(&p.out, stg, 0, tm * 128 + wg * 64, tn * 7);
            tma_st_commit();
            tma_st_wait();
        }
        TL(5, 3);
    }
}

typedef CUresult (*EncodeFn)(CUtensorMap*, CUtensorMapDataType, cuuint32_t, void*, const cuuint64_t*, const cuuint64_t*, const cuuint32_t*,
                             const cuuint32_t*, CUtensorMapInterleave, CUtensorMapSwizzle, CUtensorMapL2promotion, CUtensorMapFloatOOBfill);
EncodeFn g_encode;

void make_map(CUtensorMap* m, const void* ptr, int rank, const uint64_t* dims, const uint64_t* strides_bytes, const uint32_t* box, CUtensorMapSwizzle swz) {
    cuuint64_t d[5], st[5]; cuuint32_t b[5], es[5];
    for (int i = 0; i < rank; i++) { d[i] = dims[i]; b[i] = box[i]; es[i] = 1; }
    for (int i = 0; i + 1 < rank; i++) st[i] = strides_bytes[i];
    CUresult r = g_encode(m, CU_TENSOR_MAP_DATA_TYPE_BFLOAT16, rank, const_cast<void*>(ptr), d, st, b, es, CU_TENSOR_MAP_INTERLEAVE_NONE, swz,
                          CU_TENSOR_MAP_L2_PROMOTION_L2_128B, CU_TENSOR_MAP_FLOAT_OOB_FILL_NONE);
    if (r != CUDA_SUCCESS) fprintf(stderr, "cuTensorMapEncodeTiled failed: %d\n", (int)r);
}
void map2d(CUtensorMap* m, const void* ptr, uint64_t cols, uint64_t rows, uint32_t bc, uint32_t br, CUtensorMapSwizzle swz) {
    uint64_t dims[2] = {cols, rows}, st[1] = {cols * 2}; uint32_t box[2] = {bc, br};
    make_map(m, ptr, 2, dims, st, box, swz);
}
void map3d(CUtensorMap* m, const void* ptr, uint64_t cols, uint64_t rows, uint32_t inner, uint32_t br, uint32_t nblk, CUtensorMapSwizzle swz) {
    uint64_t dims[3] = {inner, rows, cols / inner}, st[2] = {cols * 2, (uint64_t)inner * 2}; uint32_t box[3] = {inner, br, nblk};
    make_map(m, ptr, 3, dims, st, box, swz);
}

template <class... KArgs, class... Args>
void launch(void (*kern)(KArgs...), int grid, int block, int smem, bool pdl, Args&&... args) {
    cudaLaunchConfig_t cfg = {};
    cfg.gridDim = dim3(grid); cfg.blockDim = dim3(block); cfg.dynamicSmemBytes = smem; cfg.stream = 0;
    cudaLaunchAttribute at[1];
    at[0].id = cudaLaunchAttributeProgrammaticStreamSerialization; at[0].val.programmaticStreamSerializationAllowed = 1;
    cfg.attrs = at; cfg.numAttrs = pdl ? 1 : 0;
    cudaError_t e = cudaLaunchKernelEx(&cfg, kern, KArgs(args)...);
    if (e != cudaSuccess) fprintf(stderr, "launch failed: %s\n", cudaGetErrorString(e));
}

struct HostState {
    bool ready;
    const void* key[9];
    QkvParams qkv; AttnParams attn; ResParams wo, mix2; Mix1Params mix1;
    bf16 *qkvp, *o, *h, *hn, *u;
};
HostState g_hs;

}

#define USE_PDL 1

extern "C" void kernel_launch(void* const* d_in, const int* in_sizes, int n_in, void* d_out, int out_size) {
    const bf16* x = (const bf16*)d_in[0];
    const bf16* wqkv = (const bf16*)d_in[1];
    const bf16* wo = (const bf16*)d_in[2];
    const bf16* w1 = (const bf16*)d_in[4];
    const bf16* b1 = (const bf16*)d_in[5];
    const bf16* w2 = (const bf16*)d_in[6];
    const bf16* b2 = (const bf16*)d_in[7];
    HostState& hs = g_hs;
    bool same = hs.ready;
    for (int i = 0; i < 8 && same; i++) same = (hs.key[i] == d_in[i]);
    same = same && hs.key[8] == d_out;
    if (!same) {
        if (!g_encode) {
            void* fn = nullptr; cudaDriverEntryPointQueryResult qr;
            cudaGetDriverEntryPoint("cuTensorMapEncodeTiled", &fn, cudaEnableDefault, &qr);
            g_encode = (EncodeFn)fn;
            cudaFuncSetAttribute(qkv_kernel, cudaFuncAttributeMaxDynamicSharedMemorySize, QkvCfg::SMEM);
            cudaFuncSetAttribute(attn_kernel, cudaFuncAttributeMaxDynamicSharedMemorySize, AT_SMEM);
            cudaFuncSetAttribute(res_gemm_kernel<false>, cudaFuncAttributeMaxDynamicSharedMemorySize, ResCfg<false>::SMEM);
            cudaFuncSetAttribute(res_gemm_kernel<true>, cudaFuncAttributeMaxDynamicSharedMemorySize, ResCfg<true>::SMEM);
            cudaFuncSetAttribute(mix1_kernel, cudaFuncAttributeMaxDynamicSharedMemorySize, Mix1Cfg::SMEM);
        }
        cudaGetSymbolAddress((void**)&hs.qkvp, g_qkv); cudaGetSymbolAddress((void**)&hs.o, g_o);
        cudaGetSymbolAddress((void**)&hs.h, g_h); cudaGetSymbolAddress((void**)&hs.hn, g_hn); cudaGetSymbolAddress((void**)&hs.u, g_u);
        const CUtensorMapSwizzle S128 = CU_TENSOR_MAP_SWIZZLE_128B, S64 = CU_TENSOR_MAP_SWIZZLE_64B;
        map2d(&hs.qkv.x, x, DM, SEQ, 64, 256, S128);
        hs.qkv.xp = x; hs.qkv.wp = wqkv;
        {
            uint64_t dims[4] = {64, (uint64_t)DM, 3, 16}, st[3] = {3 * DM * 2, DM * 2, 128}; uint32_t box[4] = {64, 64, 3, 1};
            make_map(&hs.qkv.w, wqkv, 4, dims, st, box, S128);
        }
        map2d(&hs.qkv.out, hs.qkvp, HD, 3 * NH * SEQ, 32, 128, S64);
        hs.attn.kv = hs.qkv.out; hs.attn.o = hs.o;
        {
            uint64_t dims[3] = {(uint64_t)HD, (uint64_t)NH * SEQ, 3}, st[2] = {HD * 2, (uint64_t)NH * SEQ * HD * 2}; uint32_t box[3] = {32, 128, 2};
            make_map(&hs.attn.kv2, hs.qkvp, 3, dims, st, box, S64);
        }
        map2d(&hs.wo.a, hs.o, DM, SEQ, 64, 128, S128);
        map3d(&hs.wo.b, wo, DM, DM, 64, 64, 2, S128);
        map2d(&hs.wo.res, x, DM, SEQ, 64, 128, S128);
        map2d(&hs.wo.out, hs.h, DM, SEQ, 64, 64, S128);
        map2d(&hs.wo.out2, hs.hn, DM, SEQ, 64, 64, S128);
        hs.wo.bias = nullptr;
        map3d(&hs.mix1.hn, hs.hn, DM, SEQ, 64, 64, 2, S128);
        map3d(&hs.mix1.w1, w1, FF, SEQ, 32, 64, 7, S64);
        map3d(&hs.mix1.out, hs.u, FF, DM, 32, 64, 7, S64);
        hs.mix1.bias = b1;
        map3d(&hs.mix2.a, w2, SEQ, FF, 64, 64, 2, S128);
        map2d(&hs.mix2.b, hs.u, FF, DM, 64, 128, S128);
        map2d(&hs.mix2.res, hs.h, DM, SEQ, 64, 128, S128);
        map2d(&hs.mix2.out, d_out, DM, SEQ, 64, 64, S128);
        hs.mix2.out2 = hs.mix2.out;
        hs.mix2.bias = b2;
        for (int i = 0; i < 8; i++) hs.key[i] = d_in[i];
        hs.key[8] = d_out;
        hs.ready = true;
    }
    const bool pdl = USE_PDL;
    const int G = 128;
    launch(qkv_kernel, G, 384, QkvCfg::SMEM, false, hs.qkv);
    launch(attn_kernel, 128, 512, AT_SMEM, pdl, hs.attn);
    launch(res_gemm_kernel<false>, G, 384, ResCfg<false>::SMEM, pdl, hs.wo);
    launch(mix1_kernel, G, 384, Mix1Cfg::SMEM, pdl, hs.mix1);
    launch(res_gemm_kernel<true>, G, 384, ResCfg<true>::SMEM, pdl, hs.mix2);
}
```

```cpp
#include <cuda_runtime.h>
#include <cuda_bf16.h>
#include <cuda.h>
#include <stdint.h>
#include <stdio.h>

typedef __nv_bfloat16 bf16;

namespace {

#define SKEW 0
#define POLY_MASK_B POLY_MASK
#define POLY_MASK 0x12492449u
#define MIX1_MC true
#define MIX2_MC false
#define WO_MC false
#define MIX1_PAIR false
#define MIX2_PAIR false
#define WO_PAIR false
#define MIX2_MAP 1
#define MIX1_SYNC 0
#define MIX2_SYNC 0
#define MIX1_PRE 2
#define RES_PRE 2
#define PF_W1 1
#define PF_W2_DELAY 4000
#define PF_W2 1
constexpr int SEQ = 2048, DM = 1024, NH = 32, HD = 32, FF = 3584;

__device__ __align__(1024) bf16 g_qkv[3 * NH * SEQ * HD];
__device__ __align__(1024) bf16 g_o[SEQ * DM];
__device__ __align__(1024) bf16 g_h[SEQ * DM];
__device__ __align__(1024) bf16 g_hn[SEQ * DM];
__device__ __align__(1024) bf16 g_u[DM * FF];
__device__ uint32_t g_norm[3 * NH * 16];
__device__ float2 g_rowstat[SEQ];
__device__ float g_colsum[8 * 3 * DM];
__device__ float2 g_hpart[SEQ * 8];
__device__ uint32_t g_cnt_ln[32];
__device__ uint32_t g_cnt_row[8], g_cnt_col[16];

#define TL(kern, slot)
#define AT(slot)

__device__ __forceinline__ uint32_t smem_u32(const void* p) { return (uint32_t)__cvta_generic_to_shared(p); }
__device__ __forceinline__ void mbar_init(uint32_t bar, uint32_t cnt) { asm volatile("mbarrier.init.shared::cta.b64 [%0], %1;" :: "r"(bar), "r"(cnt) : "memory"); }
__device__ __forceinline__ void mbar_expect_tx(uint32_t bar, uint32_t bytes) { asm volatile("mbarrier.arrive.expect_tx.shared::cta.b64 _, [%0], %1;" :: "r"(bar), "r"(bytes) : "memory"); }
__device__ __forceinline__ void mbar_arrive(uint32_t bar) { asm volatile("mbarrier.arrive.shared::cta.b64 _, [%0];" :: "r"(bar) : "memory"); }
__device__ __forceinline__ void mbar_wait(uint32_t bar, uint32_t parity) {
    asm volatile("{\n.reg .pred p;\nWAIT_%=:\nmbarrier.try_wait.parity.shared::cta.b64 p, [%0], %1;\n@p bra DONE_%=;\nbra WAIT_%=;\nDONE_%=:\n}" :: "r"(bar), "r"(parity) : "memory");
}
__device__ __forceinline__ void fence_barrier_init() { asm volatile("fence.mbarrier_init.release.cluster;" ::: "memory"); }
__device__ __forceinline__ void fence_proxy_async() { asm volatile("fence.proxy.async.shared::cta;" ::: "memory"); }
__device__ __forceinline__ void pdl_launch() { asm volatile("griddepcontrol.launch_dependents;" ::: "memory"); }
__device__ __forceinline__ void pdl_wait() { asm volatile("griddepcontrol.wait;" ::: "memory"); }
__device__ __forceinline__ void named_bar(int id, int n) { asm volatile("bar.sync %0, %1;" :: "r"(id), "r"(n) : "memory"); }
__device__ __forceinline__ void prefetch_map(const CUtensorMap* m) { asm volatile("prefetch.tensormap [%0];" :: "l"(m) : "memory"); }

__device__ __forceinline__ void tma_ld2(uint32_t dst, const CUtensorMap* m, uint32_t bar, int c0, int c1) {
    asm volatile("cp.async.bulk.tensor.2d.shared::cluster.global.mbarrier::complete_tx::bytes [%0], [%1, {%3, %4}], [%2];"
                 :: "r"(dst), "l"(m), "r"(bar), "r"(c0), "r"(c1) : "memory");
}
__device__ __forceinline__ void tma_ld3(uint32_t dst, const CUtensorMap* m, uint32_t bar, int c0, int c1, int c2) {
    asm volatile("cp.async.bulk.tensor.3d.shared::cluster.global.mbarrier::complete_tx::bytes [%0], [%1, {%3, %4, %5}], [%2];"
                 :: "r"(dst), "l"(m), "r"(bar), "r"(c0), "r"(c1), "r"(c2) : "memory");
}
__device__ __forceinline__ void tma_ld4(uint32_t dst, const CUtensorMap* m, uint32_t bar, int c0, int c1, int c2, int c3) {
    asm volatile("cp.async.bulk.tensor.4d.shared::cluster.global.mbarrier::complete_tx::bytes [%0], [%1, {%3, %4, %5, %6}], [%2];"
                 :: "r"(dst), "l"(m), "r"(bar), "r"(c0), "r"(c1), "r"(c2), "r"(c3) : "memory");
}
__device__ __forceinline__ void tma_ld3_mc(uint32_t dst, const CUtensorMap* m, uint32_t bar, int c0, int c1, int c2) {
    asm volatile("cp.async.bulk.tensor.3d.shared::cluster.global.mbarrier::complete_tx::bytes.multicast::cluster [%0], [%1, {%3, %4, %5}], [%2], %6;"
                 :: "r"(dst), "l"(m), "r"(bar), "r"(c0), "r"(c1), "r"(c2), "h"((uint16_t)3) : "memory");
}
__device__ __forceinline__ void tma_ld2_mc(uint32_t dst, const CUtensorMap* m, uint32_t bar, int c0, int c1) {
    asm volatile("cp.async.bulk.tensor.2d.shared::cluster.global.mbarrier::complete_tx::bytes.multicast::cluster [%0], [%1, {%3, %4}], [%2], %5;"
                 :: "r"(dst), "l"(m), "r"(bar), "r"(c0), "r"(c1), "h"((uint16_t)3) : "memory");
}
__device__ __forceinline__ void prefetch_line(const void* p) { asm volatile("prefetch.global.L2 [%0];" :: "l"(p)); }
__device__ __forceinline__ void l2_prefetch(const void* p, uint32_t bytes) { asm volatile("cp.async.bulk.prefetch.L2.global [%0], %1;" :: "l"(p), "r"(bytes) : "memory"); }
__device__ __forceinline__ uint32_t mapa(uint32_t addr, uint32_t cta) { uint32_t r; asm("mapa.shared::cluster.u32 %0, %1, %2;" : "=r"(r) : "r"(addr), "r"(cta)); return r; }
__device__ __forceinline__ void mbar_arrive_cluster(uint32_t bar) { asm volatile("mbarrier.arrive.shared::cluster.b64 _, [%0];" :: "r"(bar) : "memory"); }
__device__ __forceinline__ void cluster_sync() { asm volatile("barrier.cluster.arrive.release.aligned;\nbarrier.cluster.wait.acquire.aligned;" ::: "memory"); }
__device__ __forceinline__ void tma_st2(const CUtensorMap* m, uint32_t src, int c0, int c1) {
    asm volatile("cp.async.bulk.tensor.2d.global.shared::cta.bulk_group [%0, {%2, %3}], [%1];" :: "l"(m), "r"(src), "r"(c0), "r"(c1) : "memory");
}
__device__ __forceinline__ void tma_st3(const CUtensorMap* m, uint32_t src, int c0, int c1, int c2) {
    asm volatile("cp.async.bulk.tensor.3d.global.shared::cta.bulk_group [%0, {%2, %3, %4}], [%1];" :: "l"(m), "r"(src), "r"(c0), "r"(c1), "r"(c2) : "memory");
}
__device__ __forceinline__ void tma_st_commit() { asm volatile("cp.async.bulk.commit_group;" ::: "memory"); }
__device__ __forceinline__ void tma_st_wait() { asm volatile("cp.async.bulk.wait_group.read 0;" ::: "memory"); }

__device__ __forceinline__ void wg_fence() { asm volatile("wgmma.fence.sync.aligned;" ::: "memory"); }
__device__ __forceinline__ void wg_commit() { asm volatile("wgmma.commit_group.sync.aligned;" ::: "memory"); }
template <int N> __device__ __forceinline__ void wg_wait() { asm volatile("wgmma.wait_group.sync.aligned %0;" :: "n"(N) : "memory"); }
template <int R> __device__ __forceinline__ void reg_alloc() { asm volatile("setmaxnreg.inc.sync.aligned.u32 %0;" :: "n"(R)); }
template <int R> __device__ __forceinline__ void reg_dealloc() { asm volatile("setmaxnreg.dec.sync.aligned.u32 %0;" :: "n"(R)); }
template <int N> __device__ __forceinline__ void fence_regs(float (&d)[N]) {
#pragma unroll
    for (int i = 0; i < N; i++) asm volatile("" : "+f"(d[i]) :: "memory");
}

__device__ __forceinline__ uint32_t desc_lo(uint32_t addr, uint32_t lbo) { return ((addr & 0x3FFFFu) >> 4) | ((lbo >> 4) << 16); }
__device__ __forceinline__ uint32_t pack_bf16(float lo, float hi) { uint32_t d; asm("cvt.rn.bf16x2.f32 %0, %1, %2;" : "=r"(d) : "f"(hi), "f"(lo)); return d; }
__device__ __forceinline__ float bf_lo(uint32_t v) { return __uint_as_float(v << 16); }
__device__ __forceinline__ float bf_hi(uint32_t v) { return __uint_as_float(v & 0xFFFF0000u); }
__device__ __forceinline__ void stmatrix_x4(uint32_t addr, uint32_t r0, uint32_t r1, uint32_t r2, uint32_t r3) {
    asm volatile("stmatrix.sync.aligned.m8n8.x4.shared.b16 [%0], {%1, %2, %3, %4};" :: "r"(addr), "r"(r0), "r"(r1), "r"(r2), "r"(r3) : "memory");
}
__device__ __forceinline__ float ex2(float x) { float y; asm("ex2.approx.ftz.f32 %0, %1;" : "=f"(y) : "f"(x)); return y; }
__device__ __forceinline__ float tanh_fast(float x) { float y; asm("tanh.approx.f32 %0, %1;" : "=f"(y) : "f"(x)); return y; }

__device__ __forceinline__ void mma_qkv(float (&d)[96], uint32_t alo, uint32_t blo, int scale_d) {
    asm volatile("{\n.reg .pred p;\n.reg .b64 da, db;\nsetp.ne.b32 p, %98, 0;\nmov.b64 da, {%96, 0x40000040};\nmov.b64 db, {%97, 0x40000040};\n"
        "wgmma.mma_async.sync.aligned.m64n192k16.f32.bf16.bf16 {"
        "%0, %1, %2, %3, %4, %5, %6, %7, %8, %9, %10, %11, %12, %13, %14, %15, %16, %17, %18, %19, %20, %21, %22, %23, %24, %25, %26, %27, %28, %29, %30, %31,  "
        "%32, %33, %34, %35, %36, %37, %38, %39, %40, %41, %42, %43, %44, %45, %46, %47, %48, %49, %50, %51, %52, %53, %54, %55, %56, %57, %58, %59, %60, %61,  "
        "%62, %63, %64, %65, %66, %67, %68, %69, %70, %71, %72, %73, %74, %75, %76, %77, %78, %79, %80, %81, %82, %83, %84, %85, %86, %87, %88, %89, %90, %91,  "
        "%92, %93, %94, %95 "
        "}, da, db, p, 1, 1, 0, 1;\n}\n"
        : "+f"(d[0]), "+f"(d[1]), "+f"(d[2]), "+f"(d[3]), "+f"(d[4]), "+f"(d[5]), "+f"(d[6]), "+f"(d[7]), "+f"(d[8]), "+f"(d[9]), "+f"(d[10]), "+f"(d[11]),
          "+f"(d[12]), "+f"(d[13]), "+f"(d[14]), "+f"(d[15]), "+f"(d[16]), "+f"(d[17]), "+f"(d[18]), "+f"(d[19]), "+f"(d[20]), "+f"(d[21]), "+f"(d[22]),
          "+f"(d[23]), "+f"(d[24]), "+f"(d[25]), "+f"(d[26]), "+f"(d[27]), "+f"(d[28]), "+f"(d[29]), "+f"(d[30]), "+f"(d[31]), "+f"(d[32]), "+f"(d[33]),
          "+f"(d[34]), "+f"(d[35]), "+f"(d[36]), "+f"(d[37]), "+f"(d[38]), "+f"(d[39]), "+f"(d[40]), "+f"(d[41]), "+f"(d[42]), "+f"(d[43]), "+f"(d[44]),
          "+f"(d[45]), "+f"(d[46]), "+f"(d[47]), "+f"(d[48]), "+f"(d[49]), "+f"(d[50]), "+f"(d[51]), "+f"(d[52]), "+f"(d[53]), "+f"(d[54]), "+f"(d[55]),
          "+f"(d[56]), "+f"(d[57]), "+f"(d[58]), "+f"(d[59]), "+f"(d[60]), "+f"(d[61]), "+f"(d[62]), "+f"(d[63]), "+f"(d[64]), "+f"(d[65]), "+f"(d[66]),
          "+f"(d[67]), "+f"(d[68]), "+f"(d[69]), "+f"(d[70]), "+f"(d[71]), "+f"(d[72]), "+f"(d[73]), "+f"(d[74]), "+f"(d[75]), "+f"(d[76]), "+f"(d[77]),
          "+f"(d[78]), "+f"(d[79]), "+f"(d[80]), "+f"(d[81]), "+f"(d[82]), "+f"(d[83]), "+f"(d[84]), "+f"(d[85]), "+f"(d[86]), "+f"(d[87]), "+f"(d[88]),
          "+f"(d[89]), "+f"(d[90]), "+f"(d[91]), "+f"(d[92]), "+f"(d[93]), "+f"(d[94]), "+f"(d[95])
        : "r"(alo), "r"(blo), "r"(scale_d));
}
__device__ __forceinline__ void mma_wo(float (&d)[64], uint32_t alo, uint32_t blo, int scale_d) {
    asm volatile("{\n.reg .pred p;\n.reg .b64 da, db;\nsetp.ne.b32 p, %66, 0;\nmov.b64 da, {%64, 0x40000040};\nmov.b64 db, {%65, 0x40000040};\n"
        "wgmma.mma_async.sync.aligned.m64n128k16.f32.bf16.bf16 {"
        "%0, %1, %2, %3, %4, %5, %6, %7, %8, %9, %10, %11, %12, %13, %14, %15, %16, %17, %18, %19, %20, %21, %22, %23, %24, %25, %26, %27, %28, %29, %30, %31,  "
        "%32, %33, %34, %35, %36, %37, %38, %39, %40, %41, %42, %43, %44, %45, %46, %47, %48, %49, %50, %51, %52, %53, %54, %55, %56, %57, %58, %59, %60, %61,  "
        "%62, %63 "
        "}, da, db, p, 1, 1, 0, 1;\n}\n"
        : "+f"(d[0]), "+f"(d[1]), "+f"(d[2]), "+f"(d[3]), "+f"(d[4]), "+f"(d[5]), "+f"(d[6]), "+f"(d[7]), "+f"(d[8]), "+f"(d[9]), "+f"(d[10]), "+f"(d[11]),
          "+f"(d[12]), "+f"(d[13]), "+f"(d[14]), "+f"(d[15]), "+f"(d[16]), "+f"(d[17]), "+f"(d[18]), "+f"(d[19]), "+f"(d[20]), "+f"(d[21]), "+f"(d[22]),
          "+f"(d[23]), "+f"(d[24]), "+f"(d[25]), "+f"(d[26]), "+f"(d[27]), "+f"(d[28]), "+f"(d[29]), "+f"(d[30]), "+f"(d[31]), "+f"(d[32]), "+f"(d[33]),
          "+f"(d[34]), "+f"(d[35]), "+f"(d[36]), "+f"(d[37]), "+f"(d[38]), "+f"(d[39]), "+f"(d[40]), "+f"(d[41]), "+f"(d[42]), "+f"(d[43]), "+f"(d[44]),
          "+f"(d[45]), "+f"(d[46]), "+f"(d[47]), "+f"(d[48]), "+f"(d[49]), "+f"(d[50]), "+f"(d[51]), "+f"(d[52]), "+f"(d[53]), "+f"(d[54]), "+f"(d[55]),
          "+f"(d[56]), "+f"(d[57]), "+f"(d[58]), "+f"(d[59]), "+f"(d[60]), "+f"(d[61]), "+f"(d[62]), "+f"(d[63])
        : "r"(alo), "r"(blo), "r"(scale_d));
}
__device__ __forceinline__ void mma_mix2(float (&d)[64], uint32_t alo, uint32_t blo, int scale_d) {
    asm volatile("{\n.reg .pred p;\n.reg .b64 da, db;\nsetp.ne.b32 p, %66, 0;\nmov.b64 da, {%64, 0x40000040};\nmov.b64 db, {%65, 0x40000040};\n"
        "wgmma.mma_async.sync.aligned.m64n128k16.f32.bf16.bf16 {"
        "%0, %1, %2, %3, %4, %5, %6, %7, %8, %9, %10, %11, %12, %13, %14, %15, %16, %17, %18, %19, %20, %21, %22, %23, %24, %25, %26, %27, %28, %29, %30, %31,  "
        "%32, %33, %34, %35, %36, %37, %38, %39, %40, %41, %42, %43, %44, %45, %46, %47, %48, %49, %50, %51, %52, %53, %54, %55, %56, %57, %58, %59, %60, %61,  "
        "%62, %63 "
        "}, da, db, p, 1, 1, 1, 0;\n}\n"
        : "+f"(d[0]), "+f"(d[1]), "+f"(d[2]), "+f"(d[3]), "+f"(d[4]), "+f"(d[5]), "+f"(d[6]), "+f"(d[7]), "+f"(d[8]), "+f"(d[9]), "+f"(d[10]), "+f"(d[11]),
          "+f"(d[12]), "+f"(d[13]), "+f"(d[14]), "+f"(d[15]), "+f"(d[16]), "+f"(d[17]), "+f"(d[18]), "+f"(d[19]), "+f"(d[20]), "+f"(d[21]), "+f"(d[22]),
          "+f"(d[23]), "+f"(d[24]), "+f"(d[25]), "+f"(d[26]), "+f"(d[27]), "+f"(d[28]), "+f"(d[29]), "+f"(d[30]), "+f"(d[31]), "+f"(d[32]), "+f"(d[33]),
          "+f"(d[34]), "+f"(d[35]), "+f"(d[36]), "+f"(d[37]), "+f"(d[38]), "+f"(d[39]), "+f"(d[40]), "+f"(d[41]), "+f"(d[42]), "+f"(d[43]), "+f"(d[44]),
          "+f"(d[45]), "+f"(d[46]), "+f"(d[47]), "+f"(d[48]), "+f"(d[49]), "+f"(d[50]), "+f"(d[51]), "+f"(d[52]), "+f"(d[53]), "+f"(d[54]), "+f"(d[55]),
          "+f"(d[56]), "+f"(d[57]), "+f"(d[58]), "+f"(d[59]), "+f"(d[60]), "+f"(d[61]), "+f"(d[62]), "+f"(d[63])
        : "r"(alo), "r"(blo), "r"(scale_d));
}
__device__ __forceinline__ void mma_mix1(float (&d)[112], uint32_t alo, uint32_t blo, int scale_d) {
    asm volatile("{\n.reg .pred p;\n.reg .b64 da, db;\nsetp.ne.b32 p, %114, 0;\nmov.b64 da, {%112, 0x40000040};\nmov.b64 db, {%113, 0x80000020};\n"
        "wgmma.mma_async.sync.aligned.m64n224k16.f32.bf16.bf16 {"
        "%0, %1, %2, %3, %4, %5, %6, %7, %8, %9, %10, %11, %12, %13, %14, %15, %16, %17, %18, %19, %20, %21, %22, %23, %24, %25, %26, %27, %28, %29, %30, %31,  "
        "%32, %33, %34, %35, %36, %37, %38, %39, %40, %41, %42, %43, %44, %45, %46, %47, %48, %49, %50, %51, %52, %53, %54, %55, %56, %57, %58, %59, %60, %61,  "
        "%62, %63, %64, %65, %66, %67, %68, %69, %70, %71, %72, %73, %74, %75, %76, %77, %78, %79, %80, %81, %82, %83, %84, %85, %86, %87, %88, %89, %90, %91,  "
        "%92, %93, %94, %95, %96, %97, %98, %99, %100, %101, %102, %103, %104, %105, %106, %107, %108, %109, %110, %111 "
        "}, da, db, p, 1, 1, 1, 1;\n}\n"
        : "+f"(d[0]), "+f"(d[1]), "+f"(d[2]), "+f"(d[3]), "+f"(d[4]), "+f"(d[5]), "+f"(d[6]), "+f"(d[7]), "+f"(d[8]), "+f"(d[9]), "+f"(d[10]), "+f"(d[11]),
          "+f"(d[12]), "+f"(d[13]), "+f"(d[14]), "+f"(d[15]), "+f"(d[16]), "+f"(d[17]), "+f"(d[18]), "+f"(d[19]), "+f"(d[20]), "+f"(d[21]), "+f"(d[22]),
          "+f"(d[23]), "+f"(d[24]), "+f"(d[25]), "+f"(d[26]), "+f"(d[27]), "+f"(d[28]), "+f"(d[29]), "+f"(d[30]), "+f"(d[31]), "+f"(d[32]), "+f"(d[33]),
          "+f"(d[34]), "+f"(d[35]), "+f"(d[36]), "+f"(d[37]), "+f"(d[38]), "+f"(d[39]), "+f"(d[40]), "+f"(d[41]), "+f"(d[42]), "+f"(d[43]), "+f"(d[44]),
          "+f"(d[45]), "+f"(d[46]), "+f"(d[47]), "+f"(d[48]), "+f"(d[49]), "+f"(d[50]), "+f"(d[51]), "+f"(d[52]), "+f"(d[53]), "+f"(d[54]), "+f"(d[55]),
          "+f"(d[56]), "+f"(d[57]), "+f"(d[58]), "+f"(d[59]), "+f"(d[60]), "+f"(d[61]), "+f"(d[62]), "+f"(d[63]), "+f"(d[64]), "+f"(d[65]), "+f"(d[66]),
          "+f"(d[67]), "+f"(d[68]), "+f"(d[69]), "+f"(d[70]), "+f"(d[71]), "+f"(d[72]), "+f"(d[73]), "+f"(d[74]), "+f"(d[75]), "+f"(d[76]), "+f"(d[77]),
          "+f"(d[78]), "+f"(d[79]), "+f"(d[80]), "+f"(d[81]), "+f"(d[82]), "+f"(d[83]), "+f"(d[84]), "+f"(d[85]), "+f"(d[86]), "+f"(d[87]), "+f"(d[88]),
          "+f"(d[89]), "+f"(d[90]), "+f"(d[91]), "+f"(d[92]), "+f"(d[93]), "+f"(d[94]), "+f"(d[95]), "+f"(d[96]), "+f"(d[97]), "+f"(d[98]), "+f"(d[99]),
          "+f"(d[100]), "+f"(d[101]), "+f"(d[102]), "+f"(d[103]), "+f"(d[104]), "+f"(d[105]), "+f"(d[106]), "+f"(d[107]), "+f"(d[108]), "+f"(d[109]),
          "+f"(d[110]), "+f"(d[111])
        : "r"(alo), "r"(blo), "r"(scale_d));
}
__device__ __forceinline__ void mma_qk0(float (&d)[32], uint32_t alo, uint32_t blo) {
    asm volatile("{\n.reg .pred p;\n.reg .b64 da, db;\nsetp.ne.b32 p, 0, 0;\nmov.b64 da, {%32, 0x80000020};\nmov.b64 db, {%33, 0x80000020};\n"
        "wgmma.mma_async.sync.aligned.m64n64k16.f32.bf16.bf16 {"
        "%0, %1, %2, %3, %4, %5, %6, %7, %8, %9, %10, %11, %12, %13, %14, %15, %16, %17, %18, %19, %20, %21, %22, %23, %24, %25, %26, %27, %28, %29, %30, %31 "
        "}, da, db, p, 1, 1, 0, 0;\n}\n"
        : "=f"(d[0]), "=f"(d[1]), "=f"(d[2]), "=f"(d[3]), "=f"(d[4]), "=f"(d[5]), "=f"(d[6]), "=f"(d[7]), "=f"(d[8]), "=f"(d[9]), "=f"(d[10]), "=f"(d[11]),
          "=f"(d[12]), "=f"(d[13]), "=f"(d[14]), "=f"(d[15]), "=f"(d[16]), "=f"(d[17]), "=f"(d[18]), "=f"(d[19]), "=f"(d[20]), "=f"(d[21]), "=f"(d[22]),
          "=f"(d[23]), "=f"(d[24]), "=f"(d[25]), "=f"(d[26]), "=f"(d[27]), "=f"(d[28]), "=f"(d[29]), "=f"(d[30]), "=f"(d[31])
        : "r"(alo), "r"(blo));
}
__device__ __forceinline__ void mma_qk1(float (&d)[32], uint32_t alo, uint32_t blo, int scale_d) {
    asm volatile("{\n.reg .pred p;\n.reg .b64 da, db;\nsetp.ne.b32 p, %34, 0;\nmov.b64 da, {%32, 0x80000020};\nmov.b64 db, {%33, 0x80000020};\n"
        "wgmma.mma_async.sync.aligned.m64n64k16.f32.bf16.bf16 {"
        "%0, %1, %2, %3, %4, %5, %6, %7, %8, %9, %10, %11, %12, %13, %14, %15, %16, %17, %18, %19, %20, %21, %22, %23, %24, %25, %26, %27, %28, %29, %30, %31 "
        "}, da, db, p, 1, 1, 0, 0;\n}\n"
        : "+f"(d[0]), "+f"(d[1]), "+f"(d[2]), "+f"(d[3]), "+f"(d[4]), "+f"(d[5]), "+f"(d[6]), "+f"(d[7]), "+f"(d[8]), "+f"(d[9]), "+f"(d[10]), "+f"(d[11]),
          "+f"(d[12]), "+f"(d[13]), "+f"(d[14]), "+f"(d[15]), "+f"(d[16]), "+f"(d[17]), "+f"(d[18]), "+f"(d[19]), "+f"(d[20]), "+f"(d[21]), "+f"(d[22]),
          "+f"(d[23]), "+f"(d[24]), "+f"(d[25]), "+f"(d[26]), "+f"(d[27]), "+f"(d[28]), "+f"(d[29]), "+f"(d[30]), "+f"(d[31])
        : "r"(alo), "r"(blo), "r"(scale_d));
}
__device__ __forceinline__ void mma_qkw0(float (&d)[64], uint32_t alo, uint32_t blo) {
    asm volatile("{\n.reg .pred p;\n.reg .b64 da, db;\nsetp.ne.b32 p, 0, 0;\nmov.b64 da, {%64, 0x80000020};\nmov.b64 db, {%65, 0x80000020};\n"
        "wgmma.mma_async.sync.aligned.m64n128k16.f32.bf16.bf16 {"
        "%0, %1, %2, %3, %4, %5, %6, %7, %8, %9, %10, %11, %12, %13, %14, %15, %16, %17, %18, %19, %20, %21, %22, %23, %24, %25, %26, %27, %28, %29, %30, %31,  "
        "%32, %33, %34, %35, %36, %37, %38, %39, %40, %41, %42, %43, %44, %45, %46, %47, %48, %49, %50, %51, %52, %53, %54, %55, %56, %57, %58, %59, %60, %61,  "
        "%62, %63 "
        "}, da, db, p, 1, 1, 0, 0;\n}\n"
        : "=f"(d[0]), "=f"(d[1]), "=f"(d[2]), "=f"(d[3]), "=f"(d[4]), "=f"(d[5]), "=f"(d[6]), "=f"(d[7]), "=f"(d[8]), "=f"(d[9]), "=f"(d[10]), "=f"(d[11]),
          "=f"(d[12]), "=f"(d[13]), "=f"(d[14]), "=f"(d[15]), "=f"(d[16]), "=f"(d[17]), "=f"(d[18]), "=f"(d[19]), "=f"(d[20]), "=f"(d[21]), "=f"(d[22]),
          "=f"(d[23]), "=f"(d[24]), "=f"(d[25]), "=f"(d[26]), "=f"(d[27]), "=f"(d[28]), "=f"(d[29]), "=f"(d[30]), "=f"(d[31]), "=f"(d[32]), "=f"(d[33]),
          "=f"(d[34]), "=f"(d[35]), "=f"(d[36]), "=f"(d[37]), "=f"(d[38]), "=f"(d[39]), "=f"(d[40]), "=f"(d[41]), "=f"(d[42]), "=f"(d[43]), "=f"(d[44]),
          "=f"(d[45]), "=f"(d[46]), "=f"(d[47]), "=f"(d[48]), "=f"(d[49]), "=f"(d[50]), "=f"(d[51]), "=f"(d[52]), "=f"(d[53]), "=f"(d[54]), "=f"(d[55]),
          "=f"(d[56]), "=f"(d[57]), "=f"(d[58]), "=f"(d[59]), "=f"(d[60]), "=f"(d[61]), "=f"(d[62]), "=f"(d[63])
        : "r"(alo), "r"(blo));
}
__device__ __forceinline__ void mma_qkw1(float (&d)[64], uint32_t alo, uint32_t blo, int scale_d) {
    asm volatile("{\n.reg .pred p;\n.reg .b64 da, db;\nsetp.ne.b32 p, %66, 0;\nmov.b64 da, {%64, 0x80000020};\nmov.b64 db, {%65, 0x80000020};\n"
        "wgmma.mma_async.sync.aligned.m64n128k16.f32.bf16.bf16 {"
        "%0, %1, %2, %3, %4, %5, %6, %7, %8, %9, %10, %11, %12, %13, %14, %15, %16, %17, %18, %19, %20, %21, %22, %23, %24, %25, %26, %27, %28, %29, %30, %31,  "
        "%32, %33, %34, %35, %36, %37, %38, %39, %40, %41, %42, %43, %44, %45, %46, %47, %48, %49, %50, %51, %52, %53, %54, %55, %56, %57, %58, %59, %60, %61,  "
        "%62, %63 "
        "}, da, db, p, 1, 1, 0, 0;\n}\n"
        : "+f"(d[0]), "+f"(d[1]), "+f"(d[2]), "+f"(d[3]), "+f"(d[4]), "+f"(d[5]), "+f"(d[6]), "+f"(d[7]), "+f"(d[8]), "+f"(d[9]), "+f"(d[10]), "+f"(d[11]),
          "+f"(d[12]), "+f"(d[13]), "+f"(d[14]), "+f"(d[15]), "+f"(d[16]), "+f"(d[17]), "+f"(d[18]), "+f"(d[19]), "+f"(d[20]), "+f"(d[21]), "+f"(d[22]),
          "+f"(d[23]), "+f"(d[24]), "+f"(d[25]), "+f"(d[26]), "+f"(d[27]), "+f"(d[28]), "+f"(d[29]), "+f"(d[30]), "+f"(d[31]), "+f"(d[32]), "+f"(d[33]),
          "+f"(d[34]), "+f"(d[35]), "+f"(d[36]), "+f"(d[37]), "+f"(d[38]), "+f"(d[39]), "+f"(d[40]), "+f"(d[41]), "+f"(d[42]), "+f"(d[43]), "+f"(d[44]),
          "+f"(d[45]), "+f"(d[46]), "+f"(d[47]), "+f"(d[48]), "+f"(d[49]), "+f"(d[50]), "+f"(d[51]), "+f"(d[52]), "+f"(d[53]), "+f"(d[54]), "+f"(d[55]),
          "+f"(d[56]), "+f"(d[57]), "+f"(d[58]), "+f"(d[59]), "+f"(d[60]), "+f"(d[61]), "+f"(d[62]), "+f"(d[63])
        : "r"(alo), "r"(blo), "r"(scale_d));
}
__device__ __forceinline__ void mma_pv(float (&d)[20], uint32_t a0, uint32_t a1, uint32_t a2, uint32_t a3, uint32_t blo, int scale_d) {
    asm volatile("{\n.reg .pred p;\n.reg .b64 da, db;\nsetp.ne.b32 p, %25, 0;\nmov.b64 db, {%24, 0x80000020};\n"
        "wgmma.mma_async.sync.aligned.m64n40k16.f32.bf16.bf16 {"
        "%0, %1, %2, %3, %4, %5, %6, %7, %8, %9, %10, %11, %12, %13, %14, %15, %16, %17, %18, %19 "
        "}, {%20, %21, %22, %23}, db, p, 1, 1, 1;\n}\n"
        : "+f"(d[0]), "+f"(d[1]), "+f"(d[2]), "+f"(d[3]), "+f"(d[4]), "+f"(d[5]), "+f"(d[6]), "+f"(d[7]), "+f"(d[8]), "+f"(d[9]), "+f"(d[10]), "+f"(d[11]),
          "+f"(d[12]), "+f"(d[13]), "+f"(d[14]), "+f"(d[15]), "+f"(d[16]), "+f"(d[17]), "+f"(d[18]), "+f"(d[19])
        : "r"(a0), "r"(a1), "r"(a2), "r"(a3), "r"(blo), "r"(scale_d));
}

__device__ __forceinline__ float warp_sum(float v) {
#pragma unroll
    for (int o = 16; o > 0; o >>= 1) v += __shfl_xor_sync(0xffffffffu, v, o);
    return v;
}

struct GemmSmem { uint32_t base, full0, empty0, aux; };

template <class C>
__device__ __forceinline__ GemmSmem gemm_setup(uint8_t* smem_raw) {
    GemmSmem s;
    s.base = smem_u32(smem_raw);
    s.full0 = s.base + C::BAR_OFF; s.empty0 = s.full0 + 8 * C::STAGES; s.aux = s.empty0 + 8 * C::STAGES;
    if (threadIdx.x == 0) {
        if (s.base & 1023) __trap();
        for (int i = 0; i < C::STAGES; i++) { mbar_init(s.full0 + 8 * i, 1); mbar_init(s.empty0 + 8 * i, C::MC ? 16 : 8); }
        mbar_init(s.aux, C::AUX_COUNT);
        fence_barrier_init();
    }
    if (C::MC) cluster_sync(); else __syncthreads();
    return s;
}

template <class C, class P>
__device__ __forceinline__ void gemm_producer(const GemmSmem& s, const P& p, int tm, int tn) {
#pragma unroll 1
    for (int k = 0; k < C::PRE; k++) {
        mbar_expect_tx(s.full0 + 8 * k, C::STAGE_BYTES);
        C::load_w(p, s.base + k * C::STAGE_BYTES, s.full0 + 8 * k, k, tm, tn);
    }
    pdl_wait();
#pragma unroll 1
    for (int k = 0; k < C::STAGES; k++) {
        if (k >= C::PRE) mbar_expect_tx(s.full0 + 8 * k, C::STAGE_BYTES);
        C::load_x(p, s.base + k * C::STAGE_BYTES, s.full0 + 8 * k, k, tm, tn);
        if (k >= C::PRE) C::load_w(p, s.base + k * C::STAGE_BYTES, s.full0 + 8 * k, k, tm, tn);
    }
    C::load_aux(p, s, tm, tn);
    int st = 0; uint32_t ph = 0;
#pragma unroll 1
    for (int k = C::STAGES; k < C::KSTEPS; k++) {
        mbar_wait(s.empty0 + 8 * st, ph);
        mbar_expect_tx(s.full0 + 8 * st, C::STAGE_BYTES);
        C::load_x(p, s.base + st * C::STAGE_BYTES, s.full0 + 8 * st, k, tm, tn);
        C::load_w(p, s.base + st * C::STAGE_BYTES, s.full0 + 8 * st, k, tm, tn);
        C::prefetch(p, k);
        if (++st == C::STAGES) { st = 0; ph ^= 1; }
    }
}

template <class C>
__device__ __forceinline__ void gemm_mainloop(const GemmSmem& s, int wg, float (&acc)[C::MB][C::BN / 2], int tlk = 0) {
    const int lane = threadIdx.x & 31;
    if (C::SYNC_NS > 0) {
        unsigned long long t0, t1; asm volatile("mov.u64 %0, %%globaltimer;" : "=l"(t0));
        do { asm volatile("mov.u64 %0, %%globaltimer;" : "=l"(t1)); } while (t1 - t0 < C::SYNC_NS);
    }
    int st = 0; uint32_t ph = 0;
    int prev = 0;
    const uint32_t rel0 = C::MC ? mapa(s.empty0, lane & 1) : s.empty0;
#pragma unroll
    for (int m = 0; m < C::MB; m++) fence_regs(acc[m]);
#pragma unroll 1
    for (int k = 0; k < C::KSTEPS; k++) {
        mbar_wait(s.full0 + 8 * st, ph);
        const uint32_t sb = s.base + st * C::STAGE_BYTES;
        wg_fence();
#pragma unroll
        for (int kk = 0; kk < 4; kk++) {
#pragma unroll
            for (int m = 0; m < C::MB; m++) C::mma(acc[m], C::desc_a(sb, wg, m, kk), C::desc_b(sb, kk), (k | kk) != 0);
        }
        wg_commit();
        if (k > 0) {
            wg_wait<1>();
            if (k <= C::KSTEPS - C::STAGES) {
                if (C::MC) { if (lane < 2) mbar_arrive_cluster(rel0 + 8 * prev); }
                else if (lane == 0) mbar_arrive(rel0 + 8 * prev);
            }
        }
        prev = st;
        if (++st == C::STAGES) { st = 0; ph ^= 1; }
    }
    wg_wait<0>();
#pragma unroll
    for (int m = 0; m < C::MB; m++) fence_regs(acc[m]);
}

struct QkvParams { CUtensorMap x, w, out; const bf16* xp; const bf16* wp; };
struct QkvCfg {
    static constexpr int MB = 2, BN = 192, KSTEPS = 16, STAGES = 4, A_BYTES = 32768, B_BYTES = 24576;
    static constexpr int STAGE_BYTES = A_BYTES + B_BYTES, BAR_OFF = STAGES * STAGE_BYTES, AUX_OFF = BAR_OFF + 128, SMEM = AUX_OFF + 2816;
    static constexpr int AUX_COUNT = 3, PRE = STAGES;
    static constexpr bool MC = false, PAIR = false;
    static constexpr int SYNC_NS = 0;
    static __device__ __forceinline__ void prefetch(const QkvParams&, int) {}
    static __device__ __forceinline__ void load_w(const QkvParams& p, uint32_t sb, uint32_t bar, int k, int tm, int tn) { tma_ld4(sb + A_BYTES, &p.w, bar, 0, k * 64, 0, tn); }
    static __device__ __forceinline__ void load_x(const QkvParams& p, uint32_t sb, uint32_t bar, int k, int tm, int tn) { tma_ld2(sb, &p.x, bar, k * 64, tm * 256); }
    static __device__ __forceinline__ void load_aux(const QkvParams&, const GemmSmem&, int, int) {}
    static __device__ __forceinline__ uint32_t desc_a(uint32_t sb, int wg, int m, int kk) { return desc_lo(sb + (wg * 128 + m * 64) * 128 + kk * 32, 16); }
    static __device__ __forceinline__ uint32_t desc_b(uint32_t sb, int kk) { return desc_lo(sb + A_BYTES + kk * 2048, 8192); }
    static __device__ __forceinline__ void mma(float (&d)[96], uint32_t a, uint32_t b, int sc) { mma_qkv(d, a, b, sc); }
};

__device__ __forceinline__ void spin_until(const uint32_t* cnt, uint32_t target) {
    uint32_t v; int it = 0;
    do {
        asm volatile("ld.acquire.gpu.global.u32 %0, [%1];" : "=r"(v) : "l"(cnt) : "memory");
        if (++it > (1 << 22)) __trap();
    } while (v < target);
}
__device__ __forceinline__ void publish(uint32_t* cnt) { asm volatile("red.release.gpu.global.add.u32 [%0], 1;" :: "l"(cnt) : "memory"); }

__device__ __forceinline__ void qkv_aux(const QkvParams& p, uint8_t* smem_raw, const GemmSmem& s, int tm, int tn, int w, int lane) {
    for (int r = w; r < 16; r += 3) {
        const int row = tm * 256 + tn * 16 + r;
        const uint4* src = reinterpret_cast<const uint4*>(p.xp + (size_t)row * DM);
        uint32_t v[16];
#pragma unroll
        for (int i = 0; i < 4; i++) { const uint4 t = __ldg(src + lane + 32 * i); v[4 * i] = t.x; v[4 * i + 1] = t.y; v[4 * i + 2] = t.z; v[4 * i + 3] = t.w; }
        float sum = 0.f;
#pragma unroll
        for (int i = 0; i < 16; i++) sum += bf_lo(v[i]) + bf_hi(v[i]);
        const float mean = warp_sum(sum) * (1.f / DM);
        float q = 0.f;
#pragma unroll
        for (int i = 0; i < 16; i++) { const float a = bf_lo(v[i]) - mean, b = bf_hi(v[i]) - mean; q += a * a + b * b; }
        const float rstd = rsqrtf(warp_sum(q) * (1.f / DM) + 1e-5f);
        if (lane == 0) g_rowstat[row] = make_float2(mean, rstd);
    }
    __syncwarp();
    if (lane == 0) publish(&g_cnt_row[tm]);
    {
        const uint4* src = reinterpret_cast<const uint4*>(p.wp + (size_t)(tm * 128 + (lane >> 3)) * (3 * DM) + w * DM + tn * 64) + (lane & 7);
        float a[8];
#pragma unroll
        for (int i = 0; i < 8; i++) a[i] = 0.f;
#pragma unroll 1
        for (int j = 0; j < 32; j += 8) {
            uint4 t[8];
#pragma unroll
            for (int i = 0; i < 8; i++) t[i] = __ldg(src + (size_t)(j + i) * 4 * (3 * DM / 8));
#pragma unroll
            for (int i = 0; i < 8; i++) {
                a[0] += bf_lo(t[i].x); a[1] += bf_hi(t[i].x); a[2] += bf_lo(t[i].y); a[3] += bf_hi(t[i].y);
                a[4] += bf_lo(t[i].z); a[5] += bf_hi(t[i].z); a[6] += bf_lo(t[i].w); a[7] += bf_hi(t[i].w);
            }
        }
#pragma unroll
        for (int i = 0; i < 8; i++) { a[i] += __shfl_xor_sync(0xffffffffu, a[i], 8); a[i] += __shfl_xor_sync(0xffffffffu, a[i], 16); }
        if (lane < 8) {
            float4* dst = reinterpret_cast<float4*>(g_colsum + tm * (3 * DM) + tn * 192 + w * 64 + lane * 8);
            dst[0] = make_float4(a[0], a[1], a[2], a[3]); dst[1] = make_float4(a[4], a[5], a[6], a[7]);
        }
        __syncwarp();
        if (lane == 0) publish(&g_cnt_col[tn]);
    }
    float* scs = reinterpret_cast<float*>(smem_raw + QkvCfg::AUX_OFF);
    float2* sst = reinterpret_cast<float2*>(smem_raw + QkvCfg::AUX_OFF + 768);
    const int t = w * 32 + lane;
    spin_until(&g_cnt_row[tm], 16 * 3);
    for (int r = t; r < 256; r += 96) sst[r] = __ldcg(&g_rowstat[tm * 256 + r]);
    spin_until(&g_cnt_col[tn], 8 * 3);
    {
        float2 c = make_float2(0.f, 0.f);
#pragma unroll
        for (int i = 0; i < 8; i++) { const float2 u = __ldcg(reinterpret_cast<const float2*>(g_colsum + i * (3 * DM) + tn * 192) + t); c.x += u.x; c.y += u.y; }
        reinterpret_cast<float2*>(scs)[t] = c;
    }
    __syncwarp();
    if (lane == 0) mbar_arrive(s.aux);
}

__global__ void __launch_bounds__(384, 1) qkv_kernel(const __grid_constant__ QkvParams p) {
    extern __shared__ __align__(1024) uint8_t smem_raw[];
    TL(1, 4);
    pdl_launch();
    const int tm = blockIdx.x & 7, tn = blockIdx.x >> 3;
    if (threadIdx.x == 0) { prefetch_map(&p.x); prefetch_map(&p.w); prefetch_map(&p.out); }
    const GemmSmem s = gemm_setup<QkvCfg>(smem_raw);
    const int wgi = __shfl_sync(0xffffffffu, threadIdx.x >> 7, 0);
    if (wgi == 0) {
        reg_dealloc<56>();
        if (threadIdx.x == 0) gemm_producer<QkvCfg>(s, p, tm, tn);
        else if (threadIdx.x >= 32) qkv_aux(p, smem_raw, s, tm, tn, (threadIdx.x >> 5) - 1, threadIdx.x & 31);
    } else {
        reg_alloc<224>();
        const int wg = wgi - 1, warp = (threadIdx.x >> 5) & 3, lane = threadIdx.x & 31;
        float acc[2][96];
        TL(1, 0);
        gemm_mainloop<QkvCfg>(s, wg, acc, 1);
        TL(1, 1);
        mbar_wait(s.aux, 0);
        named_bar(1, 256);
        const float qscale = 0.17677669529663687f * 1.4426950408889634f;
        const float2* scs = reinterpret_cast<const float2*>(smem_raw + QkvCfg::AUX_OFF);
        const float2* sst = reinterpret_cast<const float2*>(smem_raw + QkvCfg::AUX_OFF + 768);
        float mean[4], rstd[4];
#pragma unroll
        for (int i = 0; i < 4; i++) { const float2 t = sst[wg * 128 + (i >> 1) * 64 + warp * 16 + (i & 1) * 8 + (lane >> 2)]; mean[i] = -t.x; rstd[i] = t.y; }
        uint32_t* snorm = reinterpret_cast<uint32_t*>(smem_raw + 6 * 16384) + wg * 32;
#pragma unroll
        for (int sub = 0; sub < 6; sub++) {
            float nrm[4];
#pragma unroll
            for (int m = 0; m < 2; m++) {
                const int arow = wg * 128 + m * 64 + warp * 16 + ((lane >> 3) & 1) * 8 + (lane & 7);
                const float r0 = (sub < 2) ? rstd[2 * m] * qscale : rstd[2 * m], r1 = (sub < 2) ? rstd[2 * m + 1] * qscale : rstd[2 * m + 1];
                float v[16];
#pragma unroll
                for (int j = 0; j < 4; j++) {
                    const float2 cs = scs[(sub * 4 + j) * 4 + (lane & 3)];
                    v[4 * j] = fmaf(mean[2 * m], cs.x, acc[m][sub * 16 + 4 * j]) * r0;
                    v[4 * j + 1] = fmaf(mean[2 * m], cs.y, acc[m][sub * 16 + 4 * j + 1]) * r0;
                    v[4 * j + 2] = fmaf(mean[2 * m + 1], cs.x, acc[m][sub * 16 + 4 * j + 2]) * r1;
                    v[4 * j + 3] = fmaf(mean[2 * m + 1], cs.y, acc[m][sub * 16 + 4 * j + 3]) * r1;
                }
                float n0 = 0.f, n1 = 0.f;
#pragma unroll
                for (int j = 0; j < 4; j++) {
                    n0 = fmaf(v[4 * j], v[4 * j], fmaf(v[4 * j + 1], v[4 * j + 1], n0));
                    n1 = fmaf(v[4 * j + 2], v[4 * j + 2], fmaf(v[4 * j + 3], v[4 * j + 3], n1));
                }
                nrm[2 * m] = n0; nrm[2 * m + 1] = n1;
#pragma unroll
                for (int jp = 0; jp < 2; jp++) {
                    const int chunk = jp * 2 + (lane >> 4);
                    const uint32_t addr = s.base + sub * 16384 + arow * 64 + ((chunk ^ ((arow >> 1) & 3)) << 4);
                    stmatrix_x4(addr, pack_bf16(v[8 * jp], v[8 * jp + 1]), pack_bf16(v[8 * jp + 2], v[8 * jp + 3]),
                                pack_bf16(v[8 * jp + 4], v[8 * jp + 5]), pack_bf16(v[8 * jp + 6], v[8 * jp + 7]));
                }
            }
            const bool odd = lane & 1, up = lane & 2;
            const float s0 = (odd ? nrm[2] : nrm[0]) + __shfl_xor_sync(0xffffffffu, odd ? nrm[0] : nrm[2], 1);
            const float s1 = (odd ? nrm[3] : nrm[1]) + __shfl_xor_sync(0xffffffffu, odd ? nrm[1] : nrm[3], 1);
            const float full = (up ? s1 : s0) + __shfl_xor_sync(0xffffffffu, up ? s0 : s1, 2);
            const uint32_t mx = __reduce_max_sync(0xffffffffu, __float_as_uint(full));
            if (lane == 0) snorm[warp * 8 + sub] = mx;
        }
        TL(1, 5);
        fence_proxy_async();
        named_bar(2 + wg, 128);
        if ((threadIdx.x & 127) == 0) {
#pragma unroll
            for (int sub = 0; sub < 6; sub++)
                tma_st2(&p.out, s.base + sub * 16384 + wg * 8192, 0, (sub >> 1) * (NH * SEQ) + (tn * 2 + (sub & 1)) * SEQ + tm * 256 + wg * 128);
            tma_st_commit();
            tma_st_wait();
        } else if ((threadIdx.x & 127) >= 32 && (threadIdx.x & 127) < 38) {
            const int sub = (threadIdx.x & 127) - 32;
            g_norm[((sub >> 1) * NH + tn * 2 + (sub & 1)) * 16 + tm * 2 + wg] = max(max(snorm[sub], snorm[8 + sub]), max(snorm[16 + sub], snorm[24 + sub]));
        }
        TL(1, 3);
    }
}

struct AttnParams { CUtensorMap kv, kv2; bf16* o; const uint8_t* pf_wo; const uint8_t* pf_w1; };
constexpr int AT_STAGES = 8, AT_STAGE_BYTES = 16384, AT_Q_OFF = AT_STAGES * AT_STAGE_BYTES, AT_ONES_OFF = AT_Q_OFF + 32768, AT_BAR_OFF = AT_ONES_OFF + 1024, AT_SMEM = AT_BAR_OFF + 256;
constexpr int AT_TILES = 32;

__device__ __forceinline__ float ex2_poly(float x) {
    const float magic = 12582912.f;
    const float t = x + magic;
    const float f = x - (t - magic);
    float p = fmaf(f, 0.05550410866f, 0.24022650695f);
    p = fmaf(p, f, 0.69314718056f);
    p = fmaf(p, f, 1.0f);
    return __int_as_float(__float_as_int(p) + (__float_as_int(t) << 23));
}

template <uint32_t MASK> __device__ __forceinline__ float attn_exp(float x, int i) { return ((MASK >> (i & 31)) & 1) ? ex2_poly(x) : ex2(x); }
__device__ __forceinline__ void attn_issue_tile(const AttnParams& p, uint32_t base, uint32_t full0, int g, int head) {
    const int st = g % AT_STAGES, key0 = (g & 15) * 128;
    const uint32_t bar = full0 + 8 * st, dst = base + st * AT_STAGE_BYTES;
    mbar_expect_tx(bar, AT_STAGE_BYTES);
    tma_ld3(dst, &p.kv2, bar, 0, head * SEQ + key0, 1);
}
__device__ __forceinline__ void attn_qk(float (&sacc)[32], uint32_t q_lo, uint32_t k_lo) {
    mma_qk0(sacc, q_lo, k_lo);
    mma_qk1(sacc, q_lo + 2, k_lo + 2, 1);
}
constexpr uint32_t PV_STEP = 64u - (64u << 16);
__device__ __forceinline__ void attn_pv(float (&o)[20], const uint32_t (&pr)[16], uint32_t v_lo, int first) {
#pragma unroll
    for (int kk = 0; kk < 4; kk++)
        mma_pv(o, pr[4 * kk], pr[4 * kk + 1], pr[4 * kk + 2], pr[4 * kk + 3], v_lo + kk * PV_STEP, (kk > 0) || !first);
}
__device__ __forceinline__ void attn_store_o(const float (&o)[20], const AttnParams& p, int head, int row0, int lane) {
    const float r0 = 1.f / o[16], r1 = 1.f / o[18];
    uint32_t* op = reinterpret_cast<uint32_t*>(p.o + (size_t)row0 * DM + head * HD) + (lane & 3);
#pragma unroll
    for (int j = 0; j < 4; j++) {
        op[j * 4] = pack_bf16(o[4 * j] * r0, o[4 * j + 1] * r0);
        op[j * 4 + 8 * (DM / 2)] = pack_bf16(o[4 * j + 2] * r1, o[4 * j + 3] * r1);
    }
}
__device__ __forceinline__ void attn_refill(const AttnParams& p, uint32_t base, uint32_t full0, uint32_t empty0, int g, int head) {
    if (threadIdx.x == 0 && g >= 4 && g + 4 < AT_TILES) {
        const int gp = g - 4;
        mbar_wait(empty0 + 8 * (gp % AT_STAGES), (gp / AT_STAGES) & 1);
        attn_issue_tile(p, base, full0, g + 4, head);
    }
    __syncwarp();
}

__device__ __forceinline__ void attn_fast(const AttnParams& p, uint32_t base, uint32_t full0, uint32_t empty0, int head, int qchunk) {
    const int wg = __shfl_sync(0xffffffffu, threadIdx.x >> 7, 0), warp = (threadIdx.x >> 5) & 3, lane = threadIdx.x & 31;
    const int warp_id = __shfl_sync(0xffffffffu, threadIdx.x >> 5, 0);
    const uint32_t k_lo0 = desc_lo(base, 16), v_lo0 = desc_lo(base + 8192, AT_ONES_OFF - 8192);
    const uint32_t q_lo0 = desc_lo(base + AT_Q_OFF + wg * 64 * 64, 16);
#pragma unroll 1
    for (int pass = 0; pass < 2; pass++) {
    const uint32_t q = q_lo0 + pass * (256 * 64 >> 4);
    float o[20];
#pragma unroll
    for (int i = 0; i < 20; i++) o[i] = 0.f;
#pragma unroll 1
    for (uint32_t par = 0; par < 2; par++) {
        const int rev = pass * 2 + par;
        if (PF_W1 && threadIdx.x < 256) {
            const int l = rev * 256 + threadIdx.x;
            prefetch_line(l < 128 ? p.pf_wo + ((size_t)blockIdx.x * 128 + l) * 128 : p.pf_w1 + ((size_t)blockIdx.x * 896 + (l - 128)) * 128);
        }
#pragma unroll
        for (int st = 0; st < AT_STAGES; st++) {
            if (warp_id == (st & 3) * 5) {
                const int g = rev * AT_STAGES + st;
                if (lane == 0 && g >= 4 && g + 4 < AT_TILES) {
                    mbar_wait(empty0 + 8 * ((st + 4) % AT_STAGES), (st >= 4) ? par : (par ^ 1));
                    attn_issue_tile(p, base, full0, g + 4, head);
                }
                __syncwarp();
            }
            mbar_wait(full0 + 8 * st, par);
            float sc[64];
            uint32_t pa[16], pb[16];
            AT(0);
            wg_fence();
            mma_qkw0(sc, q, k_lo0 + st * (AT_STAGE_BYTES >> 4));
            mma_qkw1(sc, q + 2, k_lo0 + st * (AT_STAGE_BYTES >> 4) + 2, 1);
            wg_commit();
            wg_wait<0>();
            fence_regs(sc);
            AT(1);
            if (lane == 0 && (st > 0 || rev > 0)) mbar_arrive(empty0 + 8 * ((st + AT_STAGES - 1) % AT_STAGES));
#pragma unroll
            for (int i = 0; i < 16; i++) pa[i] = pack_bf16(attn_exp<POLY_MASK>(sc[2 * i], 2 * i), attn_exp<POLY_MASK>(sc[2 * i + 1], 2 * i + 1));
            wg_fence();
            attn_pv(o, pa, v_lo0 + st * 16 * PV_STEP, 0);
            wg_commit();
            AT(2);
#pragma unroll
            for (int i = 0; i < 16; i++) pb[i] = pack_bf16(attn_exp<POLY_MASK_B>(sc[32 + 2 * i], 2 * i), attn_exp<POLY_MASK_B>(sc[32 + 2 * i + 1], 2 * i + 1));
            wg_wait<0>();
            wg_fence();
            attn_pv(o, pb, v_lo0 + (st * 16 + 4) * PV_STEP, 0);
            wg_commit();
            AT(3);
        }
    }
    wg_wait<0>();
    fence_regs(o);
    const int row0 = qchunk * 512 + pass * 256 + wg * 64 + warp * 16 + (lane >> 2);
    attn_store_o(o, p, head, row0, lane);
    }
}

__device__ __forceinline__ void attn_safe(const AttnParams& p, uint32_t base, uint32_t full0, uint32_t empty0, int head, int qchunk) {
    const int wg = __shfl_sync(0xffffffffu, threadIdx.x >> 7, 0), warp = (threadIdx.x >> 5) & 3, lane = threadIdx.x & 31;
    const uint32_t k_lo0 = desc_lo(base, 16), v_lo0 = desc_lo(base + 8192, AT_ONES_OFF - 8192);
#pragma unroll 1
    for (int pass = 0; pass < 2; pass++) {
        const int row0 = qchunk * 512 + pass * 256 + wg * 64 + warp * 16 + (lane >> 2);
        const uint32_t q = desc_lo(base + AT_Q_OFF + (pass * 256 + wg * 64) * 64, 16);
        float o[20];
#pragma unroll
        for (int i = 0; i < 20; i++) o[i] = 0.f;
        float m0 = -INFINITY, m1 = -INFINITY;
#pragma unroll 1
        for (int t = 0; t < 32; t++) {
            const int g = pass * 16 + (t >> 1), half = t & 1;
            const int st = g % AT_STAGES;
            const uint32_t kb = k_lo0 + st * (AT_STAGE_BYTES >> 4), vb = v_lo0 + st * 16 * PV_STEP;
            if (half == 0) { attn_refill(p, base, full0, empty0, g, head); mbar_wait(full0 + 8 * st, (g / AT_STAGES) & 1); }
            float cur[32];
            wg_fence();
            attn_qk(cur, q, kb + half * 256);
            wg_commit();
            wg_wait<0>();
            fence_regs(cur);
            float x0 = cur[0], x1 = cur[2];
#pragma unroll
            for (int i = 0; i < 8; i++) { x0 = fmaxf(x0, fmaxf(cur[4 * i], cur[4 * i + 1])); x1 = fmaxf(x1, fmaxf(cur[4 * i + 2], cur[4 * i + 3])); }
            x0 = fmaxf(x0, __shfl_xor_sync(0xffffffffu, x0, 1)); x1 = fmaxf(x1, __shfl_xor_sync(0xffffffffu, x1, 1));
            x0 = fmaxf(x0, __shfl_xor_sync(0xffffffffu, x0, 2)); x1 = fmaxf(x1, __shfl_xor_sync(0xffffffffu, x1, 2));
            const float n0 = fmaxf(m0, x0), n1 = fmaxf(m1, x1);
            const float a0 = ex2(m0 - n0), a1 = ex2(m1 - n1);
            m0 = n0; m1 = n1;
            uint32_t pr[16];
#pragma unroll
            for (int i = 0; i < 8; i++) {
                pr[2 * i] = pack_bf16(ex2(cur[4 * i] - n0), ex2(cur[4 * i + 1] - n0));
                pr[2 * i + 1] = pack_bf16(ex2(cur[4 * i + 2] - n1), ex2(cur[4 * i + 3] - n1));
            }
#pragma unroll
            for (int i = 0; i < 5; i++) { o[4 * i] *= a0; o[4 * i + 1] *= a0; o[4 * i + 2] *= a1; o[4 * i + 3] *= a1; }
            wg_fence();
            attn_pv(o, pr, vb + half * 4 * PV_STEP, 0);
            wg_commit();
            wg_wait<0>();
            fence_regs(o);
            if (half == 1 && lane == 0) mbar_arrive(empty0 + 8 * st);
        }
        attn_store_o(o, p, head, row0, lane);
    }
}

__global__ void __launch_bounds__(512, 1) attn_kernel(const __grid_constant__ AttnParams p) {
    extern __shared__ __align__(1024) uint8_t smem_raw[];
    TL(2, 4);
    pdl_launch();
    const uint32_t base = smem_u32(smem_raw);
    const uint32_t full0 = base + AT_BAR_OFF, empty0 = full0 + 8 * AT_STAGES;
    const int head = blockIdx.x >> 2, qchunk = blockIdx.x & 3;
    if (threadIdx.x == 0) {
        if (base & 1023) __trap();
        prefetch_map(&p.kv);
        for (int i = 0; i < AT_STAGES; i++) { mbar_init(full0 + 8 * i, 1); mbar_init(empty0 + 8 * i, 16); }
        mbar_init(empty0 + 8 * AT_STAGES, 1);
        fence_barrier_init();
    }
    if (threadIdx.x < 256) reinterpret_cast<uint32_t*>(smem_raw + AT_ONES_OFF)[threadIdx.x] = 0x3F803F80u;
    fence_proxy_async();
    __syncthreads();
    pdl_wait();
    TL(2, 0);
    if (threadIdx.x == 0) {
        const uint32_t qbar = empty0 + 8 * AT_STAGES;
        mbar_expect_tx(qbar, 32768);
        for (int i = 0; i < 4; i++) tma_ld2(base + AT_Q_OFF + i * 8192, &p.kv, qbar, 0, head * SEQ + qchunk * 512 + i * 128);
        for (int g = 0; g < AT_STAGES; g++) attn_issue_tile(p, base, full0, g, head);
    }
    __syncwarp();
    const int l16 = threadIdx.x & 15;
    const float qn = __uint_as_float(__reduce_max_sync(0xffffffffu, __ldcg(&g_norm[head * 16 + l16])));
    const float kn = __uint_as_float(__reduce_max_sync(0xffffffffu, __ldcg(&g_norm[(NH + head) * 16 + l16])));
    const float vn = __uint_as_float(__reduce_max_sync(0xffffffffu, __ldcg(&g_norm[(2 * NH + head) * 16 + l16])));
    if (blockIdx.x == 0 && threadIdx.x >= 64 && threadIdx.x < 64 + 24) {
        const int i = threadIdx.x - 64;
        if (i < 8) g_cnt_row[i] = 0; else g_cnt_col[i - 8] = 0;
    }
    const bool bounded = (qn * kn <= 1.0e4f) && (vn <= 1.0e9f);
    mbar_wait(empty0 + 8 * AT_STAGES, 0);
    if (bounded) attn_fast(p, base, full0, empty0, head, qchunk);
    else attn_safe(p, base, full0, empty0, head, qchunk);
    TL(2, 3);
}

struct ResParams { CUtensorMap a, b, res, out, out2; const bf16* bias; };
template <bool MIX2>
struct ResCfg {
    static constexpr int MB = 1, BN = 128, KSTEPS = MIX2 ? 56 : 16, STAGES = 6, A_BYTES = 16384, B_BYTES = 16384;
    static constexpr int STAGE_BYTES = A_BYTES + B_BYTES, STG_OFF = STAGES * STAGE_BYTES, BAR_OFF = STG_OFF + 32768, SMEM = BAR_OFF + 128;
    static constexpr int AUX_COUNT = 1, PRE = RES_PRE;
    static constexpr bool MC = MIX2 ? MIX2_MC : WO_MC, PAIR = MC || (MIX2 ? MIX2_PAIR : WO_PAIR);
    static constexpr int SYNC_NS = MIX2 ? MIX2_SYNC : 0;
    static __device__ __forceinline__ void prefetch(const ResParams&, int) {}
    static __device__ __forceinline__ void load_w(const ResParams& p, uint32_t sb, uint32_t bar, int k, int tm, int tn) {
        if (MIX2) {
            if (MC) tma_ld3_mc(sb + (tn & 1) * 8192, &p.a, bar, 0, k * 64, tm * 2 + (tn & 1));
            else { tma_ld3(sb, &p.a, bar, 0, k * 64, tm * 2); tma_ld3(sb + 8192, &p.a, bar, 0, k * 64, tm * 2 + 1); }
        } else if (MC) tma_ld3_mc(sb + A_BYTES + (tm & 1) * 8192, &p.b, bar, 0, k * 64, tn * 2 + (tm & 1));
        else { tma_ld3(sb + A_BYTES, &p.b, bar, 0, k * 64, tn * 2); tma_ld3(sb + A_BYTES + 8192, &p.b, bar, 0, k * 64, tn * 2 + 1); }
    }
    static __device__ __forceinline__ void load_x(const ResParams& p, uint32_t sb, uint32_t bar, int k, int tm, int tn) {
        if (MIX2) tma_ld2(sb + A_BYTES, &p.b, bar, k * 64, tn * 128);
        else tma_ld2(sb, &p.a, bar, k * 64, tm * 128);
    }
    static __device__ __forceinline__ void load_aux(const ResParams& p, const GemmSmem& s, int tm, int tn) {
        mbar_expect_tx(s.aux, 32768);
        tma_ld2(s.base + STG_OFF, &p.res, s.aux, tn * 128, tm * 128);
        tma_ld2(s.base + STG_OFF + 16384, &p.res, s.aux, tn * 128 + 64, tm * 128);
    }
    static __device__ __forceinline__ uint32_t desc_a(uint32_t sb, int wg, int m, int kk) {
        return MIX2 ? desc_lo(sb + wg * 8192 + kk * 2048, 8192) : desc_lo(sb + wg * 8192 + kk * 32, 16);
    }
    static __device__ __forceinline__ uint32_t desc_b(uint32_t sb, int kk) {
        return MIX2 ? desc_lo(sb + A_BYTES + kk * 32, 16) : desc_lo(sb + A_BYTES + kk * 2048, 8192);
    }
    static __device__ __forceinline__ void mma(float (&d)[64], uint32_t a, uint32_t b, int sc) {
        if (MIX2) mma_mix2(d, a, b, sc); else mma_wo(d, a, b, sc);
    }
};
template <bool MIX2>
__global__ void __launch_bounds__(384, 1) res_gemm_kernel(const __grid_constant__ ResParams p) {
    using C = ResCfg<MIX2>;
    extern __shared__ __align__(1024) uint8_t smem_raw[];
    TL(MIX2 ? 6 : 3, 4);
    pdl_launch();
    const int tm = (MIX2 && MIX2_MAP) ? blockIdx.x >> 3 : blockIdx.x & 15, tn = (MIX2 && MIX2_MAP) ? blockIdx.x & 7 : blockIdx.x >> 4;
    if (threadIdx.x == 0) { prefetch_map(&p.a); prefetch_map(&p.b); prefetch_map(&p.res); prefetch_map(&p.out); }
    const GemmSmem s = gemm_setup<C>(smem_raw);
    const int wgi = __shfl_sync(0xffffffffu, threadIdx.x >> 7, 0);
    if (wgi == 0) {
        reg_dealloc<40>();
        if (threadIdx.x == 0) gemm_producer<C>(s, p, tm, tn);
    } else {
        reg_alloc<232>();
        const int wg = wgi - 1, warp = (threadIdx.x >> 5) & 3, lane = threadIdx.x & 31;
        float acc[1][64];
        pdl_wait();
        TL(MIX2 ? 6 : 3, 0);
        const int r0 = wg * 64 + warp * 16 + (lane >> 2);
        float b0 = 0.f, b1 = 0.f;
        if (MIX2) { b0 = __bfloat162float(p.bias[tm * 128 + r0]); b1 = __bfloat162float(p.bias[tm * 128 + r0 + 8]); }
        gemm_mainloop<C>(s, wg, acc, MIX2 ? 6 : 3);
        TL(MIX2 ? 6 : 3, 1);
        mbar_wait(s.aux, 0);
        uint8_t* stg = smem_raw + C::STG_OFF;
        uint32_t hp[32];
#pragma unroll
        for (int j = 0; j < 16; j++) {
            const int off = (j >> 3) * 16384 + r0 * 128 + (((j & 7) ^ (r0 & 7)) << 4) + (lane & 3) * 4;
            uint32_t* p0 = reinterpret_cast<uint32_t*>(stg + off);
            uint32_t* p1 = reinterpret_cast<uint32_t*>(stg + off + 8 * 128);
            const uint32_t x0 = *p0, x1 = *p1;
            hp[2 * j] = pack_bf16(acc[0][4 * j] + b0 + bf_lo(x0), acc[0][4 * j + 1] + b0 + bf_hi(x0));
            hp[2 * j + 1] = pack_bf16(acc[0][4 * j + 2] + b1 + bf_lo(x1), acc[0][4 * j + 3] + b1 + bf_hi(x1));
            *p0 = hp[2 * j];
            *p1 = hp[2 * j + 1];
        }
        if (!MIX2) {
            float s0 = 0.f, s1 = 0.f;
#pragma unroll
            for (int j = 0; j < 16; j++) { s0 += bf_lo(hp[2 * j]) + bf_hi(hp[2 * j]); s1 += bf_lo(hp[2 * j + 1]) + bf_hi(hp[2 * j + 1]); }
            s0 += __shfl_xor_sync(0xffffffffu, s0, 1); s1 += __shfl_xor_sync(0xffffffffu, s1, 1);
            s0 += __shfl_xor_sync(0xffffffffu, s0, 2); s1 += __shfl_xor_sync(0xffffffffu, s1, 2);
            const float m0 = s0 * (1.f / 128), m1 = s1 * (1.f / 128);
            float q0 = 0.f, q1 = 0.f;
#pragma unroll
            for (int j = 0; j < 16; j++) {
                const float a = bf_lo(hp[2 * j]) - m0, b = bf_hi(hp[2 * j]) - m0, c = bf_lo(hp[2 * j + 1]) - m1, d = bf_hi(hp[2 * j + 1]) - m1;
                q0 = fmaf(a, a, fmaf(b, b, q0)); q1 = fmaf(c, c, fmaf(d, d, q1));
            }
            q0 += __shfl_xor_sync(0xffffffffu, q0, 1); q1 += __shfl_xor_sync(0xffffffffu, q1, 1);
            q0 += __shfl_xor_sync(0xffffffffu, q0, 2); q1 += __shfl_xor_sync(0xffffffffu, q1, 2);
            if ((lane & 3) == 0) {
                g_hpart[(tm * 128 + r0) * 8 + tn] = make_float2(m0, q0);
                g_hpart[(tm * 128 + r0 + 8) * 8 + tn] = make_float2(m1, q1);
            }
        }
        TL(MIX2 ? 6 : 3, 5);
        fence_proxy_async();
        named_bar(2 + wg, 128);
        if ((threadIdx.x & 127) == 0) {
            if (!MIX2) publish(&g_cnt_ln[tm * 2 + wg]);
            tma_st2(&p.out, s.base + C::STG_OFF + wg * 8192, tn * 128, tm * 128 + wg * 64);
            tma_st2(&p.out, s.base + C::STG_OFF + 16384 + wg * 8192, tn * 128 + 64, tm * 128 + wg * 64);
            tma_st_commit();
            if (!MIX2) spin_until(&g_cnt_ln[tm * 2 + wg], 8);
        }
        if (!MIX2) {
            named_bar(1, 256);
            float mean[2], scale[2];
#pragma unroll
            for (int i = 0; i < 2; i++) {
                const float4 t = __ldcg(reinterpret_cast<const float4*>(g_hpart + (tm * 128 + r0 + 8 * i) * 8) + (lane & 3));
                float m = t.x + t.z;
                m += __shfl_xor_sync(0xffffffffu, m, 1); m += __shfl_xor_sync(0xffffffffu, m, 2);
                m *= 0.125f;
                float q = t.y + t.w + 128.f * ((t.x - m) * (t.x - m) + (t.z - m) * (t.z - m));
                q += __shfl_xor_sync(0xffffffffu, q, 1); q += __shfl_xor_sync(0xffffffffu, q, 2);
                const float var = q * (1.f / DM);
                const float r1 = rsqrtf(var + 1e-5f);
                const float r2 = rsqrtf(var * r1 * r1 + 1e-5f);
                mean[i] = m; scale[i] = r1 * r2;
            }
#pragma unroll
            for (int j = 0; j < 16; j++) {
                const int off = (j >> 3) * 16384 + r0 * 128 + (((j & 7) ^ (r0 & 7)) << 4) + (lane & 3) * 4;
                *reinterpret_cast<uint32_t*>(smem_raw + off) = pack_bf16((bf_lo(hp[2 * j]) - mean[0]) * scale[0], (bf_hi(hp[2 * j]) - mean[0]) * scale[0]);
                *reinterpret_cast<uint32_t*>(smem_raw + off + 8 * 128) = pack_bf16((bf_lo(hp[2 * j + 1]) - mean[1]) * scale[1], (bf_hi(hp[2 * j + 1]) - mean[1]) * scale[1]);
            }
            fence_proxy_async();
            named_bar(2 + wg, 128);
            if ((threadIdx.x & 127) == 0) {
                tma_st2(&p.out2, s.base + wg * 8192, tn * 128, tm * 128 + wg * 64);
                tma_st2(&p.out2, s.base + 16384 + wg * 8192, tn * 128 + 64, tm * 128 + wg * 64);
                tma_st_commit();
            }
        }
        if ((threadIdx.x & 127) == 0) tma_st_wait();
        TL(MIX2 ? 6 : 3, 3);
    }
}

struct Mix1Params { CUtensorMap hn, w1, out; const bf16* bias; const uint8_t* pf; };
struct Mix1Cfg {
    static constexpr int MB = 1, BN = 224, KSTEPS = 32, STAGES = 5, A_BYTES = 16384, B_BYTES = 28672;
    static constexpr int STAGE_BYTES = A_BYTES + B_BYTES, BIAS_OFF = STAGES * STAGE_BYTES, BAR_OFF = BIAS_OFF + 1024, SMEM = BAR_OFF + 128;
    static constexpr int AUX_COUNT = 1, PRE = MIX1_PRE;
    static constexpr bool MC = MIX1_MC, PAIR = MC || MIX1_PAIR;
    static constexpr int SYNC_NS = MIX1_SYNC;
    static __device__ __forceinline__ void load_w(const Mix1Params& p, uint32_t sb, uint32_t bar, int k, int tm, int tn) {
        if (MC) tma_ld3_mc(sb + A_BYTES + (tm & 1) * (B_BYTES / 2), &p.w1, bar, 0, k * 64 + (tm & 1) * 32, tn * 7);
        else { tma_ld3(sb + A_BYTES, &p.w1, bar, 0, k * 64, tn * 7); tma_ld3(sb + A_BYTES + B_BYTES / 2, &p.w1, bar, 0, k * 64 + 32, tn * 7); }
    }
    static __device__ __forceinline__ void prefetch(const Mix1Params& p, int k) {}
    static __device__ __forceinline__ void load_x(const Mix1Params& p, uint32_t sb, uint32_t bar, int k, int tm, int tn) { tma_ld3(sb, &p.hn, bar, 0, k * 64, tm * 2); }
    static __device__ __forceinline__ void load_aux(const Mix1Params&, const GemmSmem&, int, int) {}
    static __device__ __forceinline__ uint32_t desc_a(uint32_t sb, int wg, int m, int kk) { return desc_lo(sb + wg * 8192 + kk * 2048, 8192); }
    static __device__ __forceinline__ uint32_t desc_b(uint32_t sb, int kk) { return desc_lo(sb + A_BYTES + (kk >> 1) * (B_BYTES / 2) + (kk & 1) * 1024, 2048); }
    static __device__ __forceinline__ void mma(float (&d)[112], uint32_t a, uint32_t b, int sc) { mma_mix1(d, a, b, sc); }
};
__global__ void __launch_bounds__(384, 1) mix1_kernel(const __grid_constant__ Mix1Params p) {
    using C = Mix1Cfg;
    extern __shared__ __align__(1024) uint8_t smem_raw[];
    TL(5, 4);
    pdl_launch();
    const int tm = blockIdx.x & 7, tn = blockIdx.x >> 3;
    if (threadIdx.x == 0) { prefetch_map(&p.hn); prefetch_map(&p.w1); prefetch_map(&p.out); }
    float* sbias = reinterpret_cast<float*>(smem_raw + C::BIAS_OFF);
    const GemmSmem s = gemm_setup<C>(smem_raw);
    const int wgi = __shfl_sync(0xffffffffu, threadIdx.x >> 7, 0);
    if (wgi == 0) {
        reg_dealloc<40>();
        if (threadIdx.x == 0) gemm_producer<C>(s, p, tm, tn);
        else if (PF_W2 && threadIdx.x >= 32 && threadIdx.x < 64) {
            pdl_wait();
            __nanosleep(PF_W2_DELAY);
#pragma unroll 1
            for (int i = 0; i < 28; i++) {
                prefetch_line(p.pf + ((size_t)blockIdx.x * 896 + i * 32 + (threadIdx.x & 31)) * 128);
                __nanosleep(300);
            }
        }
    } else {
        reg_alloc<232>();
        const int wg = wgi - 1, warp = (threadIdx.x >> 5) & 3, lane = threadIdx.x & 31;
        float acc[1][112];
        const int bi = threadIdx.x - 128;
        const bf16 bias = p.bias[tn * 224 + (bi < 224 ? bi : 0)];
        pdl_wait();
        if (blockIdx.x == 0 && threadIdx.x >= 128 && threadIdx.x < 160) g_cnt_ln[threadIdx.x - 128] = 0;
        TL(5, 0);
        gemm_mainloop<C>(s, wg, acc, 5);
        TL(5, 1);
        if (bi < 224) sbias[bi] = __bfloat162float(bias);
        named_bar(1, 256);
        const int arow = warp * 16 + ((lane >> 3) & 1) * 8 + (lane & 7);
        const uint32_t stg = s.base + wg * 28672;
#pragma unroll
        for (int jp = 0; jp < 14; jp++) {
            float v[8];
#pragma unroll
            for (int h = 0; h < 2; h++) {
                const float2 bb = *reinterpret_cast<const float2*>(sbias + (jp * 2 + h) * 8 + (lane & 3) * 2);
#pragma unroll
                for (int i = 0; i < 4; i++) {
                    const float x = acc[0][jp * 8 + h * 4 + i] + ((i & 1) ? bb.y : bb.x);
                    const float inner = x * fmaf(x * x, 0.0356774081363f, 0.7978845608029f);
                    const float hx = 0.5f * x;
                    v[h * 4 + i] = fmaf(hx, tanh_fast(inner), hx);
                }
            }
            const int j = jp * 2 + (lane >> 4);
            const uint32_t addr = stg + (j >> 2) * 4096 + arow * 64 + (((j & 3) ^ ((arow >> 1) & 3)) << 4);
            stmatrix_x4(addr, pack_bf16(v[0], v[1]), pack_bf16(v[2], v[3]), pack_bf16(v[4], v[5]), pack_bf16(v[6], v[7]));
        }
        TL(5, 5);
        fence_proxy_async();
        named_bar(2 + wg, 128);
        if ((threadIdx.x & 127) == 0) {
            tma_st3(&p.out, stg, 0, tm * 128 + wg * 64, tn * 7);
            tma_st_commit();
            tma_st_wait();
        }
        TL(5, 3);
    }
}

typedef CUresult (*EncodeFn)(CUtensorMap*, CUtensorMapDataType, cuuint32_t, void*, const cuuint64_t*, const cuuint64_t*, const cuuint32_t*,
                             const cuuint32_t*, CUtensorMapInterleave, CUtensorMapSwizzle, CUtensorMapL2promotion, CUtensorMapFloatOOBfill);
EncodeFn g_encode;

void make_map(CUtensorMap* m, const void* ptr, int rank, const uint64_t* dims, const uint64_t* strides_bytes, const uint32_t* box, CUtensorMapSwizzle swz) {
    cuuint64_t d[5], st[5]; cuuint32_t b[5], es[5];
    for (int i = 0; i < rank; i++) { d[i] = dims[i]; b[i] = box[i]; es[i] = 1; }
    for (int i = 0; i + 1 < rank; i++) st[i] = strides_bytes[i];
    CUresult r = g_encode(m, CU_TENSOR_MAP_DATA_TYPE_BFLOAT16, rank, const_cast<void*>(ptr), d, st, b, es, CU_TENSOR_MAP_INTERLEAVE_NONE, swz,
                          CU_TENSOR_MAP_L2_PROMOTION_L2_128B, CU_TENSOR_MAP_FLOAT_OOB_FILL_NONE);
    if (r != CUDA_SUCCESS) fprintf(stderr, "cuTensorMapEncodeTiled failed: %d\n", (int)r);
}
void map2d(CUtensorMap* m, const void* ptr, uint64_t cols, uint64_t rows, uint32_t bc, uint32_t br, CUtensorMapSwizzle swz) {
    uint64_t dims[2] = {cols, rows}, st[1] = {cols * 2}; uint32_t box[2] = {bc, br};
    make_map(m, ptr, 2, dims, st, box, swz);
}
void map3d(CUtensorMap* m, const void* ptr, uint64_t cols, uint64_t rows, uint32_t inner, uint32_t br, uint32_t nblk, CUtensorMapSwizzle swz) {
    uint64_t dims[3] = {inner, rows, cols / inner}, st[2] = {cols * 2, (uint64_t)inner * 2}; uint32_t box[3] = {inner, br, nblk};
    make_map(m, ptr, 3, dims, st, box, swz);
}

template <class... KArgs, class... Args>
void launch(void (*kern)(KArgs...), int grid, int block, int smem, bool pdl, bool pair, Args&&... args) {
    cudaLaunchConfig_t cfg = {};
    cfg.gridDim = dim3(grid); cfg.blockDim = dim3(block); cfg.dynamicSmemBytes = smem; cfg.stream = 0;
    cudaLaunchAttribute at[2];
    int n = 0;
    if (pdl) { at[n].id = cudaLaunchAttributeProgrammaticStreamSerialization; at[n].val.programmaticStreamSerializationAllowed = 1; n++; }
    if (pair) { at[n].id = cudaLaunchAttributeClusterDimension; at[n].val.clusterDim.x = 2; at[n].val.clusterDim.y = 1; at[n].val.clusterDim.z = 1; n++; }
    cfg.attrs = at; cfg.numAttrs = n;
    cudaError_t e = cudaLaunchKernelEx(&cfg, kern, KArgs(args)...);
    if (e != cudaSuccess) fprintf(stderr, "launch failed: %s\n", cudaGetErrorString(e));
}

struct HostState {
    bool ready;
    const void* key[9];
    QkvParams qkv; AttnParams attn; ResParams wo, mix2; Mix1Params mix1;
    bf16 *qkvp, *o, *h, *hn, *u;
};
HostState g_hs;

}

#define USE_PDL 1

extern "C" void kernel_launch(void* const* d_in, const int* in_sizes, int n_in, void* d_out, int out_size) {
    const bf16* x = (const bf16*)d_in[0];
    const bf16* wqkv = (const bf16*)d_in[1];
    const bf16* wo = (const bf16*)d_in[2];
    const bf16* w1 = (const bf16*)d_in[4];
    const bf16* b1 = (const bf16*)d_in[5];
    const bf16* w2 = (const bf16*)d_in[6];
    const bf16* b2 = (const bf16*)d_in[7];
    HostState& hs = g_hs;
    bool same = hs.ready;
    for (int i = 0; i < 8 && same; i++) same = (hs.key[i] == d_in[i]);
    same = same && hs.key[8] == d_out;
    if (!same) {
        if (!g_encode) {
            void* fn = nullptr; cudaDriverEntryPointQueryResult qr;
            cudaGetDriverEntryPoint("cuTensorMapEncodeTiled", &fn, cudaEnableDefault, &qr);
            g_encode = (EncodeFn)fn;
            cudaFuncSetAttribute(qkv_kernel, cudaFuncAttributeMaxDynamicSharedMemorySize, QkvCfg::SMEM);
            cudaFuncSetAttribute(attn_kernel, cudaFuncAttributeMaxDynamicSharedMemorySize, AT_SMEM);
            cudaFuncSetAttribute(res_gemm_kernel<false>, cudaFuncAttributeMaxDynamicSharedMemorySize, ResCfg<false>::SMEM);
            cudaFuncSetAttribute(res_gemm_kernel<true>, cudaFuncAttributeMaxDynamicSharedMemorySize, ResCfg<true>::SMEM);
            cudaFuncSetAttribute(mix1_kernel, cudaFuncAttributeMaxDynamicSharedMemorySize, Mix1Cfg::SMEM);
        }
        cudaGetSymbolAddress((void**)&hs.qkvp, g_qkv); cudaGetSymbolAddress((void**)&hs.o, g_o);
        cudaGetSymbolAddress((void**)&hs.h, g_h); cudaGetSymbolAddress((void**)&hs.hn, g_hn); cudaGetSymbolAddress((void**)&hs.u, g_u);
        const CUtensorMapSwizzle S128 = CU_TENSOR_MAP_SWIZZLE_128B, S64 = CU_TENSOR_MAP_SWIZZLE_64B;
        map2d(&hs.qkv.x, x, DM, SEQ, 64, 256, S128);
        hs.qkv.xp = x; hs.qkv.wp = wqkv;
        {
            uint64_t dims[4] = {64, (uint64_t)DM, 3, 16}, st[3] = {3 * DM * 2, DM * 2, 128}; uint32_t box[4] = {64, 64, 3, 1};
            make_map(&hs.qkv.w, wqkv, 4, dims, st, box, S128);
        }
        map2d(&hs.qkv.out, hs.qkvp, HD, 3 * NH * SEQ, 32, 128, S64);
        hs.attn.kv = hs.qkv.out; hs.attn.o = hs.o;
        {
            uint64_t dims[3] = {(uint64_t)HD, (uint64_t)NH * SEQ, 3}, st[2] = {HD * 2, (uint64_t)NH * SEQ * HD * 2}; uint32_t box[3] = {32, 128, 2};
            make_map(&hs.attn.kv2, hs.qkvp, 3, dims, st, box, S64);
        }
        map2d(&hs.wo.a, hs.o, DM, SEQ, 64, 128, S128);
        map3d(&hs.wo.b, wo, DM, DM, 64, 64, 1, S128);
        map2d(&hs.wo.res, x, DM, SEQ, 64, 128, S128);
        map2d(&hs.wo.out, hs.h, DM, SEQ, 64, 64, S128);
        map2d(&hs.wo.out2, hs.hn, DM, SEQ, 64, 64, S128);
        hs.wo.bias = nullptr;
        map3d(&hs.mix1.hn, hs.hn, DM, SEQ, 64, 64, 2, S128);
        map3d(&hs.mix1.w1, w1, FF, SEQ, 32, 32, 7, S64);
        hs.mix1.pf = (const uint8_t*)w2;
        hs.attn.pf_wo = (const uint8_t*)wo; hs.attn.pf_w1 = (const uint8_t*)w1;
        map3d(&hs.mix1.out, hs.u, FF, DM, 32, 64, 7, S64);
        hs.mix1.bias = b1;
        map3d(&hs.mix2.a, w2, SEQ, FF, 64, 64, 1, S128);
        map2d(&hs.mix2.b, hs.u, FF, DM, 64, 128, S128);
        map2d(&hs.mix2.res, hs.h, DM, SEQ, 64, 128, S128);
        map2d(&hs.mix2.out, d_out, DM, SEQ, 64, 64, S128);
        hs.mix2.out2 = hs.mix2.out;
        hs.mix2.bias = b2;
        for (int i = 0; i < 8; i++) hs.key[i] = d_in[i];
        hs.key[8] = d_out;
        hs.ready = true;
    }
    const bool pdl = USE_PDL;
    const int G = 128;
    launch(qkv_kernel, G, 384, QkvCfg::SMEM, false, QkvCfg::PAIR, hs.qkv);
    launch(attn_kernel, 128, 512, AT_SMEM, pdl, false, hs.attn);
    launch(res_gemm_kernel<false>, G, 384, ResCfg<false>::SMEM, pdl, ResCfg<false>::PAIR, hs.wo);
    launch(mix1_kernel, G, 384, Mix1Cfg::SMEM, pdl, Mix1Cfg::PAIR, hs.mix1);
    launch(res_gemm_kernel<true>, G, 384, ResCfg<true>::SMEM, pdl, ResCfg<true>::PAIR, hs.mix2);
}
```

```cpp
#include <cuda_runtime.h>
#include <cuda_bf16.h>
#include <cuda.h>
#include <stdint.h>
#include <stdio.h>

typedef __nv_bfloat16 bf16;

namespace {

#define SKEW 0
#define POLY_MASK_B POLY_MASK
#define POLY_MASK 0x12492449u
#define MIX1_MC true
#define MIX2_MC false
#define WO_MC false
#define MIX1_PAIR false
#define MIX2_PAIR true
#define WO_PAIR true
#define MIX2_MAP 1
#define WO_MAP 1
#define WO_SYNC 0
#define MIX1_SYNC 0
#define MIX2_SYNC 0
#define MIX1_PRE 2
#define WO_PRE 1
#define MIX2_PRE 1
#define PF_W1 4
#define PF_W2_DELAY 10000
#define WO_INIT true
#define MIX2_INIT true
#define O_DIRECT 1
#define PAIR_POLY 1
#define PMASK_A 0x4924
#define PMASK_B PMASK_A
#define PF_X 0
#define PF_REV 3
#define PF_W2 2
constexpr int SEQ = 2048, DM = 1024, NH = 32, HD = 32, FF = 3584;

__device__ __align__(1024) bf16 g_qkv[3 * NH * SEQ * HD];
__device__ __align__(1024) bf16 g_o[SEQ * DM];
__device__ __align__(1024) bf16 g_hn[SEQ * DM];
__device__ __align__(1024) bf16 g_u[DM * FF];
__device__ uint32_t g_norm[3 * NH * 64];
__device__ float2 g_rowstat[SEQ];
__device__ float g_colsum[8 * 3 * DM];
__device__ float2 g_rowln[SEQ];
__device__ __align__(16) unsigned long long g_hpart[SEQ * 8];
__device__ uint32_t g_cnt_row[8], g_cnt_col[16];

#define TL(kern, slot)
#define AT(slot)

__device__ __forceinline__ uint32_t smem_u32(const void* p) { return (uint32_t)__cvta_generic_to_shared(p); }
__device__ __forceinline__ void mbar_init(uint32_t bar, uint32_t cnt) { asm volatile("mbarrier.init.shared::cta.b64 [%0], %1;" :: "r"(bar), "r"(cnt) : "memory"); }
__device__ __forceinline__ void mbar_expect_tx(uint32_t bar, uint32_t bytes) { asm volatile("mbarrier.arrive.expect_tx.shared::cta.b64 _, [%0], %1;" :: "r"(bar), "r"(bytes) : "memory"); }
__device__ __forceinline__ void mbar_arrive(uint32_t bar) { asm volatile("mbarrier.arrive.shared::cta.b64 _, [%0];" :: "r"(bar) : "memory"); }
__device__ __forceinline__ void mbar_wait(uint32_t bar, uint32_t parity) {
    asm volatile("{\n.reg .pred p;\nWAIT_%=:\nmbarrier.try_wait.parity.shared::cta.b64 p, [%0], %1;\n@p bra DONE_%=;\nbra WAIT_%=;\nDONE_%=:\n}" :: "r"(bar), "r"(parity) : "memory");
}
__device__ __forceinline__ void fence_barrier_init() { asm volatile("fence.mbarrier_init.release.cluster;" ::: "memory"); }
__device__ __forceinline__ void fence_proxy_async() { asm volatile("fence.proxy.async.shared::cta;" ::: "memory"); }
__device__ __forceinline__ void pdl_launch() { asm volatile("griddepcontrol.launch_dependents;" ::: "memory"); }
__device__ __forceinline__ void pdl_wait() { asm volatile("griddepcontrol.wait;" ::: "memory"); }
__device__ __forceinline__ void named_bar(int id, int n) { asm volatile("bar.sync %0, %1;" :: "r"(id), "r"(n) : "memory"); }
__device__ __forceinline__ void named_arrive(int id, int n) { asm volatile("bar.arrive %0, %1;" :: "r"(id), "r"(n) : "memory"); }
__device__ __forceinline__ void hand_over(int id) { fence_proxy_async(); named_arrive(id, 160); }
__device__ __forceinline__ void prefetch_map(const CUtensorMap* m) { asm volatile("prefetch.tensormap [%0];" :: "l"(m) : "memory"); }

__device__ __forceinline__ void tma_ld2(uint32_t dst, const CUtensorMap* m, uint32_t bar, int c0, int c1) {
    asm volatile("cp.async.bulk.tensor.2d.shared::cluster.global.mbarrier::complete_tx::bytes [%0], [%1, {%3, %4}], [%2];"
                 :: "r"(dst), "l"(m), "r"(bar), "r"(c0), "r"(c1) : "memory");
}
__device__ __forceinline__ void tma_ld3(uint32_t dst, const CUtensorMap* m, uint32_t bar, int c0, int c1, int c2) {
    asm volatile("cp.async.bulk.tensor.3d.shared::cluster.global.mbarrier::complete_tx::bytes [%0], [%1, {%3, %4, %5}], [%2];"
                 :: "r"(dst), "l"(m), "r"(bar), "r"(c0), "r"(c1), "r"(c2) : "memory");
}
__device__ __forceinline__ void tma_ld4(uint32_t dst, const CUtensorMap* m, uint32_t bar, int c0, int c1, int c2, int c3) {
    asm volatile("cp.async.bulk.tensor.4d.shared::cluster.global.mbarrier::complete_tx::bytes [%0], [%1, {%3, %4, %5, %6}], [%2];"
                 :: "r"(dst), "l"(m), "r"(bar), "r"(c0), "r"(c1), "r"(c2), "r"(c3) : "memory");
}
__device__ __forceinline__ void tma_ld3_mc(uint32_t dst, const CUtensorMap* m, uint32_t bar, int c0, int c1, int c2) {
    asm volatile("cp.async.bulk.tensor.3d.shared::cluster.global.mbarrier::complete_tx::bytes.multicast::cluster [%0], [%1, {%3, %4, %5}], [%2], %6;"
                 :: "r"(dst), "l"(m), "r"(bar), "r"(c0), "r"(c1), "r"(c2), "h"((uint16_t)3) : "memory");
}
__device__ __forceinline__ void tma_ld2_mc(uint32_t dst, const CUtensorMap* m, uint32_t bar, int c0, int c1) {
    asm volatile("cp.async.bulk.tensor.2d.shared::cluster.global.mbarrier::complete_tx::bytes.multicast::cluster [%0], [%1, {%3, %4}], [%2], %5;"
                 :: "r"(dst), "l"(m), "r"(bar), "r"(c0), "r"(c1), "h"((uint16_t)3) : "memory");
}
__device__ __forceinline__ void prefetch_line(const void* p) { asm volatile("prefetch.global.L2 [%0];" :: "l"(p)); }
__device__ __forceinline__ void l2_prefetch(const void* p, uint32_t bytes) { asm volatile("cp.async.bulk.prefetch.L2.global [%0], %1;" :: "l"(p), "r"(bytes) : "memory"); }
__device__ __forceinline__ uint32_t mapa(uint32_t addr, uint32_t cta) { uint32_t r; asm("mapa.shared::cluster.u32 %0, %1, %2;" : "=r"(r) : "r"(addr), "r"(cta)); return r; }
__device__ __forceinline__ void mbar_arrive_cluster(uint32_t bar) { asm volatile("mbarrier.arrive.shared::cluster.b64 _, [%0];" :: "r"(bar) : "memory"); }
__device__ __forceinline__ void cluster_arrive() { asm volatile("barrier.cluster.arrive.relaxed.aligned;" ::: "memory"); }
__device__ __forceinline__ void cluster_wait() { asm volatile("barrier.cluster.wait.aligned;" ::: "memory"); }
__device__ __forceinline__ void tma_st2(const CUtensorMap* m, uint32_t src, int c0, int c1) {
    asm volatile("cp.async.bulk.tensor.2d.global.shared::cta.bulk_group [%0, {%2, %3}], [%1];" :: "l"(m), "r"(src), "r"(c0), "r"(c1) : "memory");
}
__device__ __forceinline__ void tma_st3(const CUtensorMap* m, uint32_t src, int c0, int c1, int c2) {
    asm volatile("cp.async.bulk.tensor.3d.global.shared::cta.bulk_group [%0, {%2, %3, %4}], [%1];" :: "l"(m), "r"(src), "r"(c0), "r"(c1), "r"(c2) : "memory");
}
__device__ __forceinline__ void tma_st_commit() { asm volatile("cp.async.bulk.commit_group;" ::: "memory"); }
__device__ __forceinline__ void tma_st_wait() { asm volatile("cp.async.bulk.wait_group.read 0;" ::: "memory"); }

__device__ __forceinline__ void wg_fence() { asm volatile("wgmma.fence.sync.aligned;" ::: "memory"); }
__device__ __forceinline__ void wg_commit() { asm volatile("wgmma.commit_group.sync.aligned;" ::: "memory"); }
template <int N> __device__ __forceinline__ void wg_wait() { asm volatile("wgmma.wait_group.sync.aligned %0;" :: "n"(N) : "memory"); }
template <int R> __device__ __forceinline__ void reg_alloc() { asm volatile("setmaxnreg.inc.sync.aligned.u32 %0;" :: "n"(R)); }
template <int R> __device__ __forceinline__ void reg_dealloc() { asm volatile("setmaxnreg.dec.sync.aligned.u32 %0;" :: "n"(R)); }
template <int N> __device__ __forceinline__ void fence_regs(float (&d)[N]) {
#pragma unroll
    for (int i = 0; i < N; i++) asm volatile("" : "+f"(d[i]) :: "memory");
}

__device__ __forceinline__ uint32_t desc_lo(uint32_t addr, uint32_t lbo) { return ((addr & 0x3FFFFu) >> 4) | ((lbo >> 4) << 16); }
__device__ __forceinline__ uint32_t pack_bf16(float lo, float hi) { uint32_t d; asm("cvt.rn.bf16x2.f32 %0, %1, %2;" : "=r"(d) : "f"(hi), "f"(lo)); return d; }
__device__ __forceinline__ float bf_lo(uint32_t v) { return __uint_as_float(v << 16); }
__device__ __forceinline__ float bf_hi(uint32_t v) { return __uint_as_float(v & 0xFFFF0000u); }
__device__ __forceinline__ void stmatrix_x4(uint32_t addr, uint32_t r0, uint32_t r1, uint32_t r2, uint32_t r3) {
    asm volatile("stmatrix.sync.aligned.m8n8.x4.shared.b16 [%0], {%1, %2, %3, %4};" :: "r"(addr), "r"(r0), "r"(r1), "r"(r2), "r"(r3) : "memory");
}
__device__ __forceinline__ void ldmatrix_x4(uint32_t addr, uint32_t (&r)[4]) {
    asm volatile("ldmatrix.sync.aligned.m8n8.x4.shared.b16 {%0, %1, %2, %3}, [%4];" : "=r"(r[0]), "=r"(r[1]), "=r"(r[2]), "=r"(r[3]) : "r"(addr) : "memory");
}
__device__ __forceinline__ float ex2(float x) { float y; asm("ex2.approx.ftz.f32 %0, %1;" : "=f"(y) : "f"(x)); return y; }
__device__ __forceinline__ float tanh_fast(float x) { float y; asm("tanh.approx.f32 %0, %1;" : "=f"(y) : "f"(x)); return y; }

__device__ __forceinline__ void mma_qkv(float (&d)[96], uint32_t alo, uint32_t blo, int scale_d) {
    asm volatile("{\n.reg .pred p;\n.reg .b64 da, db;\nsetp.ne.b32 p, %98, 0;\nmov.b64 da, {%96, 0x40000040};\nmov.b64 db, {%97, 0x40000040};\n"
        "wgmma.mma_async.sync.aligned.m64n192k16.f32.bf16.bf16 {"
        "%0, %1, %2, %3, %4, %5, %6, %7, %8, %9, %10, %11, %12, %13, %14, %15, %16, %17, %18, %19, %20, %21, %22, %23, %24, %25, %26, %27, %28, %29, %30, %31,  "
        "%32, %33, %34, %35, %36, %37, %38, %39, %40, %41, %42, %43, %44, %45, %46, %47, %48, %49, %50, %51, %52, %53, %54, %55, %56, %57, %58, %59, %60, %61,  "
        "%62, %63, %64, %65, %66, %67, %68, %69, %70, %71, %72, %73, %74, %75, %76, %77, %78, %79, %80, %81, %82, %83, %84, %85, %86, %87, %88, %89, %90, %91,  "
        "%92, %93, %94, %95 "
        "}, da, db, p, 1, 1, 0, 1;\n}\n"
        : "+f"(d[0]), "+f"(d[1]), "+f"(d[2]), "+f"(d[3]), "+f"(d[4]), "+f"(d[5]), "+f"(d[6]), "+f"(d[7]), "+f"(d[8]), "+f"(d[9]), "+f"(d[10]), "+f"(d[11]),
          "+f"(d[12]), "+f"(d[13]), "+f"(d[14]), "+f"(d[15]), "+f"(d[16]), "+f"(d[17]), "+f"(d[18]), "+f"(d[19]), "+f"(d[20]), "+f"(d[21]), "+f"(d[22]),
          "+f"(d[23]), "+f"(d[24]), "+f"(d[25]), "+f"(d[26]), "+f"(d[27]), "+f"(d[28]), "+f"(d[29]), "+f"(d[30]), "+f"(d[31]), "+f"(d[32]), "+f"(d[33]),
          "+f"(d[34]), "+f"(d[35]), "+f"(d[36]), "+f"(d[37]), "+f"(d[38]), "+f"(d[39]), "+f"(d[40]), "+f"(d[41]), "+f"(d[42]), "+f"(d[43]), "+f"(d[44]),
          "+f"(d[45]), "+f"(d[46]), "+f"(d[47]), "+f"(d[48]), "+f"(d[49]), "+f"(d[50]), "+f"(d[51]), "+f"(d[52]), "+f"(d[53]), "+f"(d[54]), "+f"(d[55]),
          "+f"(d[56]), "+f"(d[57]), "+f"(d[58]), "+f"(d[59]), "+f"(d[60]), "+f"(d[61]), "+f"(d[62]), "+f"(d[63]), "+f"(d[64]), "+f"(d[65]), "+f"(d[66]),
          "+f"(d[67]), "+f"(d[68]), "+f"(d[69]), "+f"(d[70]), "+f"(d[71]), "+f"(d[72]), "+f"(d[73]), "+f"(d[74]), "+f"(d[75]), "+f"(d[76]), "+f"(d[77]),
          "+f"(d[78]), "+f"(d[79]), "+f"(d[80]), "+f"(d[81]), "+f"(d[82]), "+f"(d[83]), "+f"(d[84]), "+f"(d[85]), "+f"(d[86]), "+f"(d[87]), "+f"(d[88]),
          "+f"(d[89]), "+f"(d[90]), "+f"(d[91]), "+f"(d[92]), "+f"(d[93]), "+f"(d[94]), "+f"(d[95])
        : "r"(alo), "r"(blo), "r"(scale_d));
}
__device__ __forceinline__ void mma_wo(float (&d)[64], uint32_t alo, uint32_t blo, int scale_d) {
    asm volatile("{\n.reg .pred p;\n.reg .b64 da, db;\nsetp.ne.b32 p, %66, 0;\nmov.b64 da, {%64, 0x40000040};\nmov.b64 db, {%65, 0x40000040};\n"
        "wgmma.mma_async.sync.aligned.m64n128k16.f32.bf16.bf16 {"
        "%0, %1, %2, %3, %4, %5, %6, %7, %8, %9, %10, %11, %12, %13, %14, %15, %16, %17, %18, %19, %20, %21, %22, %23, %24, %25, %26, %27, %28, %29, %30, %31,  "
        "%32, %33, %34, %35, %36, %37, %38, %39, %40, %41, %42, %43, %44, %45, %46, %47, %48, %49, %50, %51, %52, %53, %54, %55, %56, %57, %58, %59, %60, %61,  "
        "%62, %63 "
        "}, da, db, p, 1, 1, 0, 1;\n}\n"
        : "+f"(d[0]), "+f"(d[1]), "+f"(d[2]), "+f"(d[3]), "+f"(d[4]), "+f"(d[5]), "+f"(d[6]), "+f"(d[7]), "+f"(d[8]), "+f"(d[9]), "+f"(d[10]), "+f"(d[11]),
          "+f"(d[12]), "+f"(d[13]), "+f"(d[14]), "+f"(d[15]), "+f"(d[16]), "+f"(d[17]), "+f"(d[18]), "+f"(d[19]), "+f"(d[20]), "+f"(d[21]), "+f"(d[22]),
          "+f"(d[23]), "+f"(d[24]), "+f"(d[25]), "+f"(d[26]), "+f"(d[27]), "+f"(d[28]), "+f"(d[29]), "+f"(d[30]), "+f"(d[31]), "+f"(d[32]), "+f"(d[33]),
          "+f"(d[34]), "+f"(d[35]), "+f"(d[36]), "+f"(d[37]), "+f"(d[38]), "+f"(d[39]), "+f"(d[40]), "+f"(d[41]), "+f"(d[42]), "+f"(d[43]), "+f"(d[44]),
          "+f"(d[45]), "+f"(d[46]), "+f"(d[47]), "+f"(d[48]), "+f"(d[49]), "+f"(d[50]), "+f"(d[51]), "+f"(d[52]), "+f"(d[53]), "+f"(d[54]), "+f"(d[55]),
          "+f"(d[56]), "+f"(d[57]), "+f"(d[58]), "+f"(d[59]), "+f"(d[60]), "+f"(d[61]), "+f"(d[62]), "+f"(d[63])
        : "r"(alo), "r"(blo), "r"(scale_d));
}
__device__ __forceinline__ void mma_mix2(float (&d)[64], uint32_t alo, uint32_t blo, int scale_d) {
    asm volatile("{\n.reg .pred p;\n.reg .b64 da, db;\nsetp.ne.b32 p, %66, 0;\nmov.b64 da, {%64, 0x40000040};\nmov.b64 db, {%65, 0x40000040};\n"
        "wgmma.mma_async.sync.aligned.m64n128k16.f32.bf16.bf16 {"
        "%0, %1, %2, %3, %4, %5, %6, %7, %8, %9, %10, %11, %12, %13, %14, %15, %16, %17, %18, %19, %20, %21, %22, %23, %24, %25, %26, %27, %28, %29, %30, %31,  "
        "%32, %33, %34, %35, %36, %37, %38, %39, %40, %41, %42, %43, %44, %45, %46, %47, %48, %49, %50, %51, %52, %53, %54, %55, %56, %57, %58, %59, %60, %61,  "
        "%62, %63 "
        "}, da, db, p, 1, 1, 1, 0;\n}\n"
        : "+f"(d[0]), "+f"(d[1]), "+f"(d[2]), "+f"(d[3]), "+f"(d[4]), "+f"(d[5]), "+f"(d[6]), "+f"(d[7]), "+f"(d[8]), "+f"(d[9]), "+f"(d[10]), "+f"(d[11]),
          "+f"(d[12]), "+f"(d[13]), "+f"(d[14]), "+f"(d[15]), "+f"(d[16]), "+f"(d[17]), "+f"(d[18]), "+f"(d[19]), "+f"(d[20]), "+f"(d[21]), "+f"(d[22]),
          "+f"(d[23]), "+f"(d[24]), "+f"(d[25]), "+f"(d[26]), "+f"(d[27]), "+f"(d[28]), "+f"(d[29]), "+f"(d[30]), "+f"(d[31]), "+f"(d[32]), "+f"(d[33]),
          "+f"(d[34]), "+f"(d[35]), "+f"(d[36]), "+f"(d[37]), "+f"(d[38]), "+f"(d[39]), "+f"(d[40]), "+f"(d[41]), "+f"(d[42]), "+f"(d[43]), "+f"(d[44]),
          "+f"(d[45]), "+f"(d[46]), "+f"(d[47]), "+f"(d[48]), "+f"(d[49]), "+f"(d[50]), "+f"(d[51]), "+f"(d[52]), "+f"(d[53]), "+f"(d[54]), "+f"(d[55]),
          "+f"(d[56]), "+f"(d[57]), "+f"(d[58]), "+f"(d[59]), "+f"(d[60]), "+f"(d[61]), "+f"(d[62]), "+f"(d[63])
        : "r"(alo), "r"(blo), "r"(scale_d));
}
__device__ __forceinline__ void mma_mix1(float (&d)[112], uint32_t alo, uint32_t blo, int scale_d) {
    asm volatile("{\n.reg .pred p;\n.reg .b64 da, db;\nsetp.ne.b32 p, %114, 0;\nmov.b64 da, {%112, 0x40000040};\nmov.b64 db, {%113, 0x80000020};\n"
        "wgmma.mma_async.sync.aligned.m64n224k16.f32.bf16.bf16 {"
        "%0, %1, %2, %3, %4, %5, %6, %7, %8, %9, %10, %11, %12, %13, %14, %15, %16, %17, %18, %19, %20, %21, %22, %23, %24, %25, %26, %27, %28, %29, %30, %31,  "
        "%32, %33, %34, %35, %36, %37, %38, %39, %40, %41, %42, %43, %44, %45, %46, %47, %48, %49, %50, %51, %52, %53, %54, %55, %56, %57, %58, %59, %60, %61,  "
        "%62, %63, %64, %65, %66, %67, %68, %69, %70, %71, %72, %73, %74, %75, %76, %77, %78, %79, %80, %81, %82, %83, %84, %85, %86, %87, %88, %89, %90, %91,  "
        "%92, %93, %94, %95, %96, %97, %98, %99, %100, %101, %102, %103, %104, %105, %106, %107, %108, %109, %110, %111 "
        "}, da, db, p, 1, 1, 1, 1;\n}\n"
        : "+f"(d[0]), "+f"(d[1]), "+f"(d[2]), "+f"(d[3]), "+f"(d[4]), "+f"(d[5]), "+f"(d[6]), "+f"(d[7]), "+f"(d[8]), "+f"(d[9]), "+f"(d[10]), "+f"(d[11]),
          "+f"(d[12]), "+f"(d[13]), "+f"(d[14]), "+f"(d[15]), "+f"(d[16]), "+f"(d[17]), "+f"(d[18]), "+f"(d[19]), "+f"(d[20]), "+f"(d[21]), "+f"(d[22]),
          "+f"(d[23]), "+f"(d[24]), "+f"(d[25]), "+f"(d[26]), "+f"(d[27]), "+f"(d[28]), "+f"(d[29]), "+f"(d[30]), "+f"(d[31]), "+f"(d[32]), "+f"(d[33]),
          "+f"(d[34]), "+f"(d[35]), "+f"(d[36]), "+f"(d[37]), "+f"(d[38]), "+f"(d[39]), "+f"(d[40]), "+f"(d[41]), "+f"(d[42]), "+f"(d[43]), "+f"(d[44]),
          "+f"(d[45]), "+f"(d[46]), "+f"(d[47]), "+f"(d[48]), "+f"(d[49]), "+f"(d[50]), "+f"(d[51]), "+f"(d[52]), "+f"(d[53]), "+f"(d[54]), "+f"(d[55]),
          "+f"(d[56]), "+f"(d[57]), "+f"(d[58]), "+f"(d[59]), "+f"(d[60]), "+f"(d[61]), "+f"(d[62]), "+f"(d[63]), "+f"(d[64]), "+f"(d[65]), "+f"(d[66]),
          "+f"(d[67]), "+f"(d[68]), "+f"(d[69]), "+f"(d[70]), "+f"(d[71]), "+f"(d[72]), "+f"(d[73]), "+f"(d[74]), "+f"(d[75]), "+f"(d[76]), "+f"(d[77]),
          "+f"(d[78]), "+f"(d[79]), "+f"(d[80]), "+f"(d[81]), "+f"(d[82]), "+f"(d[83]), "+f"(d[84]), "+f"(d[85]), "+f"(d[86]), "+f"(d[87]), "+f"(d[88]),
          "+f"(d[89]), "+f"(d[90]), "+f"(d[91]), "+f"(d[92]), "+f"(d[93]), "+f"(d[94]), "+f"(d[95]), "+f"(d[96]), "+f"(d[97]), "+f"(d[98]), "+f"(d[99]),
          "+f"(d[100]), "+f"(d[101]), "+f"(d[102]), "+f"(d[103]), "+f"(d[104]), "+f"(d[105]), "+f"(d[106]), "+f"(d[107]), "+f"(d[108]), "+f"(d[109]),
          "+f"(d[110]), "+f"(d[111])
        : "r"(alo), "r"(blo), "r"(scale_d));
}
__device__ __forceinline__ void mma_qk0(float (&d)[32], uint32_t alo, uint32_t blo) {
    asm volatile("{\n.reg .pred p;\n.reg .b64 da, db;\nsetp.ne.b32 p, 0, 0;\nmov.b64 da, {%32, 0x80000020};\nmov.b64 db, {%33, 0x80000020};\n"
        "wgmma.mma_async.sync.aligned.m64n64k16.f32.bf16.bf16 {"
        "%0, %1, %2, %3, %4, %5, %6, %7, %8, %9, %10, %11, %12, %13, %14, %15, %16, %17, %18, %19, %20, %21, %22, %23, %24, %25, %26, %27, %28, %29, %30, %31 "
        "}, da, db, p, 1, 1, 0, 0;\n}\n"
        : "=f"(d[0]), "=f"(d[1]), "=f"(d[2]), "=f"(d[3]), "=f"(d[4]), "=f"(d[5]), "=f"(d[6]), "=f"(d[7]), "=f"(d[8]), "=f"(d[9]), "=f"(d[10]), "=f"(d[11]),
          "=f"(d[12]), "=f"(d[13]), "=f"(d[14]), "=f"(d[15]), "=f"(d[16]), "=f"(d[17]), "=f"(d[18]), "=f"(d[19]), "=f"(d[20]), "=f"(d[21]), "=f"(d[22]),
          "=f"(d[23]), "=f"(d[24]), "=f"(d[25]), "=f"(d[26]), "=f"(d[27]), "=f"(d[28]), "=f"(d[29]), "=f"(d[30]), "=f"(d[31])
        : "r"(alo), "r"(blo));
}
__device__ __forceinline__ void mma_qk1(float (&d)[32], uint32_t alo, uint32_t blo, int scale_d) {
    asm volatile("{\n.reg .pred p;\n.reg .b64 da, db;\nsetp.ne.b32 p, %34, 0;\nmov.b64 da, {%32, 0x80000020};\nmov.b64 db, {%33, 0x80000020};\n"
        "wgmma.mma_async.sync.aligned.m64n64k16.f32.bf16.bf16 {"
        "%0, %1, %2, %3, %4, %5, %6, %7, %8, %9, %10, %11, %12, %13, %14, %15, %16, %17, %18, %19, %20, %21, %22, %23, %24, %25, %26, %27, %28, %29, %30, %31 "
        "}, da, db, p, 1, 1, 0, 0;\n}\n"
        : "+f"(d[0]), "+f"(d[1]), "+f"(d[2]), "+f"(d[3]), "+f"(d[4]), "+f"(d[5]), "+f"(d[6]), "+f"(d[7]), "+f"(d[8]), "+f"(d[9]), "+f"(d[10]), "+f"(d[11]),
          "+f"(d[12]), "+f"(d[13]), "+f"(d[14]), "+f"(d[15]), "+f"(d[16]), "+f"(d[17]), "+f"(d[18]), "+f"(d[19]), "+f"(d[20]), "+f"(d[21]), "+f"(d[22]),
          "+f"(d[23]), "+f"(d[24]), "+f"(d[25]), "+f"(d[26]), "+f"(d[27]), "+f"(d[28]), "+f"(d[29]), "+f"(d[30]), "+f"(d[31])
        : "r"(alo), "r"(blo), "r"(scale_d));
}
__device__ __forceinline__ void mma_qkw0(float (&d)[64], uint32_t alo, uint32_t blo) {
    asm volatile("{\n.reg .pred p;\n.reg .b64 da, db;\nsetp.ne.b32 p, 0, 0;\nmov.b64 da, {%64, 0x80000020};\nmov.b64 db, {%65, 0x80000020};\n"
        "wgmma.mma_async.sync.aligned.m64n128k16.f32.bf16.bf16 {"
        "%0, %1, %2, %3, %4, %5, %6, %7, %8, %9, %10, %11, %12, %13, %14, %15, %16, %17, %18, %19, %20, %21, %22, %23, %24, %25, %26, %27, %28, %29, %30, %31,  "
        "%32, %33, %34, %35, %36, %37, %38, %39, %40, %41, %42, %43, %44, %45, %46, %47, %48, %49, %50, %51, %52, %53, %54, %55, %56, %57, %58, %59, %60, %61,  "
        "%62, %63 "
        "}, da, db, p, 1, 1, 0, 0;\n}\n"
        : "=f"(d[0]), "=f"(d[1]), "=f"(d[2]), "=f"(d[3]), "=f"(d[4]), "=f"(d[5]), "=f"(d[6]), "=f"(d[7]), "=f"(d[8]), "=f"(d[9]), "=f"(d[10]), "=f"(d[11]),
          "=f"(d[12]), "=f"(d[13]), "=f"(d[14]), "=f"(d[15]), "=f"(d[16]), "=f"(d[17]), "=f"(d[18]), "=f"(d[19]), "=f"(d[20]), "=f"(d[21]), "=f"(d[22]),
          "=f"(d[23]), "=f"(d[24]), "=f"(d[25]), "=f"(d[26]), "=f"(d[27]), "=f"(d[28]), "=f"(d[29]), "=f"(d[30]), "=f"(d[31]), "=f"(d[32]), "=f"(d[33]),
          "=f"(d[34]), "=f"(d[35]), "=f"(d[36]), "=f"(d[37]), "=f"(d[38]), "=f"(d[39]), "=f"(d[40]), "=f"(d[41]), "=f"(d[42]), "=f"(d[43]), "=f"(d[44]),
          "=f"(d[45]), "=f"(d[46]), "=f"(d[47]), "=f"(d[48]), "=f"(d[49]), "=f"(d[50]), "=f"(d[51]), "=f"(d[52]), "=f"(d[53]), "=f"(d[54]), "=f"(d[55]),
          "=f"(d[56]), "=f"(d[57]), "=f"(d[58]), "=f"(d[59]), "=f"(d[60]), "=f"(d[61]), "=f"(d[62]), "=f"(d[63])
        : "r"(alo), "r"(blo));
}
__device__ __forceinline__ void mma_qkw1(float (&d)[64], uint32_t alo, uint32_t blo, int scale_d) {
    asm volatile("{\n.reg .pred p;\n.reg .b64 da, db;\nsetp.ne.b32 p, %66, 0;\nmov.b64 da, {%64, 0x80000020};\nmov.b64 db, {%65, 0x80000020};\n"
        "wgmma.mma_async.sync.aligned.m64n128k16.f32.bf16.bf16 {"
        "%0, %1, %2, %3, %4, %5, %6, %7, %8, %9, %10, %11, %12, %13, %14, %15, %16, %17, %18, %19, %20, %21, %22, %23, %24, %25, %26, %27, %28, %29, %30, %31,  "
        "%32, %33, %34, %35, %36, %37, %38, %39, %40, %41, %42, %43, %44, %45, %46, %47, %48, %49, %50, %51, %52, %53, %54, %55, %56, %57, %58, %59, %60, %61,  "
        "%62, %63 "
        "}, da, db, p, 1, 1, 0, 0;\n}\n"
        : "+f"(d[0]), "+f"(d[1]), "+f"(d[2]), "+f"(d[3]), "+f"(d[4]), "+f"(d[5]), "+f"(d[6]), "+f"(d[7]), "+f"(d[8]), "+f"(d[9]), "+f"(d[10]), "+f"(d[11]),
          "+f"(d[12]), "+f"(d[13]), "+f"(d[14]), "+f"(d[15]), "+f"(d[16]), "+f"(d[17]), "+f"(d[18]), "+f"(d[19]), "+f"(d[20]), "+f"(d[21]), "+f"(d[22]),
          "+f"(d[23]), "+f"(d[24]), "+f"(d[25]), "+f"(d[26]), "+f"(d[27]), "+f"(d[28]), "+f"(d[29]), "+f"(d[30]), "+f"(d[31]), "+f"(d[32]), "+f"(d[33]),
          "+f"(d[34]), "+f"(d[35]), "+f"(d[36]), "+f"(d[37]), "+f"(d[38]), "+f"(d[39]), "+f"(d[40]), "+f"(d[41]), "+f"(d[42]), "+f"(d[43]), "+f"(d[44]),
          "+f"(d[45]), "+f"(d[46]), "+f"(d[47]), "+f"(d[48]), "+f"(d[49]), "+f"(d[50]), "+f"(d[51]), "+f"(d[52]), "+f"(d[53]), "+f"(d[54]), "+f"(d[55]),
          "+f"(d[56]), "+f"(d[57]), "+f"(d[58]), "+f"(d[59]), "+f"(d[60]), "+f"(d[61]), "+f"(d[62]), "+f"(d[63])
        : "r"(alo), "r"(blo), "r"(scale_d));
}
__device__ __forceinline__ void mma_pv(float (&d)[20], uint32_t a0, uint32_t a1, uint32_t a2, uint32_t a3, uint32_t blo, int scale_d) {
    asm volatile("{\n.reg .pred p;\n.reg .b64 da, db;\nsetp.ne.b32 p, %25, 0;\nmov.b64 db, {%24, 0x80000020};\n"
        "wgmma.mma_async.sync.aligned.m64n40k16.f32.bf16.bf16 {"
        "%0, %1, %2, %3, %4, %5, %6, %7, %8, %9, %10, %11, %12, %13, %14, %15, %16, %17, %18, %19 "
        "}, {%20, %21, %22, %23}, db, p, 1, 1, 1;\n}\n"
        : "+f"(d[0]), "+f"(d[1]), "+f"(d[2]), "+f"(d[3]), "+f"(d[4]), "+f"(d[5]), "+f"(d[6]), "+f"(d[7]), "+f"(d[8]), "+f"(d[9]), "+f"(d[10]), "+f"(d[11]),
          "+f"(d[12]), "+f"(d[13]), "+f"(d[14]), "+f"(d[15]), "+f"(d[16]), "+f"(d[17]), "+f"(d[18]), "+f"(d[19])
        : "r"(a0), "r"(a1), "r"(a2), "r"(a3), "r"(blo), "r"(scale_d));
}

__device__ __forceinline__ float warp_sum(float v) {
#pragma unroll
    for (int o = 16; o > 0; o >>= 1) v += __shfl_xor_sync(0xffffffffu, v, o);
    return v;
}

struct GemmSmem { uint32_t base, full0, empty0, aux; };

template <class C>
__device__ __forceinline__ GemmSmem gemm_setup(uint8_t* smem_raw) {
    GemmSmem s;
    s.base = smem_u32(smem_raw);
    s.full0 = s.base + C::BAR_OFF; s.empty0 = s.full0 + 8 * C::STAGES; s.aux = s.empty0 + 8 * C::STAGES;
    if (threadIdx.x == 0) {
        if (s.base & 1023) __trap();
        for (int i = 0; i < C::STAGES; i++) { mbar_init(s.full0 + 8 * i, 1); mbar_init(s.empty0 + 8 * i, C::MC ? 16 : 8); }
        mbar_init(s.aux, C::AUX_COUNT);
        fence_barrier_init();
    }
    __syncthreads();
    if (C::MC) { cluster_arrive(); cluster_wait(); }
    return s;
}

#define TK(slot)
#define TKC(slot)
template <class C, class P>
__device__ __forceinline__ void gemm_producer(const GemmSmem& s, const P& p, int tm, int tn) {
    TK(8);
    if (C::ACC_INIT) C::load_aux(p, s, tm, tn);
#pragma unroll 1
    for (int k = 0; k < C::PRE; k++) {
        mbar_expect_tx(s.full0 + 8 * k, C::STAGE_BYTES);
        C::load_w(p, s.base + k * C::STAGE_BYTES, s.full0 + 8 * k, k, tm, tn);
    }
    TK(9);
    pdl_wait();
    TK(10);
#pragma unroll 1
    for (int k = 0; k < C::STAGES; k++) {
        if (k >= C::PRE) mbar_expect_tx(s.full0 + 8 * k, C::STAGE_BYTES);
        C::load_x(p, s.base + k * C::STAGE_BYTES, s.full0 + 8 * k, k, tm, tn);
        if (k >= C::PRE) C::load_w(p, s.base + k * C::STAGE_BYTES, s.full0 + 8 * k, k, tm, tn);
    }
    TK(11);
    if (!C::ACC_INIT) C::load_aux(p, s, tm, tn);
    int st = 0; uint32_t ph = 0;
#pragma unroll 1
    for (int k = C::STAGES; k < C::KSTEPS; k++) {
        mbar_wait(s.empty0 + 8 * st, ph);
        mbar_expect_tx(s.full0 + 8 * st, C::STAGE_BYTES);
        C::load_x(p, s.base + st * C::STAGE_BYTES, s.full0 + 8 * st, k, tm, tn);
        C::load_w(p, s.base + st * C::STAGE_BYTES, s.full0 + 8 * st, k, tm, tn);
        C::prefetch(p, k);
        if (++st == C::STAGES) { st = 0; ph ^= 1; }
    }
}

template <class C>
__device__ __forceinline__ void gemm_mainloop(const GemmSmem& s, int wg, float (&acc)[C::MB][C::BN / 2], int tlk = 0) {
    const int lane = threadIdx.x & 31;
    if constexpr (C::SYNC_NS > 0) {
        unsigned long long t0, t1; asm volatile("mov.u64 %0, %%globaltimer;" : "=l"(t0));
        do { asm volatile("mov.u64 %0, %%globaltimer;" : "=l"(t1)); } while (t1 - t0 < C::SYNC_NS);
    }
    int st = 0; uint32_t ph = 0;
    int prev = 0;
    const uint32_t rel0 = C::MC ? mapa(s.empty0, lane & 1) : s.empty0;
#pragma unroll
    for (int m = 0; m < C::MB; m++) fence_regs(acc[m]);
#pragma unroll 1
    for (int k = 0; k < C::KSTEPS; k++) {
        mbar_wait(s.full0 + 8 * st, ph);
        const uint32_t sb = s.base + st * C::STAGE_BYTES;
        wg_fence();
#pragma unroll
        for (int kk = 0; kk < 4; kk++) {
#pragma unroll
            for (int m = 0; m < C::MB; m++) C::mma(acc[m], C::desc_a(sb, wg, m, kk), C::desc_b(sb, kk), C::ACC_INIT || (k | kk) != 0);
        }
        wg_commit();
        if (k > 0) {
            wg_wait<1>();
            if (k <= C::KSTEPS - C::STAGES) {
                if (C::MC) { if (lane < 2) mbar_arrive_cluster(rel0 + 8 * prev); }
                else if (lane == 0) mbar_arrive(rel0 + 8 * prev);
            }
        }
        prev = st;
        if (++st == C::STAGES) { st = 0; ph ^= 1; }
    }
    wg_wait<0>();
#pragma unroll
    for (int m = 0; m < C::MB; m++) fence_regs(acc[m]);
}

struct QkvParams { CUtensorMap x, w, out; const bf16* xp; const bf16* wp; };
struct QkvCfg {
    static constexpr int MB = 2, BN = 192, KSTEPS = 16, STAGES = 4, A_BYTES = 32768, B_BYTES = 24576;
    static constexpr int STAGE_BYTES = A_BYTES + B_BYTES, BAR_OFF = STAGES * STAGE_BYTES, AUX_OFF = BAR_OFF + 128, SMEM = AUX_OFF + 2816;
    static constexpr int AUX_COUNT = 3, PRE = STAGES;
    static constexpr int TLK = 1;
    static constexpr bool MC = false, PAIR = false, ACC_INIT = false;
    static constexpr int SYNC_NS = 0;
    static __device__ __forceinline__ void prefetch(const QkvParams&, int) {}
    static __device__ __forceinline__ void load_w(const QkvParams& p, uint32_t sb, uint32_t bar, int k, int tm, int tn) { tma_ld4(sb + A_BYTES, &p.w, bar, 0, k * 64, 0, tn); }
    static __device__ __forceinline__ void load_x(const QkvParams& p, uint32_t sb, uint32_t bar, int k, int tm, int tn) { tma_ld2(sb, &p.x, bar, k * 64, tm * 256); }
    static __device__ __forceinline__ void load_aux(const QkvParams&, const GemmSmem&, int, int) {}
    static __device__ __forceinline__ uint32_t desc_a(uint32_t sb, int wg, int m, int kk) { return desc_lo(sb + (wg * 128 + m * 64) * 128 + kk * 32, 16); }
    static __device__ __forceinline__ uint32_t desc_b(uint32_t sb, int kk) { return desc_lo(sb + A_BYTES + kk * 2048, 8192); }
    static __device__ __forceinline__ void mma(float (&d)[96], uint32_t a, uint32_t b, int sc) { mma_qkv(d, a, b, sc); }
};

__device__ __forceinline__ void spin_until(const uint32_t* cnt, uint32_t target) {
    uint32_t v; int it = 0;
    do {
        asm volatile("ld.acquire.gpu.global.u32 %0, [%1];" : "=r"(v) : "l"(cnt) : "memory");
        if (++it > (1 << 22)) __trap();
    } while (v < target);
}
__device__ __forceinline__ void publish(uint32_t* cnt) { asm volatile("red.release.gpu.global.add.u32 [%0], 1;" :: "l"(cnt) : "memory"); }

__device__ __forceinline__ void qkv_aux(const QkvParams& p, uint8_t* smem_raw, const GemmSmem& s, int tm, int tn, int w, int lane) {
    for (int r = w; r < 16; r += 3) {
        const int row = tm * 256 + tn * 16 + r;
        const uint4* src = reinterpret_cast<const uint4*>(p.xp + (size_t)row * DM);
        uint32_t v[16];
#pragma unroll
        for (int i = 0; i < 4; i++) { const uint4 t = __ldg(src + lane + 32 * i); v[4 * i] = t.x; v[4 * i + 1] = t.y; v[4 * i + 2] = t.z; v[4 * i + 3] = t.w; }
        float sum = 0.f;
#pragma unroll
        for (int i = 0; i < 16; i++) sum += bf_lo(v[i]) + bf_hi(v[i]);
        const float mean = warp_sum(sum) * (1.f / DM);
        float q = 0.f;
#pragma unroll
        for (int i = 0; i < 16; i++) { const float a = bf_lo(v[i]) - mean, b = bf_hi(v[i]) - mean; q += a * a + b * b; }
        const float rstd = rsqrtf(warp_sum(q) * (1.f / DM) + 1e-5f);
        if (lane == 0) g_rowstat[row] = make_float2(mean, rstd);
    }
    __syncwarp();
    if (lane == 0) publish(&g_cnt_row[tm]);
    {
        const uint4* src = reinterpret_cast<const uint4*>(p.wp + (size_t)(tm * 128 + (lane >> 3)) * (3 * DM) + w * DM + tn * 64) + (lane & 7);
        float a[8];
#pragma unroll
        for (int i = 0; i < 8; i++) a[i] = 0.f;
#pragma unroll 1
        for (int j = 0; j < 32; j += 8) {
            uint4 t[8];
#pragma unroll
            for (int i = 0; i < 8; i++) t[i] = __ldg(src + (size_t)(j + i) * 4 * (3 * DM / 8));
#pragma unroll
            for (int i = 0; i < 8; i++) {
                a[0] += bf_lo(t[i].x); a[1] += bf_hi(t[i].x); a[2] += bf_lo(t[i].y); a[3] += bf_hi(t[i].y);
                a[4] += bf_lo(t[i].z); a[5] += bf_hi(t[i].z); a[6] += bf_lo(t[i].w); a[7] += bf_hi(t[i].w);
            }
        }
#pragma unroll
        for (int i = 0; i < 8; i++) { a[i] += __shfl_xor_sync(0xffffffffu, a[i], 8); a[i] += __shfl_xor_sync(0xffffffffu, a[i], 16); }
        if (lane < 8) {
            float4* dst = reinterpret_cast<float4*>(g_colsum + tm * (3 * DM) + tn * 192 + w * 64 + lane * 8);
            dst[0] = make_float4(a[0], a[1], a[2], a[3]); dst[1] = make_float4(a[4], a[5], a[6], a[7]);
        }
        __syncwarp();
        if (lane == 0) publish(&g_cnt_col[tn]);
    }
    float* scs = reinterpret_cast<float*>(smem_raw + QkvCfg::AUX_OFF);
    float2* sst = reinterpret_cast<float2*>(smem_raw + QkvCfg::AUX_OFF + 768);
    const int t = w * 32 + lane;
    spin_until(&g_cnt_row[tm], 16 * 3);
    for (int r = t; r < 256; r += 96) sst[r] = __ldcg(&g_rowstat[tm * 256 + r]);
    spin_until(&g_cnt_col[tn], 8 * 3);
    {
        float2 c = make_float2(0.f, 0.f);
#pragma unroll
        for (int i = 0; i < 8; i++) { const float2 u = __ldcg(reinterpret_cast<const float2*>(g_colsum + i * (3 * DM) + tn * 192) + t); c.x += u.x; c.y += u.y; }
        reinterpret_cast<float2*>(scs)[t] = c;
    }
    __syncwarp();
    if (lane == 0) mbar_arrive(s.aux);
}

__global__ void __launch_bounds__(384, 1) qkv_kernel(const __grid_constant__ QkvParams p) {
    extern __shared__ __align__(1024) uint8_t smem_raw[];
    TL(1, 4);
    pdl_launch();
    const int tm = blockIdx.x & 7, tn = blockIdx.x >> 3;
    if (threadIdx.x == 0) { prefetch_map(&p.x); prefetch_map(&p.w); prefetch_map(&p.out); }
    const GemmSmem s = gemm_setup<QkvCfg>(smem_raw);
    const int wgi = __shfl_sync(0xffffffffu, threadIdx.x >> 7, 0);
    if (wgi == 0) {
        reg_dealloc<56>();
        if (threadIdx.x < 32) {
            if (threadIdx.x == 0) gemm_producer<QkvCfg>(s, p, tm, tn);
            __syncwarp();
#pragma unroll 1
            for (int i = 0; i < 12; i++) {
                const int sub = i >> 1, wg = i & 1;
                named_bar(2 + i, 160);
                if (threadIdx.x == 0) tma_st2(&p.out, s.base + sub * 16384 + wg * 8192, 0, (sub >> 1) * (NH * SEQ) + (tn * 2 + (sub & 1)) * SEQ + tm * 256 + wg * 128);
            }
            if (threadIdx.x == 0) { tma_st_commit(); tma_st_wait(); TL(1, 3); }
        } else qkv_aux(p, smem_raw, s, tm, tn, (threadIdx.x >> 5) - 1, threadIdx.x & 31);
    } else {
        reg_alloc<224>();
        const int wg = wgi - 1, warp = (threadIdx.x >> 5) & 3, lane = threadIdx.x & 31;
        float acc[2][96];
        TL(1, 0);
        gemm_mainloop<QkvCfg>(s, wg, acc, 1);
        TL(1, 1);
        mbar_wait(s.aux, 0);
        named_bar(1, 256);
        const float qscale = 0.17677669529663687f * 1.4426950408889634f;
        const float2* scs = reinterpret_cast<const float2*>(smem_raw + QkvCfg::AUX_OFF);
        const float2* sst = reinterpret_cast<const float2*>(smem_raw + QkvCfg::AUX_OFF + 768);
        float mean[4], rstd[4];
#pragma unroll
        for (int i = 0; i < 4; i++) { const float2 t = sst[wg * 128 + (i >> 1) * 64 + warp * 16 + (i & 1) * 8 + (lane >> 2)]; mean[i] = -t.x; rstd[i] = t.y; }
#pragma unroll
        for (int sub = 0; sub < 6; sub++) {
            float nrm[4];
#pragma unroll
            for (int m = 0; m < 2; m++) {
                const int arow = wg * 128 + m * 64 + warp * 16 + ((lane >> 3) & 1) * 8 + (lane & 7);
                const float r0 = (sub < 2) ? rstd[2 * m] * qscale : rstd[2 * m], r1 = (sub < 2) ? rstd[2 * m + 1] * qscale : rstd[2 * m + 1];
                float v[16];
#pragma unroll
                for (int j = 0; j < 4; j++) {
                    const float2 cs = scs[(sub * 4 + j) * 4 + (lane & 3)];
                    v[4 * j] = fmaf(mean[2 * m], cs.x, acc[m][sub * 16 + 4 * j]) * r0;
                    v[4 * j + 1] = fmaf(mean[2 * m], cs.y, acc[m][sub * 16 + 4 * j + 1]) * r0;
                    v[4 * j + 2] = fmaf(mean[2 * m + 1], cs.x, acc[m][sub * 16 + 4 * j + 2]) * r1;
                    v[4 * j + 3] = fmaf(mean[2 * m + 1], cs.y, acc[m][sub * 16 + 4 * j + 3]) * r1;
                }
                float n0 = 0.f, n1 = 0.f;
#pragma unroll
                for (int j = 0; j < 4; j++) {
                    n0 = fmaf(v[4 * j], v[4 * j], fmaf(v[4 * j + 1], v[4 * j + 1], n0));
                    n1 = fmaf(v[4 * j + 2], v[4 * j + 2], fmaf(v[4 * j + 3], v[4 * j + 3], n1));
                }
                nrm[2 * m] = n0; nrm[2 * m + 1] = n1;
#pragma unroll
                for (int jp = 0; jp < 2; jp++) {
                    const int chunk = jp * 2 + (lane >> 4);
                    const uint32_t addr = s.base + sub * 16384 + arow * 64 + ((chunk ^ ((arow >> 1) & 3)) << 4);
                    stmatrix_x4(addr, pack_bf16(v[8 * jp], v[8 * jp + 1]), pack_bf16(v[8 * jp + 2], v[8 * jp + 3]),
                                pack_bf16(v[8 * jp + 4], v[8 * jp + 5]), pack_bf16(v[8 * jp + 6], v[8 * jp + 7]));
                }
            }
            hand_over(2 + sub * 2 + wg);
            const bool odd = lane & 1, up = lane & 2;
            const float s0 = (odd ? nrm[2] : nrm[0]) + __shfl_xor_sync(0xffffffffu, odd ? nrm[0] : nrm[2], 1);
            const float s1 = (odd ? nrm[3] : nrm[1]) + __shfl_xor_sync(0xffffffffu, odd ? nrm[1] : nrm[3], 1);
            const float full = (up ? s1 : s0) + __shfl_xor_sync(0xffffffffu, up ? s0 : s1, 2);
            const uint32_t mx = __reduce_max_sync(0xffffffffu, __float_as_uint(full));
            if (lane == 0) g_norm[((sub >> 1) * NH + tn * 2 + (sub & 1)) * 64 + (tm * 2 + wg) * 4 + warp] = mx;
        }
        TL(1, 5);
    }
}

struct AttnParams { CUtensorMap kv, kv2, o; bf16* optr; const uint8_t* pf_wo; const uint8_t* pf_w1; const uint8_t* pf_x; };
constexpr int AT_STAGES = 8, AT_STAGE_BYTES = 16384, AT_Q_OFF = AT_STAGES * AT_STAGE_BYTES, AT_ONES_OFF = AT_Q_OFF + 32768, AT_STG_OFF = AT_ONES_OFF + 1024, AT_BAR_OFF = AT_STG_OFF + 16384, AT_SMEM = AT_BAR_OFF + 256;
constexpr int AT_TILES = 32;

__device__ __forceinline__ float ex2_poly(float x) {
    const float magic = 12582912.f;
    const float t = x + magic;
    const float f = x - (t - magic);
    float p = fmaf(f, 0.05550410866f, 0.24022650695f);
    p = fmaf(p, f, 0.69314718056f);
    p = fmaf(p, f, 1.0f);
    return __int_as_float(__float_as_int(p) + (__float_as_int(t) << 23));
}

__device__ __forceinline__ uint32_t fma_bf16x2(uint32_t a, uint32_t b, uint32_t c) { uint32_t d; asm("fma.rn.bf16x2 %0, %1, %2, %3;" : "=r"(d) : "r"(a), "r"(b), "r"(c)); return d; }
__device__ __forceinline__ uint32_t ex2_pair(float x0, float x1, uint32_t c3) {
    const float m0 = 12582912.f, m1 = 12582912.f - 64.f;
    const float t0 = x0 + m0, t1 = x1 + m1;
    const uint32_t f = pack_bf16(x0 - (t0 - m0), x1 - (t1 - m1));
    uint32_t p = fma_bf16x2(f, c3, 0xBE763E76u);
    p = fma_bf16x2(p, f, 0xBF313F31u);
    p = fma_bf16x2(p, f, 0xBF803F80u);
    return p + (__float_as_uint(t1) << 23) + (__float_as_uint(t0) << 7);
}
template <uint32_t MASK> __device__ __forceinline__ uint32_t attn_exp2(float x0, float x1, int i, uint32_t c3) {
    return ((MASK >> i) & 1) ? ex2_pair(x0, x1, c3) : pack_bf16(ex2(x0), ex2(x1));
}
template <uint32_t MASK> __device__ __forceinline__ float attn_exp(float x, int i) { return ((MASK >> (i & 31)) & 1) ? ex2_poly(x) : ex2(x); }
__device__ __forceinline__ void attn_issue_tile(const AttnParams& p, uint32_t base, uint32_t full0, int g, int head) {
    const int st = g % AT_STAGES, key0 = (g & 15) * 128;
    const uint32_t bar = full0 + 8 * st, dst = base + st * AT_STAGE_BYTES;
    mbar_expect_tx(bar, AT_STAGE_BYTES);
    tma_ld3(dst, &p.kv2, bar, 0, head * SEQ + key0, 1);
}
__device__ __forceinline__ void attn_qk(float (&sacc)[32], uint32_t q_lo, uint32_t k_lo) {
    mma_qk0(sacc, q_lo, k_lo);
    mma_qk1(sacc, q_lo + 2, k_lo + 2, 1);
}
constexpr uint32_t PV_STEP = 64u - (64u << 16);
__device__ __forceinline__ void attn_pv(float (&o)[20], const uint32_t (&pr)[16], uint32_t v_lo, int first) {
#pragma unroll
    for (int kk = 0; kk < 4; kk++)
        mma_pv(o, pr[4 * kk], pr[4 * kk + 1], pr[4 * kk + 2], pr[4 * kk + 3], v_lo + kk * PV_STEP, (kk > 0) || !first);
}
__device__ __forceinline__ void attn_store_o(const float (&o)[20], const AttnParams& p, uint32_t base, int head, int row0, int lane) {
    const float r0 = 1.f / o[16], r1 = 1.f / o[18];
    {
        uint32_t a[4], b[4];
#pragma unroll
        for (int j = 0; j < 4; j++) { a[j] = pack_bf16(o[4 * j] * r0, o[4 * j + 1] * r0); b[j] = pack_bf16(o[4 * j + 2] * r1, o[4 * j + 3] * r1); }
        const bool odd = lane & 1, up = lane & 2;
#pragma unroll
        for (int h = 0; h < 2; h++) {
            uint32_t t = __shfl_xor_sync(0xffffffffu, odd ? a[2 * h] : a[2 * h + 1], 1); if (odd) a[2 * h] = t; else a[2 * h + 1] = t;
            t = __shfl_xor_sync(0xffffffffu, odd ? b[2 * h] : b[2 * h + 1], 1); if (odd) b[2 * h] = t; else b[2 * h + 1] = t;
        }
#pragma unroll
        for (int h = 0; h < 2; h++) {
            uint32_t t = __shfl_xor_sync(0xffffffffu, up ? a[h] : a[h + 2], 2); if (up) a[h] = t; else a[h + 2] = t;
            t = __shfl_xor_sync(0xffffffffu, up ? b[h] : b[h + 2], 2); if (up) b[h] = t; else b[h + 2] = t;
        }
        uint4* op = reinterpret_cast<uint4*>(p.optr + (size_t)(row0 + (lane >> 2)) * DM + head * HD) + (lane & 3);
        op[0] = make_uint4(a[0], a[1], a[2], a[3]);
        op[8 * (DM / 8)] = make_uint4(b[0], b[1], b[2], b[3]);
        return;
    }
    const uint32_t stg = base + AT_STG_OFF + (threadIdx.x >> 5) * 1024;
    const int arow = ((lane >> 3) & 1) * 8 + (lane & 7);
    if (lane == 0) tma_st_wait();
    __syncwarp();
#pragma unroll
    for (int jp = 0; jp < 2; jp++) {
        const int chunk = jp * 2 + (lane >> 4);
        stmatrix_x4(stg + arow * 64 + ((chunk ^ ((arow >> 1) & 3)) << 4), pack_bf16(o[8 * jp] * r0, o[8 * jp + 1] * r0), pack_bf16(o[8 * jp + 2] * r1, o[8 * jp + 3] * r1),
                    pack_bf16(o[8 * jp + 4] * r0, o[8 * jp + 5] * r0), pack_bf16(o[8 * jp + 6] * r1, o[8 * jp + 7] * r1));
    }
    fence_proxy_async();
    __syncwarp();
    if (lane == 0) { tma_st2(&p.o, stg, head * HD, row0); tma_st_commit(); }
}
__device__ __forceinline__ void attn_refill(const AttnParams& p, uint32_t base, uint32_t full0, uint32_t empty0, int g, int head) {
    if (threadIdx.x == 0 && g >= 4 && g + 4 < AT_TILES) {
        const int gp = g - 4;
        mbar_wait(empty0 + 8 * (gp % AT_STAGES), (gp / AT_STAGES) & 1);
        attn_issue_tile(p, base, full0, g + 4, head);
    }
    __syncwarp();
}

__device__ __forceinline__ void attn_fast(const AttnParams& p, uint32_t base, uint32_t full0, uint32_t empty0, int head, int qchunk) {
    const int wg = __shfl_sync(0xffffffffu, threadIdx.x >> 7, 0), warp = (threadIdx.x >> 5) & 3, lane = threadIdx.x & 31;
    const int warp_id = __shfl_sync(0xffffffffu, threadIdx.x >> 5, 0);
    const uint32_t k_lo0 = desc_lo(base, 16), v_lo0 = desc_lo(base + 8192, AT_ONES_OFF - 8192);
    const uint32_t q_lo0 = desc_lo(base + AT_Q_OFF + wg * 64 * 64, 16);
    uint32_t c3;
    asm volatile("ld.shared.u32 %0, [%1];" : "=r"(c3) : "r"(base + AT_ONES_OFF));
    c3 ^= 0x3F803F80u ^ 0xBD693D69u;
#pragma unroll 1
    for (int pass = 0; pass < 2; pass++) {
    const uint32_t q = q_lo0 + pass * (256 * 64 >> 4);
    float o[20];
#pragma unroll
    for (int i = 0; i < 20; i++) o[i] = 0.f;
    if (PF_W1 == 3 && pass == 1 && threadIdx.x < 128 + 140) {
        const int l = threadIdx.x;
        prefetch_line(l < 128 ? p.pf_wo + ((size_t)blockIdx.x * 128 + l) * 128 : p.pf_w1 + ((size_t)blockIdx.x * 140 + (l - 128)) * 128);
    }
#pragma unroll 1
    for (uint32_t par = 0; par < 2; par++) {
        const int rev = pass * 2 + par;
        if (PF_W1 == 1 && threadIdx.x < 256) {
            const int l = rev * 256 + threadIdx.x;
            prefetch_line(l < 128 ? p.pf_wo + ((size_t)blockIdx.x * 128 + l) * 128 : p.pf_w1 + ((size_t)blockIdx.x * 896 + (l - 128)) * 128);
        }
        if (PF_W1 == 2 && rev == PF_REV && threadIdx.x < 128 + 140) {
            const int l = threadIdx.x;
            prefetch_line(l < 128 ? p.pf_wo + ((size_t)blockIdx.x * 128 + l) * 128 : p.pf_w1 + ((size_t)blockIdx.x * 140 + (l - 128)) * 128);
        }
#pragma unroll
        for (int st = 0; st < AT_STAGES; st++) {
            if (warp_id == (st & 3) * 5) {
                const int g = rev * AT_STAGES + st;
                if (lane == 0 && g >= 4 && g + 4 < AT_TILES) {
                    mbar_wait(empty0 + 8 * ((st + 4) % AT_STAGES), (st >= 4) ? par : (par ^ 1));
                    attn_issue_tile(p, base, full0, g + 4, head);
                }
                __syncwarp();
            }
            mbar_wait(full0 + 8 * st, par);
            float sc[64];
            uint32_t pa[16], pb[16];
            AT(0);
            wg_fence();
            mma_qkw0(sc, q, k_lo0 + st * (AT_STAGE_BYTES >> 4));
            mma_qkw1(sc, q + 2, k_lo0 + st * (AT_STAGE_BYTES >> 4) + 2, 1);
            wg_commit();
            wg_wait<0>();
            fence_regs(sc);
            AT(1);
            if (lane == 0 && (st > 0 || rev > 0)) mbar_arrive(empty0 + 8 * ((st + AT_STAGES - 1) % AT_STAGES));
#pragma unroll
            for (int i = 0; i < 16; i++) pa[i] = PAIR_POLY ? attn_exp2<PMASK_A>(sc[2 * i], sc[2 * i + 1], i, c3) : pack_bf16(attn_exp<POLY_MASK>(sc[2 * i], 2 * i), attn_exp<POLY_MASK>(sc[2 * i + 1], 2 * i + 1));
            wg_fence();
            attn_pv(o, pa, v_lo0 + st * 16 * PV_STEP, 0);
            wg_commit();
            AT(2);
#pragma unroll
            for (int i = 0; i < 16; i++) pb[i] = PAIR_POLY ? attn_exp2<PMASK_B>(sc[32 + 2 * i], sc[32 + 2 * i + 1], i, c3) : pack_bf16(attn_exp<POLY_MASK_B>(sc[32 + 2 * i], 2 * i), attn_exp<POLY_MASK_B>(sc[32 + 2 * i + 1], 2 * i + 1));
            wg_wait<0>();
            wg_fence();
            attn_pv(o, pb, v_lo0 + (st * 16 + 4) * PV_STEP, 0);
            wg_commit();
            AT(3);
        }
    }
    wg_wait<0>();
    fence_regs(o);
    attn_store_o(o, p, base, head, qchunk * 512 + pass * 256 + wg * 64 + warp * 16, lane);
    }
}

__device__ __forceinline__ void attn_safe(const AttnParams& p, uint32_t base, uint32_t full0, uint32_t empty0, int head, int qchunk) {
    const int wg = __shfl_sync(0xffffffffu, threadIdx.x >> 7, 0), warp = (threadIdx.x >> 5) & 3, lane = threadIdx.x & 31;
    const uint32_t k_lo0 = desc_lo(base, 16), v_lo0 = desc_lo(base + 8192, AT_ONES_OFF - 8192);
#pragma unroll 1
    for (int pass = 0; pass < 2; pass++) {
        const uint32_t q = desc_lo(base + AT_Q_OFF + (pass * 256 + wg * 64) * 64, 16);
        float o[20];
#pragma unroll
        for (int i = 0; i < 20; i++) o[i] = 0.f;
        float m0 = -INFINITY, m1 = -INFINITY;
#pragma unroll 1
        for (int t = 0; t < 32; t++) {
            const int g = pass * 16 + (t >> 1), half = t & 1;
            const int st = g % AT_STAGES;
            const uint32_t kb = k_lo0 + st * (AT_STAGE_BYTES >> 4), vb = v_lo0 + st * 16 * PV_STEP;
            if (half == 0) { attn_refill(p, base, full0, empty0, g, head); mbar_wait(full0 + 8 * st, (g / AT_STAGES) & 1); }
            float cur[32];
            wg_fence();
            attn_qk(cur, q, kb + half * 256);
            wg_commit();
            wg_wait<0>();
            fence_regs(cur);
            float x0 = cur[0], x1 = cur[2];
#pragma unroll
            for (int i = 0; i < 8; i++) { x0 = fmaxf(x0, fmaxf(cur[4 * i], cur[4 * i + 1])); x1 = fmaxf(x1, fmaxf(cur[4 * i + 2], cur[4 * i + 3])); }
            x0 = fmaxf(x0, __shfl_xor_sync(0xffffffffu, x0, 1)); x1 = fmaxf(x1, __shfl_xor_sync(0xffffffffu, x1, 1));
            x0 = fmaxf(x0, __shfl_xor_sync(0xffffffffu, x0, 2)); x1 = fmaxf(x1, __shfl_xor_sync(0xffffffffu, x1, 2));
            const float n0 = fmaxf(m0, x0), n1 = fmaxf(m1, x1);
            const float a0 = ex2(m0 - n0), a1 = ex2(m1 - n1);
            m0 = n0; m1 = n1;
            uint32_t pr[16];
#pragma unroll
            for (int i = 0; i < 8; i++) {
                pr[2 * i] = pack_bf16(ex2(cur[4 * i] - n0), ex2(cur[4 * i + 1] - n0));
                pr[2 * i + 1] = pack_bf16(ex2(cur[4 * i + 2] - n1), ex2(cur[4 * i + 3] - n1));
            }
#pragma unroll
            for (int i = 0; i < 5; i++) { o[4 * i] *= a0; o[4 * i + 1] *= a0; o[4 * i + 2] *= a1; o[4 * i + 3] *= a1; }
            wg_fence();
            attn_pv(o, pr, vb + half * 4 * PV_STEP, 0);
            wg_commit();
            wg_wait<0>();
            fence_regs(o);
            if (half == 1 && lane == 0) mbar_arrive(empty0 + 8 * st);
        }
        attn_store_o(o, p, base, head, qchunk * 512 + pass * 256 + wg * 64 + warp * 16, lane);
    }
}

__global__ void __launch_bounds__(512, 1) attn_kernel(const __grid_constant__ AttnParams p) {
    extern __shared__ __align__(1024) uint8_t smem_raw[];
    TL(2, 4);
    pdl_launch();
    const uint32_t base = smem_u32(smem_raw);
    const uint32_t full0 = base + AT_BAR_OFF, empty0 = full0 + 8 * AT_STAGES;
    const int head = blockIdx.x >> 2, qchunk = blockIdx.x & 3;
    if (threadIdx.x == 0) {
        if (base & 1023) __trap();
        prefetch_map(&p.kv);
        for (int i = 0; i < AT_STAGES; i++) { mbar_init(full0 + 8 * i, 1); mbar_init(empty0 + 8 * i, 16); }
        mbar_init(empty0 + 8 * AT_STAGES, 1);
        fence_barrier_init();
    }
    if (threadIdx.x < 256) reinterpret_cast<uint32_t*>(smem_raw + AT_ONES_OFF)[threadIdx.x] = 0x3F803F80u;
    fence_proxy_async();
    __syncthreads();
    pdl_wait();
    TL(2, 0);
    if (threadIdx.x == 0) {
        const uint32_t qbar = empty0 + 8 * AT_STAGES;
        mbar_expect_tx(qbar, 32768);
        for (int i = 0; i < 4; i++) tma_ld2(base + AT_Q_OFF + i * 8192, &p.kv, qbar, 0, head * SEQ + qchunk * 512 + i * 128);
        for (int g = 0; g < AT_STAGES; g++) attn_issue_tile(p, base, full0, g, head);
    }
    __syncwarp();
    const uint2* nrm = reinterpret_cast<const uint2*>(g_norm) + head * 32 + (threadIdx.x & 31);
    const uint2 nq = __ldcg(nrm), nk = __ldcg(nrm + NH * 32), nv = __ldcg(nrm + 2 * NH * 32);
    const float qn = __uint_as_float(__reduce_max_sync(0xffffffffu, max(nq.x, nq.y)));
    const float kn = __uint_as_float(__reduce_max_sync(0xffffffffu, max(nk.x, nk.y)));
    const float vn = __uint_as_float(__reduce_max_sync(0xffffffffu, max(nv.x, nv.y)));
    if (blockIdx.x == 0 && threadIdx.x >= 64 && threadIdx.x < 64 + 24) {
        const int i = threadIdx.x - 64;
        if (i < 8) g_cnt_row[i] = 0; else g_cnt_col[i - 8] = 0;
    }
    if (PF_W1 == 4) {
        const int l = threadIdx.x;
        if (l < 128 + 140) prefetch_line(l < 128 ? p.pf_wo + ((size_t)blockIdx.x * 128 + l) * 128 : p.pf_w1 + ((size_t)blockIdx.x * 140 + (l - 128)) * 128);
        if (PF_X && l >= 256) prefetch_line(p.pf_x + ((size_t)blockIdx.x * 256 + (l - 256)) * 128);
    }
    if (threadIdx.x >= 448) reinterpret_cast<uint4*>(g_hpart)[blockIdx.x * 64 + threadIdx.x - 448] = make_uint4(0, 0, 0, 0);
    const bool bounded = (qn * kn <= 1.0e4f) && (vn <= 1.0e9f);
    mbar_wait(empty0 + 8 * AT_STAGES, 0);
    if (bounded) attn_fast(p, base, full0, empty0, head, qchunk);
    else attn_safe(p, base, full0, empty0, head, qchunk);
    if ((threadIdx.x & 31) == 0) tma_st_wait();
    TL(2, 3);
}

struct ResParams { CUtensorMap a, b, res, out; const bf16* bias; };
template <bool MIX2>
struct ResCfg {
    static constexpr int MB = 1, BN = 128, KSTEPS = MIX2 ? 56 : 16, STAGES = 6, A_BYTES = 16384, B_BYTES = 16384;
    static constexpr int STAGE_BYTES = A_BYTES + B_BYTES, STG_OFF = STAGES * STAGE_BYTES, BAR_OFF = STG_OFF + 32768, SMEM = BAR_OFF + 128;
    static constexpr int AUX_COUNT = 1, PRE = MIX2 ? MIX2_PRE : WO_PRE;
    static constexpr int TLK = MIX2 ? 6 : 3;
    static constexpr bool MC = MIX2 ? MIX2_MC : WO_MC, PAIR = MC || (MIX2 ? MIX2_PAIR : WO_PAIR), ACC_INIT = MIX2 ? MIX2_INIT : WO_INIT;
    static constexpr int SYNC_NS = MIX2 ? MIX2_SYNC : WO_SYNC;
    static __device__ __forceinline__ void prefetch(const ResParams&, int) {}
    static __device__ __forceinline__ void load_w(const ResParams& p, uint32_t sb, uint32_t bar, int k, int tm, int tn) {
        if (MIX2) {
            if (MC) tma_ld3_mc(sb + (tn & 1) * 8192, &p.a, bar, 0, k * 64, tm * 2 + (tn & 1));
            else tma_ld3(sb, &p.a, bar, 0, k * 64, tm * 2);
        } else tma_ld3(sb + A_BYTES, &p.b, bar, 0, k * 64, tn * 2);
    }
    static __device__ __forceinline__ void load_x(const ResParams& p, uint32_t sb, uint32_t bar, int k, int tm, int tn) {
        if (MIX2) tma_ld2(sb + A_BYTES, &p.b, bar, k * 64, tn * 128);
        else if (MC) tma_ld2_mc(sb + (tn & 1) * 8192, &p.a, bar, k * 64, tm * 128 + (tn & 1) * 64);
        else tma_ld2(sb, &p.a, bar, k * 64, tm * 128);
    }
    static __device__ __forceinline__ void load_aux(const ResParams& p, const GemmSmem& s, int tm, int tn) {
        mbar_expect_tx(s.aux, 32768);
        tma_ld2(s.base + STG_OFF, &p.res, s.aux, tn * 128, tm * 128);
        tma_ld2(s.base + STG_OFF + 16384, &p.res, s.aux, tn * 128 + 64, tm * 128);
    }
    static __device__ __forceinline__ uint32_t desc_a(uint32_t sb, int wg, int m, int kk) {
        return MIX2 ? desc_lo(sb + wg * 8192 + kk * 2048, 8192) : desc_lo(sb + wg * 8192 + kk * 32, 16);
    }
    static __device__ __forceinline__ uint32_t desc_b(uint32_t sb, int kk) {
        return MIX2 ? desc_lo(sb + A_BYTES + kk * 32, 16) : desc_lo(sb + A_BYTES + kk * 2048, 8192);
    }
    static __device__ __forceinline__ void mma(float (&d)[64], uint32_t a, uint32_t b, int sc) {
        if (MIX2) mma_mix2(d, a, b, sc); else mma_wo(d, a, b, sc);
    }
};
template <bool MIX2>
__global__ void __launch_bounds__(384, 1) res_gemm_kernel(const __grid_constant__ ResParams p) {
    using C = ResCfg<MIX2>;
    extern __shared__ __align__(1024) uint8_t smem_raw[];
    TL(MIX2 ? 6 : 3, 4);
    if (!MIX2) pdl_launch();
    constexpr bool MAP = MIX2 ? MIX2_MAP : WO_MAP;
    const int tm = MAP ? blockIdx.x >> 3 : blockIdx.x & 15, tn = MAP ? blockIdx.x & 7 : blockIdx.x >> 4;
    if (threadIdx.x == 0) { prefetch_map(&p.a); prefetch_map(&p.b); prefetch_map(&p.res); prefetch_map(&p.out); }
    const GemmSmem s = gemm_setup<C>(smem_raw);
    const int wgi = __shfl_sync(0xffffffffu, threadIdx.x >> 7, 0);
    if (wgi == 0) {
        reg_dealloc<40>();
        if (threadIdx.x < 32) {
            if (threadIdx.x == 0) gemm_producer<C>(s, p, tm, tn);
            __syncwarp();
#pragma unroll 1
            for (int i = 0; i < 4; i++) {
                const int b = i >> 1, wg = i & 1;
                named_bar(2 + i, 160);
                if (threadIdx.x == 0) tma_st2(&p.out, s.base + C::STG_OFF + b * 16384 + wg * 8192, tn * 128 + b * 64, tm * 128 + wg * 64);
            }
            if (threadIdx.x == 0) { tma_st_commit(); tma_st_wait(); TL(MIX2 ? 6 : 3, 3); }
        }
    } else {
        reg_alloc<232>();
        const int wg = wgi - 1, warp = (threadIdx.x >> 5) & 3, lane = threadIdx.x & 31;
        const int r0 = wg * 64 + warp * 16 + (lane >> 2);
        const int arow = wg * 64 + warp * 16 + ((lane >> 3) & 1) * 8 + (lane & 7);
        const uint32_t stg = s.base + C::STG_OFF + arow * 128;
        float acc[1][64];
        auto residual = [&]() {
            float a0 = 1.f, a1 = 1.f, c0 = 0.f, c1 = 0.f;
            if (MIX2) {
                const float2 t0 = __ldcg(&g_rowln[tm * 128 + r0]), t1 = __ldcg(&g_rowln[tm * 128 + r0 + 8]);
                a0 = t0.y; a1 = t1.y;
                c0 = t0.x + __bfloat162float(p.bias[tm * 128 + r0]); c1 = t1.x + __bfloat162float(p.bias[tm * 128 + r0 + 8]);
            }
            return make_float4(a0, a1, c0, c1);
        };
        auto apply = [&](const float4 ac) {
            mbar_wait(s.aux, 0);
#pragma unroll
            for (int jp = 0; jp < 8; jp++) {
                const int chunk = jp * 2 + (lane >> 4);
                uint32_t r[4];
                ldmatrix_x4(stg + (chunk >> 3) * 16384 + (((chunk & 7) ^ (arow & 7)) << 4), r);
#pragma unroll
                for (int i = 0; i < 4; i++) {
                    const float a = (i & 1) ? ac.y : ac.x, c = (i & 1) ? ac.w : ac.z;
                    const float v0 = MIX2 ? fmaf(bf_lo(r[i]), a, c) : bf_lo(r[i]), v1 = MIX2 ? fmaf(bf_hi(r[i]), a, c) : bf_hi(r[i]);
                    acc[0][jp * 8 + 2 * i] = C::ACC_INIT ? v0 : acc[0][jp * 8 + 2 * i] + v0;
                    acc[0][jp * 8 + 2 * i + 1] = C::ACC_INIT ? v1 : acc[0][jp * 8 + 2 * i + 1] + v1;
                }
            }
        };
        const float4 ac = residual();
        if (C::ACC_INIT) apply(ac);
        pdl_wait();
        TL(MIX2 ? 6 : 3, 0);
        gemm_mainloop<C>(s, wg, acc, MIX2 ? 6 : 3);
        TL(MIX2 ? 6 : 3, 1);
        if (!C::ACC_INIT) apply(ac);
        float sc0 = 1.f, sc1 = 1.f, of0 = 0.f, of1 = 0.f;
        if (!MIX2) {
            float s0 = 0.f, s1 = 0.f;
#pragma unroll
            for (int j = 0; j < 16; j++) { s0 += acc[0][4 * j] + acc[0][4 * j + 1]; s1 += acc[0][4 * j + 2] + acc[0][4 * j + 3]; }
            s0 += __shfl_xor_sync(0xffffffffu, s0, 1); s1 += __shfl_xor_sync(0xffffffffu, s1, 1);
            s0 += __shfl_xor_sync(0xffffffffu, s0, 2); s1 += __shfl_xor_sync(0xffffffffu, s1, 2);
            const float m0 = s0 * (1.f / 128), m1 = s1 * (1.f / 128);
            float q0 = 0.f, q1 = 0.f;
#pragma unroll
            for (int j = 0; j < 16; j++) {
                const float a = acc[0][4 * j] - m0, b = acc[0][4 * j + 1] - m0, c = acc[0][4 * j + 2] - m1, d = acc[0][4 * j + 3] - m1;
                q0 = fmaf(a, a, fmaf(b, b, q0)); q1 = fmaf(c, c, fmaf(d, d, q1));
            }
            q0 += __shfl_xor_sync(0xffffffffu, q0, 1); q1 += __shfl_xor_sync(0xffffffffu, q1, 1);
            q0 += __shfl_xor_sync(0xffffffffu, q0, 2); q1 += __shfl_xor_sync(0xffffffffu, q1, 2);
            const int wrow = tm * 128 + wg * 64 + warp * 16;
            if ((lane & 3) < 2) {
                const float m = (lane & 1) ? m1 : m0, q = (lane & 1) ? q1 : q0;
                const unsigned long long w = ((unsigned long long)(__float_as_uint(q) | 0x80000000u) << 32) | __float_as_uint(m);
                asm volatile("st.relaxed.gpu.global.u64 [%0], %1;" :: "l"(g_hpart + tn * SEQ + wrow + (lane >> 2) + (lane & 1) * 8), "l"(w) : "memory");
            }
            TL(3, 5);
            TKC(13);
            const unsigned long long* part = g_hpart + (lane >> 2) * SEQ + wrow + (lane & 3) * 4;
            unsigned long long t[4];
            int it = 0;
            bool ok;
            do {
                asm volatile("ld.relaxed.gpu.global.v2.u64 {%0, %1}, [%2];" : "=l"(t[0]), "=l"(t[1]) : "l"(part) : "memory");
                asm volatile("ld.relaxed.gpu.global.v2.u64 {%0, %1}, [%2];" : "=l"(t[2]), "=l"(t[3]) : "l"(part + 2) : "memory");
                ok = (long long)(t[0] & t[1] & t[2] & t[3]) < 0;
                if (++it > (1 << 20)) __trap();
            } while (!__all_sync(0xffffffffu, ok));
            TKC(14);
            float mt[4], qt[4];
#pragma unroll
            for (int i = 0; i < 4; i++) {
                const float mi = __uint_as_float((uint32_t)t[i]), qi = __uint_as_float((uint32_t)(t[i] >> 32) & 0x7FFFFFFFu);
                float m = mi;
                m += __shfl_xor_sync(0xffffffffu, m, 4); m += __shfl_xor_sync(0xffffffffu, m, 8); m += __shfl_xor_sync(0xffffffffu, m, 16);
                m *= 0.125f;
                float q = fmaf(128.f * (mi - m), mi - m, qi);
                q += __shfl_xor_sync(0xffffffffu, q, 4); q += __shfl_xor_sync(0xffffffffu, q, 8); q += __shfl_xor_sync(0xffffffffu, q, 16);
                mt[i] = m; qt[i] = q;
            }
            const int sel = (lane >> 2) & 3;
            const float mean = sel == 0 ? mt[0] : sel == 1 ? mt[1] : sel == 2 ? mt[2] : mt[3];
            const float var = (sel == 0 ? qt[0] : sel == 1 ? qt[1] : sel == 2 ? qt[2] : qt[3]) * (1.f / DM);
            const float r1 = rsqrtf(var + 1e-5f);
            const float r2 = rsqrtf(var * r1 * r1 + 1e-5f);
            const float scale = r1 * r2, off = -mean * scale;
            if (tn == 0 && lane < 16) g_rowln[wrow + 4 * (lane & 3) + sel] = make_float2(mean, 1.f / scale);
            const int ra = lane >> 2, src0 = ((ra & 3) << 2) | (ra >> 2);
            sc0 = __shfl_sync(0xffffffffu, scale, src0); of0 = __shfl_sync(0xffffffffu, off, src0);
            sc1 = __shfl_sync(0xffffffffu, scale, src0 + 2); of1 = __shfl_sync(0xffffffffu, off, src0 + 2);
        }
#pragma unroll
        for (int jp = 0; jp < 8; jp++) {
            const int chunk = jp * 2 + (lane >> 4);
            uint32_t r[4];
#pragma unroll
            for (int i = 0; i < 4; i++) {
                const float sc = (i & 1) ? sc1 : sc0, of = (i & 1) ? of1 : of0;
                const float v0 = acc[0][jp * 8 + 2 * i], v1 = acc[0][jp * 8 + 2 * i + 1];
                r[i] = MIX2 ? pack_bf16(v0, v1) : pack_bf16(fmaf(v0, sc, of), fmaf(v1, sc, of));
            }
            stmatrix_x4(stg + (chunk >> 3) * 16384 + (((chunk & 7) ^ (arow & 7)) << 4), r[0], r[1], r[2], r[3]);
            if ((jp & 3) == 3) hand_over(2 + (jp >> 2) * 2 + wg);
        }
        if (MIX2) TL(6, 5);
        TKC(15);
    }
}

struct Mix1Params { CUtensorMap hn, w1, out; const bf16* bias; const uint8_t* pf; };
struct Mix1Cfg {
    static constexpr int MB = 1, BN = 224, KSTEPS = 32, STAGES = 5, A_BYTES = 16384, B_BYTES = 28672;
    static constexpr int STAGE_BYTES = A_BYTES + B_BYTES, BIAS_OFF = STAGES * STAGE_BYTES, BAR_OFF = BIAS_OFF + 1024, SMEM = BAR_OFF + 128;
    static constexpr int AUX_COUNT = 1, PRE = MIX1_PRE;
    static constexpr int TLK = 5;
    static constexpr bool MC = MIX1_MC, PAIR = MC || MIX1_PAIR, ACC_INIT = false;
    static constexpr int SYNC_NS = MIX1_SYNC;
    static __device__ __forceinline__ void load_w(const Mix1Params& p, uint32_t sb, uint32_t bar, int k, int tm, int tn) {
        if (MC) tma_ld3_mc(sb + A_BYTES + (tm & 1) * (B_BYTES / 2), &p.w1, bar, 0, k * 64 + (tm & 1) * 32, tn * 7);
        else { tma_ld3(sb + A_BYTES, &p.w1, bar, 0, k * 64, tn * 7); tma_ld3(sb + A_BYTES + B_BYTES / 2, &p.w1, bar, 0, k * 64 + 32, tn * 7); }
    }
    static __device__ __forceinline__ void prefetch(const Mix1Params& p, int k) {}
    static __device__ __forceinline__ void load_x(const Mix1Params& p, uint32_t sb, uint32_t bar, int k, int tm, int tn) { tma_ld3(sb, &p.hn, bar, 0, k * 64, tm * 2); }
    static __device__ __forceinline__ void load_aux(const Mix1Params&, const GemmSmem&, int, int) {}
    static __device__ __forceinline__ uint32_t desc_a(uint32_t sb, int wg, int m, int kk) { return desc_lo(sb + wg * 8192 + kk * 2048, 8192); }
    static __device__ __forceinline__ uint32_t desc_b(uint32_t sb, int kk) { return desc_lo(sb + A_BYTES + (kk >> 1) * (B_BYTES / 2) + (kk & 1) * 1024, 2048); }
    static __device__ __forceinline__ void mma(float (&d)[112], uint32_t a, uint32_t b, int sc) { mma_mix1(d, a, b, sc); }
};
__global__ void __launch_bounds__(384, 1) mix1_kernel(const __grid_constant__ Mix1Params p) {
    using C = Mix1Cfg;
    extern __shared__ __align__(1024) uint8_t smem_raw[];
    TL(5, 4);
    const int tm = blockIdx.x & 7, tn = blockIdx.x >> 3;
    if (threadIdx.x == 0) { prefetch_map(&p.hn); prefetch_map(&p.w1); prefetch_map(&p.out); }
    float* sbias = reinterpret_cast<float*>(smem_raw + C::BIAS_OFF);
    const GemmSmem s = gemm_setup<C>(smem_raw);
    const int wgi = __shfl_sync(0xffffffffu, threadIdx.x >> 7, 0);
    if (wgi == 0) {
        reg_dealloc<40>();
        if (threadIdx.x < 32) {
            if (threadIdx.x == 0) gemm_producer<C>(s, p, tm, tn);
            __syncwarp();
#pragma unroll 1
            for (int i = 0; i < 14; i++) {
                const int b = i >> 1, wg = i & 1;
                named_bar(2 + i, 160);
                if (threadIdx.x == 0) tma_st3(&p.out, s.base + wg * 28672 + b * 4096, 0, tm * 128 + wg * 64, tn * 7 + b);
            }
            if (threadIdx.x == 0) { tma_st_commit(); tma_st_wait(); TL(5, 3); }
        } else if (PF_W2 && threadIdx.x >= 32 && threadIdx.x < 64) {
            pdl_wait();
            __nanosleep(PF_W2_DELAY);
            if (PF_W2 == 1) {
#pragma unroll 1
            for (int i = 0; i < 28; i++) {
                prefetch_line(p.pf + ((size_t)blockIdx.x * 896 + i * 32 + (threadIdx.x & 31)) * 128);
                __nanosleep(300);
            }
            } else {
#pragma unroll 1
            for (int i = 0; i < 4; i++) prefetch_line(p.pf + ((size_t)blockIdx.x * 128 + i * 32 + (threadIdx.x & 31)) * 128);
            }
        }
    } else {
        reg_alloc<232>();
        const int wg = wgi - 1, warp = (threadIdx.x >> 5) & 3, lane = threadIdx.x & 31;
        float acc[1][112];
        const int bi = threadIdx.x - 128;
        const bf16 bias = p.bias[tn * 224 + (bi < 224 ? bi : 0)];
        pdl_wait();
        pdl_launch();
        TL(5, 0);
        gemm_mainloop<C>(s, wg, acc, 5);
        TL(5, 1);
        if (bi < 224) sbias[bi] = __bfloat162float(bias);
        named_bar(1, 256);
        const int arow = warp * 16 + ((lane >> 3) & 1) * 8 + (lane & 7);
        const uint32_t stg = s.base + wg * 28672;
#pragma unroll
        for (int jp = 0; jp < 14; jp++) {
            float v[8];
#pragma unroll
            for (int h = 0; h < 2; h++) {
                const float2 bb = *reinterpret_cast<const float2*>(sbias + (jp * 2 + h) * 8 + (lane & 3) * 2);
#pragma unroll
                for (int i = 0; i < 4; i++) {
                    const float x = acc[0][jp * 8 + h * 4 + i] + ((i & 1) ? bb.y : bb.x);
                    const float inner = x * fmaf(x * x, 0.0356774081363f, 0.7978845608029f);
                    const float hx = 0.5f * x;
                    v[h * 4 + i] = fmaf(hx, tanh_fast(inner), hx);
                }
            }
            const int j = jp * 2 + (lane >> 4);
            const uint32_t addr = stg + (j >> 2) * 4096 + arow * 64 + (((j & 3) ^ ((arow >> 1) & 3)) << 4);
            stmatrix_x4(addr, pack_bf16(v[0], v[1]), pack_bf16(v[2], v[3]), pack_bf16(v[4], v[5]), pack_bf16(v[6], v[7]));
            if (jp & 1) hand_over(2 + (jp >> 1) * 2 + wg);
        }
        TL(5, 5);
    }
}

typedef CUresult (*EncodeFn)(CUtensorMap*, CUtensorMapDataType, cuuint32_t, void*, const cuuint64_t*, const cuuint64_t*, const cuuint32_t*,
                             const cuuint32_t*, CUtensorMapInterleave, CUtensorMapSwizzle, CUtensorMapL2promotion, CUtensorMapFloatOOBfill);
EncodeFn g_encode;

void make_map(CUtensorMap* m, const void* ptr, int rank, const uint64_t* dims, const uint64_t* strides_bytes, const uint32_t* box, CUtensorMapSwizzle swz) {
    cuuint64_t d[5], st[5]; cuuint32_t b[5], es[5];
    for (int i = 0; i < rank; i++) { d[i] = dims[i]; b[i] = box[i]; es[i] = 1; }
    for (int i = 0; i + 1 < rank; i++) st[i] = strides_bytes[i];
    CUresult r = g_encode(m, CU_TENSOR_MAP_DATA_TYPE_BFLOAT16, rank, const_cast<void*>(ptr), d, st, b, es, CU_TENSOR_MAP_INTERLEAVE_NONE, swz,
                          CU_TENSOR_MAP_L2_PROMOTION_L2_128B, CU_TENSOR_MAP_FLOAT_OOB_FILL_NONE);
    if (r != CUDA_SUCCESS) fprintf(stderr, "cuTensorMapEncodeTiled failed: %d\n", (int)r);
}
void map2d(CUtensorMap* m, const void* ptr, uint64_t cols, uint64_t rows, uint32_t bc, uint32_t br, CUtensorMapSwizzle swz) {
    uint64_t dims[2] = {cols, rows}, st[1] = {cols * 2}; uint32_t box[2] = {bc, br};
    make_map(m, ptr, 2, dims, st, box, swz);
}
void map3d(CUtensorMap* m, const void* ptr, uint64_t cols, uint64_t rows, uint32_t inner, uint32_t br, uint32_t nblk, CUtensorMapSwizzle swz) {
    uint64_t dims[3] = {inner, rows, cols / inner}, st[2] = {cols * 2, (uint64_t)inner * 2}; uint32_t box[3] = {inner, br, nblk};
    make_map(m, ptr, 3, dims, st, box, swz);
}

template <class... KArgs, class... Args>
void launch(void (*kern)(KArgs...), int grid, int block, int smem, bool pdl, bool pair, Args&&... args) {
    cudaLaunchConfig_t cfg = {};
    cfg.gridDim = dim3(grid); cfg.blockDim = dim3(block); cfg.dynamicSmemBytes = smem; cfg.stream = 0;
    cudaLaunchAttribute at[2];
    int n = 0;
    if (pdl) { at[n].id = cudaLaunchAttributeProgrammaticStreamSerialization; at[n].val.programmaticStreamSerializationAllowed = 1; n++; }
    if (pair) { at[n].id = cudaLaunchAttributeClusterDimension; at[n].val.clusterDim.x = 2; at[n].val.clusterDim.y = 1; at[n].val.clusterDim.z = 1; n++; }
    cfg.attrs = at; cfg.numAttrs = n;
    cudaError_t e = cudaLaunchKernelEx(&cfg, kern, KArgs(args)...);
    if (e != cudaSuccess) fprintf(stderr, "launch failed: %s\n", cudaGetErrorString(e));
}

struct HostState {
    bool ready;
    const void* key[9];
    QkvParams qkv; AttnParams attn; ResParams wo, mix2; Mix1Params mix1;
    bf16 *qkvp, *o, *hn, *u;
};
HostState g_hs;

}

#define USE_PDL 1

extern "C" void kernel_launch(void* const* d_in, const int* in_sizes, int n_in, void* d_out, int out_size) {
    const bf16* x = (const bf16*)d_in[0];
    const bf16* wqkv = (const bf16*)d_in[1];
    const bf16* wo = (const bf16*)d_in[2];
    const bf16* w1 = (const bf16*)d_in[4];
    const bf16* b1 = (const bf16*)d_in[5];
    const bf16* w2 = (const bf16*)d_in[6];
    const bf16* b2 = (const bf16*)d_in[7];
    HostState& hs = g_hs;
    bool same = hs.ready;
    for (int i = 0; i < 8 && same; i++) same = (hs.key[i] == d_in[i]);
    same = same && hs.key[8] == d_out;
    if (!same) {
        if (!g_encode) {
            void* fn = nullptr; cudaDriverEntryPointQueryResult qr;
            cudaGetDriverEntryPoint("cuTensorMapEncodeTiled", &fn, cudaEnableDefault, &qr);
            g_encode = (EncodeFn)fn;
            cudaFuncSetAttribute(qkv_kernel, cudaFuncAttributeMaxDynamicSharedMemorySize, QkvCfg::SMEM);
            cudaFuncSetAttribute(attn_kernel, cudaFuncAttributeMaxDynamicSharedMemorySize, AT_SMEM);
            cudaFuncSetAttribute(res_gemm_kernel<false>, cudaFuncAttributeMaxDynamicSharedMemorySize, ResCfg<false>::SMEM);
            cudaFuncSetAttribute(res_gemm_kernel<true>, cudaFuncAttributeMaxDynamicSharedMemorySize, ResCfg<true>::SMEM);
            cudaFuncSetAttribute(mix1_kernel, cudaFuncAttributeMaxDynamicSharedMemorySize, Mix1Cfg::SMEM);
        }
        cudaGetSymbolAddress((void**)&hs.qkvp, g_qkv); cudaGetSymbolAddress((void**)&hs.o, g_o);
        cudaGetSymbolAddress((void**)&hs.hn, g_hn); cudaGetSymbolAddress((void**)&hs.u, g_u);
        const CUtensorMapSwizzle S128 = CU_TENSOR_MAP_SWIZZLE_128B, S64 = CU_TENSOR_MAP_SWIZZLE_64B;
        map2d(&hs.qkv.x, x, DM, SEQ, 64, 256, S128);
        hs.qkv.xp = x; hs.qkv.wp = wqkv;
        {
            uint64_t dims[4] = {64, (uint64_t)DM, 3, 16}, st[3] = {3 * DM * 2, DM * 2, 128}; uint32_t box[4] = {64, 64, 3, 1};
            make_map(&hs.qkv.w, wqkv, 4, dims, st, box, S128);
        }
        map2d(&hs.qkv.out, hs.qkvp, HD, 3 * NH * SEQ, 32, 128, S64);
        hs.attn.kv = hs.qkv.out;
        map2d(&hs.attn.o, hs.o, DM, SEQ, 32, 16, S64); hs.attn.optr = hs.o;
        {
            uint64_t dims[3] = {(uint64_t)HD, (uint64_t)NH * SEQ, 3}, st[2] = {HD * 2, (uint64_t)NH * SEQ * HD * 2}; uint32_t box[3] = {32, 128, 2};
            make_map(&hs.attn.kv2, hs.qkvp, 3, dims, st, box, S64);
        }
        map2d(&hs.wo.a, hs.o, DM, SEQ, 64, ResCfg<false>::MC ? 64 : 128, S128);
        map3d(&hs.wo.b, wo, DM, DM, 64, 64, 2, S128);
        map2d(&hs.wo.res, x, DM, SEQ, 64, 128, S128);
        map2d(&hs.wo.out, hs.hn, DM, SEQ, 64, 64, S128);
        hs.wo.bias = nullptr;
        map3d(&hs.mix1.hn, hs.hn, DM, SEQ, 64, 64, 2, S128);
        map3d(&hs.mix1.w1, w1, FF, SEQ, 32, 32, 7, S64);
        hs.mix1.pf = (const uint8_t*)w2;
        hs.attn.pf_wo = (const uint8_t*)wo; hs.attn.pf_w1 = (const uint8_t*)w1; hs.attn.pf_x = (const uint8_t*)x;
        map3d(&hs.mix1.out, hs.u, FF, DM, 32, 64, 1, S64);
        hs.mix1.bias = b1;
        map3d(&hs.mix2.a, w2, SEQ, FF, 64, 64, ResCfg<true>::MC ? 1 : 2, S128);
        map2d(&hs.mix2.b, hs.u, FF, DM, 64, 128, S128);
        map2d(&hs.mix2.res, hs.hn, DM, SEQ, 64, 128, S128);
        map2d(&hs.mix2.out, d_out, DM, SEQ, 64, 64, S128);
        hs.mix2.bias = b2;
        for (int i = 0; i < 8; i++) hs.key[i] = d_in[i];
        hs.key[8] = d_out;
        hs.ready = true;
    }
    const bool pdl = USE_PDL;
    const int G = 128;
    launch(qkv_kernel, G, 384, QkvCfg::SMEM, false, QkvCfg::PAIR, hs.qkv);
    launch(attn_kernel, 128, 512, AT_SMEM, pdl, false, hs.attn);
    launch(res_gemm_kernel<false>, G, 384, ResCfg<false>::SMEM, pdl, ResCfg<false>::PAIR, hs.wo);
    launch(mix1_kernel, G, 384, Mix1Cfg::SMEM, pdl, Mix1Cfg::PAIR, hs.mix1);
    launch(res_gemm_kernel<true>, G, 384, ResCfg<true>::SMEM, pdl, ResCfg<true>::PAIR, hs.mix2);
}
```

```cpp
#include <cuda_runtime.h>
#include <cuda_bf16.h>
#include <cuda.h>
#include <stdint.h>
#include <stdio.h>

typedef __nv_bfloat16 bf16;

namespace {

#define SKEW 0
#define POLY_MASK_B POLY_MASK
#define POLY_MASK 0x12492449u
#define MIX1_MC true
#define MIX2_MC false
#define WO_MC false
#define MIX1_PAIR false
#define MIX2_PAIR true
#define WO_PAIR true
#define MIX2_MAP 1
#define WO_MAP 1
#define WO_SYNC 0
#define MIX1_SYNC 0
#define MIX2_SYNC 0
#define MIX1_PRE 2
#define WO_PRE 1
#define MIX2_PRE 1
#define PF_W1 4
#define PF_W2_DELAY 10000
#define WO_INIT true
#define MIX2_INIT true
#define O_DIRECT 1
#define PAIR_POLY 1
#define PMASK_A 0x4924
#define PMASK_B PMASK_A
#define ATTN_PIPE 1
#define QMASK_0 0xF0
#define QMASK_1 0xF0
#define QMASK_2 0xF0
#define QMASK_3 0xF0
#define EXP_FX 2
#define IMM_DESC 1
#define PF_X 0
#define PF_REV 3
#define PF_W2 2
constexpr int SEQ = 2048, DM = 1024, NH = 32, HD = 32, FF = 3584;

__device__ __align__(1024) bf16 g_qkv[3 * NH * SEQ * HD];
__device__ __align__(1024) bf16 g_o[SEQ * DM];
__device__ __align__(1024) bf16 g_hn[SEQ * DM];
__device__ __align__(1024) bf16 g_u[DM * FF];
__device__ uint32_t g_norm[3 * NH * 64];
__device__ float2 g_rowstat[SEQ];
__device__ float g_colsum[8 * 3 * DM];
__device__ float2 g_rowln[SEQ];
__device__ __align__(16) unsigned long long g_hpart[SEQ * 8];
__device__ uint32_t g_cnt_row[8], g_cnt_col[16];

#define TL(kern, slot)
#define AT(slot)

__device__ __forceinline__ uint32_t smem_u32(const void* p) { return (uint32_t)__cvta_generic_to_shared(p); }
__device__ __forceinline__ void mbar_init(uint32_t bar, uint32_t cnt) { asm volatile("mbarrier.init.shared::cta.b64 [%0], %1;" :: "r"(bar), "r"(cnt) : "memory"); }
__device__ __forceinline__ void mbar_expect_tx(uint32_t bar, uint32_t bytes) { asm volatile("mbarrier.arrive.expect_tx.shared::cta.b64 _, [%0], %1;" :: "r"(bar), "r"(bytes) : "memory"); }
__device__ __forceinline__ void mbar_arrive(uint32_t bar) { asm volatile("mbarrier.arrive.shared::cta.b64 _, [%0];" :: "r"(bar) : "memory"); }
__device__ __forceinline__ void mbar_wait(uint32_t bar, uint32_t parity) {
    asm volatile("{\n.reg .pred p;\nWAIT_%=:\nmbarrier.try_wait.parity.shared::cta.b64 p, [%0], %1;\n@p bra DONE_%=;\nbra WAIT_%=;\nDONE_%=:\n}" :: "r"(bar), "r"(parity) : "memory");
}
__device__ __forceinline__ void fence_barrier_init() { asm volatile("fence.mbarrier_init.release.cluster;" ::: "memory"); }
__device__ __forceinline__ void fence_proxy_async() { asm volatile("fence.proxy.async.shared::cta;" ::: "memory"); }
__device__ __forceinline__ void pdl_launch() { asm volatile("griddepcontrol.launch_dependents;" ::: "memory"); }
__device__ __forceinline__ void pdl_wait() { asm volatile("griddepcontrol.wait;" ::: "memory"); }
__device__ __forceinline__ void named_bar(int id, int n) { asm volatile("bar.sync %0, %1;" :: "r"(id), "r"(n) : "memory"); }
__device__ __forceinline__ void named_arrive(int id, int n) { asm volatile("bar.arrive %0, %1;" :: "r"(id), "r"(n) : "memory"); }
__device__ __forceinline__ void hand_over(int id) { fence_proxy_async(); named_arrive(id, 160); }
__device__ __forceinline__ void prefetch_map(const CUtensorMap* m) { asm volatile("prefetch.tensormap [%0];" :: "l"(m) : "memory"); }

__device__ __forceinline__ void tma_ld2(uint32_t dst, const CUtensorMap* m, uint32_t bar, int c0, int c1) {
    asm volatile("cp.async.bulk.tensor.2d.shared::cluster.global.mbarrier::complete_tx::bytes [%0], [%1, {%3, %4}], [%2];"
                 :: "r"(dst), "l"(m), "r"(bar), "r"(c0), "r"(c1) : "memory");
}
__device__ __forceinline__ void tma_ld3(uint32_t dst, const CUtensorMap* m, uint32_t bar, int c0, int c1, int c2) {
    asm volatile("cp.async.bulk.tensor.3d.shared::cluster.global.mbarrier::complete_tx::bytes [%0], [%1, {%3, %4, %5}], [%2];"
                 :: "r"(dst), "l"(m), "r"(bar), "r"(c0), "r"(c1), "r"(c2) : "memory");
}
__device__ __forceinline__ void tma_ld4(uint32_t dst, const CUtensorMap* m, uint32_t bar, int c0, int c1, int c2, int c3) {
    asm volatile("cp.async.bulk.tensor.4d.shared::cluster.global.mbarrier::complete_tx::bytes [%0], [%1, {%3, %4, %5, %6}], [%2];"
                 :: "r"(dst), "l"(m), "r"(bar), "r"(c0), "r"(c1), "r"(c2), "r"(c3) : "memory");
}
__device__ __forceinline__ void tma_ld3_mc(uint32_t dst, const CUtensorMap* m, uint32_t bar, int c0, int c1, int c2) {
    asm volatile("cp.async.bulk.tensor.3d.shared::cluster.global.mbarrier::complete_tx::bytes.multicast::cluster [%0], [%1, {%3, %4, %5}], [%2], %6;"
                 :: "r"(dst), "l"(m), "r"(bar), "r"(c0), "r"(c1), "r"(c2), "h"((uint16_t)3) : "memory");
}
__device__ __forceinline__ void tma_ld2_mc(uint32_t dst, const CUtensorMap* m, uint32_t bar, int c0, int c1) {
    asm volatile("cp.async.bulk.tensor.2d.shared::cluster.global.mbarrier::complete_tx::bytes.multicast::cluster [%0], [%1, {%3, %4}], [%2], %5;"
                 :: "r"(dst), "l"(m), "r"(bar), "r"(c0), "r"(c1), "h"((uint16_t)3) : "memory");
}
__device__ __forceinline__ void prefetch_line(const void* p) { asm volatile("prefetch.global.L2 [%0];" :: "l"(p)); }
__device__ __forceinline__ void l2_prefetch(const void* p, uint32_t bytes) { asm volatile("cp.async.bulk.prefetch.L2.global [%0], %1;" :: "l"(p), "r"(bytes) : "memory"); }
__device__ __forceinline__ uint32_t mapa(uint32_t addr, uint32_t cta) { uint32_t r; asm("mapa.shared::cluster.u32 %0, %1, %2;" : "=r"(r) : "r"(addr), "r"(cta)); return r; }
__device__ __forceinline__ void mbar_arrive_cluster(uint32_t bar) { asm volatile("mbarrier.arrive.shared::cluster.b64 _, [%0];" :: "r"(bar) : "memory"); }
__device__ __forceinline__ void cluster_arrive() { asm volatile("barrier.cluster.arrive.relaxed.aligned;" ::: "memory"); }
__device__ __forceinline__ void cluster_wait() { asm volatile("barrier.cluster.wait.aligned;" ::: "memory"); }
__device__ __forceinline__ void tma_st2(const CUtensorMap* m, uint32_t src, int c0, int c1) {
    asm volatile("cp.async.bulk.tensor.2d.global.shared::cta.bulk_group [%0, {%2, %3}], [%1];" :: "l"(m), "r"(src), "r"(c0), "r"(c1) : "memory");
}
__device__ __forceinline__ void tma_st3(const CUtensorMap* m, uint32_t src, int c0, int c1, int c2) {
    asm volatile("cp.async.bulk.tensor.3d.global.shared::cta.bulk_group [%0, {%2, %3, %4}], [%1];" :: "l"(m), "r"(src), "r"(c0), "r"(c1), "r"(c2) : "memory");
}
__device__ __forceinline__ void tma_st_commit() { asm volatile("cp.async.bulk.commit_group;" ::: "memory"); }
__device__ __forceinline__ void tma_st_wait() { asm volatile("cp.async.bulk.wait_group.read 0;" ::: "memory"); }

__device__ __forceinline__ void wg_fence() { asm volatile("wgmma.fence.sync.aligned;" ::: "memory"); }
__device__ __forceinline__ void wg_commit() { asm volatile("wgmma.commit_group.sync.aligned;" ::: "memory"); }
template <int N> __device__ __forceinline__ void wg_wait() { asm volatile("wgmma.wait_group.sync.aligned %0;" :: "n"(N) : "memory"); }
template <int R> __device__ __forceinline__ void reg_alloc() { asm volatile("setmaxnreg.inc.sync.aligned.u32 %0;" :: "n"(R)); }
template <int R> __device__ __forceinline__ void reg_dealloc() { asm volatile("setmaxnreg.dec.sync.aligned.u32 %0;" :: "n"(R)); }
template <int N> __device__ __forceinline__ void fence_regs(float (&d)[N]) {
#pragma unroll
    for (int i = 0; i < N; i++) asm volatile("" : "+f"(d[i]) :: "memory");
}

__device__ __forceinline__ uint32_t desc_lo(uint32_t addr, uint32_t lbo) { return ((addr & 0x3FFFFu) >> 4) | ((lbo >> 4) << 16); }
__device__ __forceinline__ uint32_t pack_bf16(float lo, float hi) { uint32_t d; asm("cvt.rn.bf16x2.f32 %0, %1, %2;" : "=r"(d) : "f"(hi), "f"(lo)); return d; }
__device__ __forceinline__ float bf_lo(uint32_t v) { return __uint_as_float(v << 16); }
__device__ __forceinline__ float bf_hi(uint32_t v) { return __uint_as_float(v & 0xFFFF0000u); }
__device__ __forceinline__ void stmatrix_x4(uint32_t addr, uint32_t r0, uint32_t r1, uint32_t r2, uint32_t r3) {
    asm volatile("stmatrix.sync.aligned.m8n8.x4.shared.b16 [%0], {%1, %2, %3, %4};" :: "r"(addr), "r"(r0), "r"(r1), "r"(r2), "r"(r3) : "memory");
}
__device__ __forceinline__ void ldmatrix_x4(uint32_t addr, uint32_t (&r)[4]) {
    asm volatile("ldmatrix.sync.aligned.m8n8.x4.shared.b16 {%0, %1, %2, %3}, [%4];" : "=r"(r[0]), "=r"(r[1]), "=r"(r[2]), "=r"(r[3]) : "r"(addr) : "memory");
}
__device__ __forceinline__ float ex2(float x) { float y; asm("ex2.approx.ftz.f32 %0, %1;" : "=f"(y) : "f"(x)); return y; }
__device__ __forceinline__ float tanh_fast(float x) { float y; asm("tanh.approx.f32 %0, %1;" : "=f"(y) : "f"(x)); return y; }

__device__ __forceinline__ void mma_qkv(float (&d)[96], uint32_t alo, uint32_t blo, int scale_d) {
    asm volatile("{\n.reg .pred p;\n.reg .b64 da, db;\nsetp.ne.b32 p, %98, 0;\nmov.b64 da, {%96, 0x40000040};\nmov.b64 db, {%97, 0x40000040};\n"
        "wgmma.mma_async.sync.aligned.m64n192k16.f32.bf16.bf16 {"
        "%0, %1, %2, %3, %4, %5, %6, %7, %8, %9, %10, %11, %12, %13, %14, %15, %16, %17, %18, %19, %20, %21, %22, %23, %24, %25, %26, %27, %28, %29, %30, %31,  "
        "%32, %33, %34, %35, %36, %37, %38, %39, %40, %41, %42, %43, %44, %45, %46, %47, %48, %49, %50, %51, %52, %53, %54, %55, %56, %57, %58, %59, %60, %61,  "
        "%62, %63, %64, %65, %66, %67, %68, %69, %70, %71, %72, %73, %74, %75, %76, %77, %78, %79, %80, %81, %82, %83, %84, %85, %86, %87, %88, %89, %90, %91,  "
        "%92, %93, %94, %95 "
        "}, da, db, p, 1, 1, 0, 1;\n}\n"
        : "+f"(d[0]), "+f"(d[1]), "+f"(d[2]), "+f"(d[3]), "+f"(d[4]), "+f"(d[5]), "+f"(d[6]), "+f"(d[7]), "+f"(d[8]), "+f"(d[9]), "+f"(d[10]), "+f"(d[11]),
          "+f"(d[12]), "+f"(d[13]), "+f"(d[14]), "+f"(d[15]), "+f"(d[16]), "+f"(d[17]), "+f"(d[18]), "+f"(d[19]), "+f"(d[20]), "+f"(d[21]), "+f"(d[22]),
          "+f"(d[23]), "+f"(d[24]), "+f"(d[25]), "+f"(d[26]), "+f"(d[27]), "+f"(d[28]), "+f"(d[29]), "+f"(d[30]), "+f"(d[31]), "+f"(d[32]), "+f"(d[33]),
          "+f"(d[34]), "+f"(d[35]), "+f"(d[36]), "+f"(d[37]), "+f"(d[38]), "+f"(d[39]), "+f"(d[40]), "+f"(d[41]), "+f"(d[42]), "+f"(d[43]), "+f"(d[44]),
          "+f"(d[45]), "+f"(d[46]), "+f"(d[47]), "+f"(d[48]), "+f"(d[49]), "+f"(d[50]), "+f"(d[51]), "+f"(d[52]), "+f"(d[53]), "+f"(d[54]), "+f"(d[55]),
          "+f"(d[56]), "+f"(d[57]), "+f"(d[58]), "+f"(d[59]), "+f"(d[60]), "+f"(d[61]), "+f"(d[62]), "+f"(d[63]), "+f"(d[64]), "+f"(d[65]), "+f"(d[66]),
          "+f"(d[67]), "+f"(d[68]), "+f"(d[69]), "+f"(d[70]), "+f"(d[71]), "+f"(d[72]), "+f"(d[73]), "+f"(d[74]), "+f"(d[75]), "+f"(d[76]), "+f"(d[77]),
          "+f"(d[78]), "+f"(d[79]), "+f"(d[80]), "+f"(d[81]), "+f"(d[82]), "+f"(d[83]), "+f"(d[84]), "+f"(d[85]), "+f"(d[86]), "+f"(d[87]), "+f"(d[88]),
          "+f"(d[89]), "+f"(d[90]), "+f"(d[91]), "+f"(d[92]), "+f"(d[93]), "+f"(d[94]), "+f"(d[95])
        : "r"(alo), "r"(blo), "r"(scale_d));
}
__device__ __forceinline__ void mma_wo(float (&d)[64], uint32_t alo, uint32_t blo, int scale_d) {
    asm volatile("{\n.reg .pred p;\n.reg .b64 da, db;\nsetp.ne.b32 p, %66, 0;\nmov.b64 da, {%64, 0x40000040};\nmov.b64 db, {%65, 0x40000040};\n"
        "wgmma.mma_async.sync.aligned.m64n128k16.f32.bf16.bf16 {"
        "%0, %1, %2, %3, %4, %5, %6, %7, %8, %9, %10, %11, %12, %13, %14, %15, %16, %17, %18, %19, %20, %21, %22, %23, %24, %25, %26, %27, %28, %29, %30, %31,  "
        "%32, %33, %34, %35, %36, %37, %38, %39, %40, %41, %42, %43, %44, %45, %46, %47, %48, %49, %50, %51, %52, %53, %54, %55, %56, %57, %58, %59, %60, %61,  "
        "%62, %63 "
        "}, da, db, p, 1, 1, 0, 1;\n}\n"
        : "+f"(d[0]), "+f"(d[1]), "+f"(d[2]), "+f"(d[3]), "+f"(d[4]), "+f"(d[5]), "+f"(d[6]), "+f"(d[7]), "+f"(d[8]), "+f"(d[9]), "+f"(d[10]), "+f"(d[11]),
          "+f"(d[12]), "+f"(d[13]), "+f"(d[14]), "+f"(d[15]), "+f"(d[16]), "+f"(d[17]), "+f"(d[18]), "+f"(d[19]), "+f"(d[20]), "+f"(d[21]), "+f"(d[22]),
          "+f"(d[23]), "+f"(d[24]), "+f"(d[25]), "+f"(d[26]), "+f"(d[27]), "+f"(d[28]), "+f"(d[29]), "+f"(d[30]), "+f"(d[31]), "+f"(d[32]), "+f"(d[33]),
          "+f"(d[34]), "+f"(d[35]), "+f"(d[36]), "+f"(d[37]), "+f"(d[38]), "+f"(d[39]), "+f"(d[40]), "+f"(d[41]), "+f"(d[42]), "+f"(d[43]), "+f"(d[44]),
          "+f"(d[45]), "+f"(d[46]), "+f"(d[47]), "+f"(d[48]), "+f"(d[49]), "+f"(d[50]), "+f"(d[51]), "+f"(d[52]), "+f"(d[53]), "+f"(d[54]), "+f"(d[55]),
          "+f"(d[56]), "+f"(d[57]), "+f"(d[58]), "+f"(d[59]), "+f"(d[60]), "+f"(d[61]), "+f"(d[62]), "+f"(d[63])
        : "r"(alo), "r"(blo), "r"(scale_d));
}
__device__ __forceinline__ void mma_mix2(float (&d)[64], uint32_t alo, uint32_t blo, int scale_d) {
    asm volatile("{\n.reg .pred p;\n.reg .b64 da, db;\nsetp.ne.b32 p, %66, 0;\nmov.b64 da, {%64, 0x40000040};\nmov.b64 db, {%65, 0x40000040};\n"
        "wgmma.mma_async.sync.aligned.m64n128k16.f32.bf16.bf16 {"
        "%0, %1, %2, %3, %4, %5, %6, %7, %8, %9, %10, %11, %12, %13, %14, %15, %16, %17, %18, %19, %20, %21, %22, %23, %24, %25, %26, %27, %28, %29, %30, %31,  "
        "%32, %33, %34, %35, %36, %37, %38, %39, %40, %41, %42, %43, %44, %45, %46, %47, %48, %49, %50, %51, %52, %53, %54, %55, %56, %57, %58, %59, %60, %61,  "
        "%62, %63 "
        "}, da, db, p, 1, 1, 1, 0;\n}\n"
        : "+f"(d[0]), "+f"(d[1]), "+f"(d[2]), "+f"(d[3]), "+f"(d[4]), "+f"(d[5]), "+f"(d[6]), "+f"(d[7]), "+f"(d[8]), "+f"(d[9]), "+f"(d[10]), "+f"(d[11]),
          "+f"(d[12]), "+f"(d[13]), "+f"(d[14]), "+f"(d[15]), "+f"(d[16]), "+f"(d[17]), "+f"(d[18]), "+f"(d[19]), "+f"(d[20]), "+f"(d[21]), "+f"(d[22]),
          "+f"(d[23]), "+f"(d[24]), "+f"(d[25]), "+f"(d[26]), "+f"(d[27]), "+f"(d[28]), "+f"(d[29]), "+f"(d[30]), "+f"(d[31]), "+f"(d[32]), "+f"(d[33]),
          "+f"(d[34]), "+f"(d[35]), "+f"(d[36]), "+f"(d[37]), "+f"(d[38]), "+f"(d[39]), "+f"(d[40]), "+f"(d[41]), "+f"(d[42]), "+f"(d[43]), "+f"(d[44]),
          "+f"(d[45]), "+f"(d[46]), "+f"(d[47]), "+f"(d[48]), "+f"(d[49]), "+f"(d[50]), "+f"(d[51]), "+f"(d[52]), "+f"(d[53]), "+f"(d[54]), "+f"(d[55]),
          "+f"(d[56]), "+f"(d[57]), "+f"(d[58]), "+f"(d[59]), "+f"(d[60]), "+f"(d[61]), "+f"(d[62]), "+f"(d[63])
        : "r"(alo), "r"(blo), "r"(scale_d));
}
__device__ __forceinline__ void mma_mix1(float (&d)[112], uint32_t alo, uint32_t blo, int scale_d) {
    asm volatile("{\n.reg .pred p;\n.reg .b64 da, db;\nsetp.ne.b32 p, %114, 0;\nmov.b64 da, {%112, 0x40000040};\nmov.b64 db, {%113, 0x80000020};\n"
        "wgmma.mma_async.sync.aligned.m64n224k16.f32.bf16.bf16 {"
        "%0, %1, %2, %3, %4, %5, %6, %7, %8, %9, %10, %11, %12, %13, %14, %15, %16, %17, %18, %19, %20, %21, %22, %23, %24, %25, %26, %27, %28, %29, %30, %31,  "
        "%32, %33, %34, %35, %36, %37, %38, %39, %40, %41, %42, %43, %44, %45, %46, %47, %48, %49, %50, %51, %52, %53, %54, %55, %56, %57, %58, %59, %60, %61,  "
        "%62, %63, %64, %65, %66, %67, %68, %69, %70, %71, %72, %73, %74, %75, %76, %77, %78, %79, %80, %81, %82, %83, %84, %85, %86, %87, %88, %89, %90, %91,  "
        "%92, %93, %94, %95, %96, %97, %98, %99, %100, %101, %102, %103, %104, %105, %106, %107, %108, %109, %110, %111 "
        "}, da, db, p, 1, 1, 1, 1;\n}\n"
        : "+f"(d[0]), "+f"(d[1]), "+f"(d[2]), "+f"(d[3]), "+f"(d[4]), "+f"(d[5]), "+f"(d[6]), "+f"(d[7]), "+f"(d[8]), "+f"(d[9]), "+f"(d[10]), "+f"(d[11]),
          "+f"(d[12]), "+f"(d[13]), "+f"(d[14]), "+f"(d[15]), "+f"(d[16]), "+f"(d[17]), "+f"(d[18]), "+f"(d[19]), "+f"(d[20]), "+f"(d[21]), "+f"(d[22]),
          "+f"(d[23]), "+f"(d[24]), "+f"(d[25]), "+f"(d[26]), "+f"(d[27]), "+f"(d[28]), "+f"(d[29]), "+f"(d[30]), "+f"(d[31]), "+f"(d[32]), "+f"(d[33]),
          "+f"(d[34]), "+f"(d[35]), "+f"(d[36]), "+f"(d[37]), "+f"(d[38]), "+f"(d[39]), "+f"(d[40]), "+f"(d[41]), "+f"(d[42]), "+f"(d[43]), "+f"(d[44]),
          "+f"(d[45]), "+f"(d[46]), "+f"(d[47]), "+f"(d[48]), "+f"(d[49]), "+f"(d[50]), "+f"(d[51]), "+f"(d[52]), "+f"(d[53]), "+f"(d[54]), "+f"(d[55]),
          "+f"(d[56]), "+f"(d[57]), "+f"(d[58]), "+f"(d[59]), "+f"(d[60]), "+f"(d[61]), "+f"(d[62]), "+f"(d[63]), "+f"(d[64]), "+f"(d[65]), "+f"(d[66]),
          "+f"(d[67]), "+f"(d[68]), "+f"(d[69]), "+f"(d[70]), "+f"(d[71]), "+f"(d[72]), "+f"(d[73]), "+f"(d[74]), "+f"(d[75]), "+f"(d[76]), "+f"(d[77]),
          "+f"(d[78]), "+f"(d[79]), "+f"(d[80]), "+f"(d[81]), "+f"(d[82]), "+f"(d[83]), "+f"(d[84]), "+f"(d[85]), "+f"(d[86]), "+f"(d[87]), "+f"(d[88]),
          "+f"(d[89]), "+f"(d[90]), "+f"(d[91]), "+f"(d[92]), "+f"(d[93]), "+f"(d[94]), "+f"(d[95]), "+f"(d[96]), "+f"(d[97]), "+f"(d[98]), "+f"(d[99]),
          "+f"(d[100]), "+f"(d[101]), "+f"(d[102]), "+f"(d[103]), "+f"(d[104]), "+f"(d[105]), "+f"(d[106]), "+f"(d[107]), "+f"(d[108]), "+f"(d[109]),
          "+f"(d[110]), "+f"(d[111])
        : "r"(alo), "r"(blo), "r"(scale_d));
}
__device__ __forceinline__ void mma_qk0(float (&d)[32], uint32_t alo, uint32_t blo) {
    asm volatile("{\n.reg .pred p;\n.reg .b64 da, db;\nsetp.ne.b32 p, 0, 0;\nmov.b64 da, {%32, 0x80000020};\nmov.b64 db, {%33, 0x80000020};\n"
        "wgmma.mma_async.sync.aligned.m64n64k16.f32.bf16.bf16 {"
        "%0, %1, %2, %3, %4, %5, %6, %7, %8, %9, %10, %11, %12, %13, %14, %15, %16, %17, %18, %19, %20, %21, %22, %23, %24, %25, %26, %27, %28, %29, %30, %31 "
        "}, da, db, p, 1, 1, 0, 0;\n}\n"
        : "=f"(d[0]), "=f"(d[1]), "=f"(d[2]), "=f"(d[3]), "=f"(d[4]), "=f"(d[5]), "=f"(d[6]), "=f"(d[7]), "=f"(d[8]), "=f"(d[9]), "=f"(d[10]), "=f"(d[11]),
          "=f"(d[12]), "=f"(d[13]), "=f"(d[14]), "=f"(d[15]), "=f"(d[16]), "=f"(d[17]), "=f"(d[18]), "=f"(d[19]), "=f"(d[20]), "=f"(d[21]), "=f"(d[22]),
          "=f"(d[23]), "=f"(d[24]), "=f"(d[25]), "=f"(d[26]), "=f"(d[27]), "=f"(d[28]), "=f"(d[29]), "=f"(d[30]), "=f"(d[31])
        : "r"(alo), "r"(blo));
}
__device__ __forceinline__ void mma_qk1(float (&d)[32], uint32_t alo, uint32_t blo, int scale_d) {
    asm volatile("{\n.reg .pred p;\n.reg .b64 da, db;\nsetp.ne.b32 p, %34, 0;\nmov.b64 da, {%32, 0x80000020};\nmov.b64 db, {%33, 0x80000020};\n"
        "wgmma.mma_async.sync.aligned.m64n64k16.f32.bf16.bf16 {"
        "%0, %1, %2, %3, %4, %5, %6, %7, %8, %9, %10, %11, %12, %13, %14, %15, %16, %17, %18, %19, %20, %21, %22, %23, %24, %25, %26, %27, %28, %29, %30, %31 "
        "}, da, db, p, 1, 1, 0, 0;\n}\n"
        : "+f"(d[0]), "+f"(d[1]), "+f"(d[2]), "+f"(d[3]), "+f"(d[4]), "+f"(d[5]), "+f"(d[6]), "+f"(d[7]), "+f"(d[8]), "+f"(d[9]), "+f"(d[10]), "+f"(d[11]),
          "+f"(d[12]), "+f"(d[13]), "+f"(d[14]), "+f"(d[15]), "+f"(d[16]), "+f"(d[17]), "+f"(d[18]), "+f"(d[19]), "+f"(d[20]), "+f"(d[21]), "+f"(d[22]),
          "+f"(d[23]), "+f"(d[24]), "+f"(d[25]), "+f"(d[26]), "+f"(d[27]), "+f"(d[28]), "+f"(d[29]), "+f"(d[30]), "+f"(d[31])
        : "r"(alo), "r"(blo), "r"(scale_d));
}
__device__ __forceinline__ void mma_qkw0(float (&d)[64], uint32_t alo, uint32_t blo) {
    asm volatile("{\n.reg .pred p;\n.reg .b64 da, db;\nsetp.ne.b32 p, 0, 0;\nmov.b64 da, {%64, 0x80000020};\nmov.b64 db, {%65, 0x80000020};\n"
        "wgmma.mma_async.sync.aligned.m64n128k16.f32.bf16.bf16 {"
        "%0, %1, %2, %3, %4, %5, %6, %7, %8, %9, %10, %11, %12, %13, %14, %15, %16, %17, %18, %19, %20, %21, %22, %23, %24, %25, %26, %27, %28, %29, %30, %31,  "
        "%32, %33, %34, %35, %36, %37, %38, %39, %40, %41, %42, %43, %44, %45, %46, %47, %48, %49, %50, %51, %52, %53, %54, %55, %56, %57, %58, %59, %60, %61,  "
        "%62, %63 "
        "}, da, db, p, 1, 1, 0, 0;\n}\n"
        : "=f"(d[0]), "=f"(d[1]), "=f"(d[2]), "=f"(d[3]), "=f"(d[4]), "=f"(d[5]), "=f"(d[6]), "=f"(d[7]), "=f"(d[8]), "=f"(d[9]), "=f"(d[10]), "=f"(d[11]),
          "=f"(d[12]), "=f"(d[13]), "=f"(d[14]), "=f"(d[15]), "=f"(d[16]), "=f"(d[17]), "=f"(d[18]), "=f"(d[19]), "=f"(d[20]), "=f"(d[21]), "=f"(d[22]),
          "=f"(d[23]), "=f"(d[24]), "=f"(d[25]), "=f"(d[26]), "=f"(d[27]), "=f"(d[28]), "=f"(d[29]), "=f"(d[30]), "=f"(d[31]), "=f"(d[32]), "=f"(d[33]),
          "=f"(d[34]), "=f"(d[35]), "=f"(d[36]), "=f"(d[37]), "=f"(d[38]), "=f"(d[39]), "=f"(d[40]), "=f"(d[41]), "=f"(d[42]), "=f"(d[43]), "=f"(d[44]),
          "=f"(d[45]), "=f"(d[46]), "=f"(d[47]), "=f"(d[48]), "=f"(d[49]), "=f"(d[50]), "=f"(d[51]), "=f"(d[52]), "=f"(d[53]), "=f"(d[54]), "=f"(d[55]),
          "=f"(d[56]), "=f"(d[57]), "=f"(d[58]), "=f"(d[59]), "=f"(d[60]), "=f"(d[61]), "=f"(d[62]), "=f"(d[63])
        : "r"(alo), "r"(blo));
}
__device__ __forceinline__ void mma_qkw1(float (&d)[64], uint32_t alo, uint32_t blo, int scale_d) {
    asm volatile("{\n.reg .pred p;\n.reg .b64 da, db;\nsetp.ne.b32 p, %66, 0;\nmov.b64 da, {%64, 0x80000020};\nmov.b64 db, {%65, 0x80000020};\n"
        "wgmma.mma_async.sync.aligned.m64n128k16.f32.bf16.bf16 {"
        "%0, %1, %2, %3, %4, %5, %6, %7, %8, %9, %10, %11, %12, %13, %14, %15, %16, %17, %18, %19, %20, %21, %22, %23, %24, %25, %26, %27, %28, %29, %30, %31,  "
        "%32, %33, %34, %35, %36, %37, %38, %39, %40, %41, %42, %43, %44, %45, %46, %47, %48, %49, %50, %51, %52, %53, %54, %55, %56, %57, %58, %59, %60, %61,  "
        "%62, %63 "
        "}, da, db, p, 1, 1, 0, 0;\n}\n"
        : "+f"(d[0]), "+f"(d[1]), "+f"(d[2]), "+f"(d[3]), "+f"(d[4]), "+f"(d[5]), "+f"(d[6]), "+f"(d[7]), "+f"(d[8]), "+f"(d[9]), "+f"(d[10]), "+f"(d[11]),
          "+f"(d[12]), "+f"(d[13]), "+f"(d[14]), "+f"(d[15]), "+f"(d[16]), "+f"(d[17]), "+f"(d[18]), "+f"(d[19]), "+f"(d[20]), "+f"(d[21]), "+f"(d[22]),
          "+f"(d[23]), "+f"(d[24]), "+f"(d[25]), "+f"(d[26]), "+f"(d[27]), "+f"(d[28]), "+f"(d[29]), "+f"(d[30]), "+f"(d[31]), "+f"(d[32]), "+f"(d[33]),
          "+f"(d[34]), "+f"(d[35]), "+f"(d[36]), "+f"(d[37]), "+f"(d[38]), "+f"(d[39]), "+f"(d[40]), "+f"(d[41]), "+f"(d[42]), "+f"(d[43]), "+f"(d[44]),
          "+f"(d[45]), "+f"(d[46]), "+f"(d[47]), "+f"(d[48]), "+f"(d[49]), "+f"(d[50]), "+f"(d[51]), "+f"(d[52]), "+f"(d[53]), "+f"(d[54]), "+f"(d[55]),
          "+f"(d[56]), "+f"(d[57]), "+f"(d[58]), "+f"(d[59]), "+f"(d[60]), "+f"(d[61]), "+f"(d[62]), "+f"(d[63])
        : "r"(alo), "r"(blo), "r"(scale_d));
}
__device__ __forceinline__ void mma_pv(float (&d)[20], uint32_t a0, uint32_t a1, uint32_t a2, uint32_t a3, uint32_t blo, int scale_d) {
    asm volatile("{\n.reg .pred p;\n.reg .b64 da, db;\nsetp.ne.b32 p, %25, 0;\nmov.b64 db, {%24, 0x80000020};\n"
        "wgmma.mma_async.sync.aligned.m64n40k16.f32.bf16.bf16 {"
        "%0, %1, %2, %3, %4, %5, %6, %7, %8, %9, %10, %11, %12, %13, %14, %15, %16, %17, %18, %19 "
        "}, {%20, %21, %22, %23}, db, p, 1, 1, 1;\n}\n"
        : "+f"(d[0]), "+f"(d[1]), "+f"(d[2]), "+f"(d[3]), "+f"(d[4]), "+f"(d[5]), "+f"(d[6]), "+f"(d[7]), "+f"(d[8]), "+f"(d[9]), "+f"(d[10]), "+f"(d[11]),
          "+f"(d[12]), "+f"(d[13]), "+f"(d[14]), "+f"(d[15]), "+f"(d[16]), "+f"(d[17]), "+f"(d[18]), "+f"(d[19])
        : "r"(a0), "r"(a1), "r"(a2), "r"(a3), "r"(blo), "r"(scale_d));
}

__device__ __forceinline__ float warp_sum(float v) {
#pragma unroll
    for (int o = 16; o > 0; o >>= 1) v += __shfl_xor_sync(0xffffffffu, v, o);
    return v;
}

struct GemmSmem { uint32_t base, full0, empty0, aux; };

template <class C>
__device__ __forceinline__ GemmSmem gemm_setup(uint8_t* smem_raw) {
    GemmSmem s;
    s.base = smem_u32(smem_raw);
    s.full0 = s.base + C::BAR_OFF; s.empty0 = s.full0 + 8 * C::STAGES; s.aux = s.empty0 + 8 * C::STAGES;
    if (threadIdx.x == 0) {
        if (s.base & 1023) __trap();
        for (int i = 0; i < C::STAGES; i++) { mbar_init(s.full0 + 8 * i, 1); mbar_init(s.empty0 + 8 * i, C::MC ? 16 : 8); }
        mbar_init(s.aux, C::AUX_COUNT);
        fence_barrier_init();
    }
    __syncthreads();
    if (C::MC) { cluster_arrive(); cluster_wait(); }
    return s;
}

#define TK(slot)
#define TKC(slot)
template <class C, class P>
__device__ __forceinline__ void gemm_producer(const GemmSmem& s, const P& p, int tm, int tn) {
    TK(8);
    if (C::ACC_INIT) C::load_aux(p, s, tm, tn);
#pragma unroll 1
    for (int k = 0; k < C::PRE; k++) {
        mbar_expect_tx(s.full0 + 8 * k, C::STAGE_BYTES);
        C::load_w(p, s.base + k * C::STAGE_BYTES, s.full0 + 8 * k, k, tm, tn);
    }
    TK(9);
    pdl_wait();
    TK(10);
#pragma unroll 1
    for (int k = 0; k < C::STAGES; k++) {
        if (k >= C::PRE) mbar_expect_tx(s.full0 + 8 * k, C::STAGE_BYTES);
        C::load_x(p, s.base + k * C::STAGE_BYTES, s.full0 + 8 * k, k, tm, tn);
        if (k >= C::PRE) C::load_w(p, s.base + k * C::STAGE_BYTES, s.full0 + 8 * k, k, tm, tn);
    }
    TK(11);
    if (!C::ACC_INIT) C::load_aux(p, s, tm, tn);
    int st = 0; uint32_t ph = 0;
#pragma unroll 1
    for (int k = C::STAGES; k < C::KSTEPS; k++) {
        mbar_wait(s.empty0 + 8 * st, ph);
        mbar_expect_tx(s.full0 + 8 * st, C::STAGE_BYTES);
        C::load_x(p, s.base + st * C::STAGE_BYTES, s.full0 + 8 * st, k, tm, tn);
        C::load_w(p, s.base + st * C::STAGE_BYTES, s.full0 + 8 * st, k, tm, tn);
        C::prefetch(p, k);
        if (++st == C::STAGES) { st = 0; ph ^= 1; }
    }
}

template <class C>
__device__ __forceinline__ void gemm_mainloop(const GemmSmem& s, int wg, float (&acc)[C::MB][C::BN / 2], int tlk = 0) {
    const int lane = threadIdx.x & 31;
    if constexpr (C::SYNC_NS > 0) {
        unsigned long long t0, t1; asm volatile("mov.u64 %0, %%globaltimer;" : "=l"(t0));
        do { asm volatile("mov.u64 %0, %%globaltimer;" : "=l"(t1)); } while (t1 - t0 < C::SYNC_NS);
    }
    int st = 0; uint32_t ph = 0;
    int prev = 0;
    const uint32_t rel0 = C::MC ? mapa(s.empty0, lane & 1) : s.empty0;
#pragma unroll
    for (int m = 0; m < C::MB; m++) fence_regs(acc[m]);
#pragma unroll 1
    for (int k = 0; k < C::KSTEPS; k++) {
        mbar_wait(s.full0 + 8 * st, ph);
        const uint32_t sb = s.base + st * C::STAGE_BYTES;
        wg_fence();
#pragma unroll
        for (int kk = 0; kk < 4; kk++) {
#pragma unroll
            for (int m = 0; m < C::MB; m++) C::mma(acc[m], C::desc_a(sb, wg, m, kk), C::desc_b(sb, kk), C::ACC_INIT || (k | kk) != 0);
        }
        wg_commit();
        if (k > 0) {
            wg_wait<1>();
            if (k <= C::KSTEPS - C::STAGES) {
                if (C::MC) { if (lane < 2) mbar_arrive_cluster(rel0 + 8 * prev); }
                else if (lane == 0) mbar_arrive(rel0 + 8 * prev);
            }
        }
        prev = st;
        if (++st == C::STAGES) { st = 0; ph ^= 1; }
    }
    wg_wait<0>();
#pragma unroll
    for (int m = 0; m < C::MB; m++) fence_regs(acc[m]);
}

struct QkvParams { CUtensorMap x, w, out; const bf16* xp; const bf16* wp; };
struct QkvCfg {
    static constexpr int MB = 2, BN = 192, KSTEPS = 16, STAGES = 4, A_BYTES = 32768, B_BYTES = 24576;
    static constexpr int STAGE_BYTES = A_BYTES + B_BYTES, BAR_OFF = STAGES * STAGE_BYTES, AUX_OFF = BAR_OFF + 128, SMEM = AUX_OFF + 2816;
    static constexpr int AUX_COUNT = 3, PRE = STAGES;
    static constexpr int TLK = 1;
    static constexpr bool MC = false, PAIR = false, ACC_INIT = false;
    static constexpr int SYNC_NS = 0;
    static __device__ __forceinline__ void prefetch(const QkvParams&, int) {}
    static __device__ __forceinline__ void load_w(const QkvParams& p, uint32_t sb, uint32_t bar, int k, int tm, int tn) { tma_ld4(sb + A_BYTES, &p.w, bar, 0, k * 64, 0, tn); }
    static __device__ __forceinline__ void load_x(const QkvParams& p, uint32_t sb, uint32_t bar, int k, int tm, int tn) { tma_ld2(sb, &p.x, bar, k * 64, tm * 256); }
    static __device__ __forceinline__ void load_aux(const QkvParams&, const GemmSmem&, int, int) {}
    static __device__ __forceinline__ uint32_t desc_a(uint32_t sb, int wg, int m, int kk) { return desc_lo(sb + (wg * 128 + m * 64) * 128 + kk * 32, 16); }
    static __device__ __forceinline__ uint32_t desc_b(uint32_t sb, int kk) { return desc_lo(sb + A_BYTES + kk * 2048, 8192); }
    static __device__ __forceinline__ void mma(float (&d)[96], uint32_t a, uint32_t b, int sc) { mma_qkv(d, a, b, sc); }
};

__device__ __forceinline__ void spin_until(const uint32_t* cnt, uint32_t target) {
    uint32_t v; int it = 0;
    do {
        asm volatile("ld.acquire.gpu.global.u32 %0, [%1];" : "=r"(v) : "l"(cnt) : "memory");
        if (++it > (1 << 22)) __trap();
    } while (v < target);
}
__device__ __forceinline__ void publish(uint32_t* cnt) { asm volatile("red.release.gpu.global.add.u32 [%0], 1;" :: "l"(cnt) : "memory"); }

__device__ __forceinline__ void qkv_aux(const QkvParams& p, uint8_t* smem_raw, const GemmSmem& s, int tm, int tn, int w, int lane) {
    for (int r = w; r < 16; r += 3) {
        const int row = tm * 256 + tn * 16 + r;
        const uint4* src = reinterpret_cast<const uint4*>(p.xp + (size_t)row * DM);
        uint32_t v[16];
#pragma unroll
        for (int i = 0; i < 4; i++) { const uint4 t = __ldg(src + lane + 32 * i); v[4 * i] = t.x; v[4 * i + 1] = t.y; v[4 * i + 2] = t.z; v[4 * i + 3] = t.w; }
        float sum = 0.f;
#pragma unroll
        for (int i = 0; i < 16; i++) sum += bf_lo(v[i]) + bf_hi(v[i]);
        const float mean = warp_sum(sum) * (1.f / DM);
        float q = 0.f;
#pragma unroll
        for (int i = 0; i < 16; i++) { const float a = bf_lo(v[i]) - mean, b = bf_hi(v[i]) - mean; q += a * a + b * b; }
        const float rstd = rsqrtf(warp_sum(q) * (1.f / DM) + 1e-5f);
        if (lane == 0) g_rowstat[row] = make_float2(mean, rstd);
    }
    __syncwarp();
    if (lane == 0) publish(&g_cnt_row[tm]);
    {
        const uint4* src = reinterpret_cast<const uint4*>(p.wp + (size_t)(tm * 128 + (lane >> 3)) * (3 * DM) + w * DM + tn * 64) + (lane & 7);
        float a[8];
#pragma unroll
        for (int i = 0; i < 8; i++) a[i] = 0.f;
#pragma unroll 1
        for (int j = 0; j < 32; j += 8) {
            uint4 t[8];
#pragma unroll
            for (int i = 0; i < 8; i++) t[i] = __ldg(src + (size_t)(j + i) * 4 * (3 * DM / 8));
#pragma unroll
            for (int i = 0; i < 8; i++) {
                a[0] += bf_lo(t[i].x); a[1] += bf_hi(t[i].x); a[2] += bf_lo(t[i].y); a[3] += bf_hi(t[i].y);
                a[4] += bf_lo(t[i].z); a[5] += bf_hi(t[i].z); a[6] += bf_lo(t[i].w); a[7] += bf_hi(t[i].w);
            }
        }
#pragma unroll
        for (int i = 0; i < 8; i++) { a[i] += __shfl_xor_sync(0xffffffffu, a[i], 8); a[i] += __shfl_xor_sync(0xffffffffu, a[i], 16); }
        if (lane < 8) {
            float4* dst = reinterpret_cast<float4*>(g_colsum + tm * (3 * DM) + tn * 192 + w * 64 + lane * 8);
            dst[0] = make_float4(a[0], a[1], a[2], a[3]); dst[1] = make_float4(a[4], a[5], a[6], a[7]);
        }
        __syncwarp();
        if (lane == 0) publish(&g_cnt_col[tn]);
    }
    float* scs = reinterpret_cast<float*>(smem_raw + QkvCfg::AUX_OFF);
    float2* sst = reinterpret_cast<float2*>(smem_raw + QkvCfg::AUX_OFF + 768);
    const int t = w * 32 + lane;
    spin_until(&g_cnt_row[tm], 16 * 3);
    for (int r = t; r < 256; r += 96) sst[r] = __ldcg(&g_rowstat[tm * 256 + r]);
    spin_until(&g_cnt_col[tn], 8 * 3);
    {
        float2 c = make_float2(0.f, 0.f);
#pragma unroll
        for (int i = 0; i < 8; i++) { const float2 u = __ldcg(reinterpret_cast<const float2*>(g_colsum + i * (3 * DM) + tn * 192) + t); c.x += u.x; c.y += u.y; }
        reinterpret_cast<float2*>(scs)[t] = c;
    }
    __syncwarp();
    if (lane == 0) mbar_arrive(s.aux);
}

__global__ void __launch_bounds__(384, 1) qkv_kernel(const __grid_constant__ QkvParams p) {
    extern __shared__ __align__(1024) uint8_t smem_raw[];
    TL(1, 4);
    pdl_launch();
    const int tm = blockIdx.x & 7, tn = blockIdx.x >> 3;
    if (threadIdx.x == 0) { prefetch_map(&p.x); prefetch_map(&p.w); prefetch_map(&p.out); }
    const GemmSmem s = gemm_setup<QkvCfg>(smem_raw);
    const int wgi = __shfl_sync(0xffffffffu, threadIdx.x >> 7, 0);
    if (wgi == 0) {
        reg_dealloc<56>();
        if (threadIdx.x < 32) {
            if (threadIdx.x == 0) gemm_producer<QkvCfg>(s, p, tm, tn);
            __syncwarp();
#pragma unroll 1
            for (int i = 0; i < 12; i++) {
                const int sub = i >> 1, wg = i & 1;
                named_bar(2 + i, 160);
                if (threadIdx.x == 0) tma_st2(&p.out, s.base + sub * 16384 + wg * 8192, 0, (sub >> 1) * (NH * SEQ) + (tn * 2 + (sub & 1)) * SEQ + tm * 256 + wg * 128);
            }
            if (threadIdx.x == 0) { tma_st_commit(); tma_st_wait(); TL(1, 3); }
        } else qkv_aux(p, smem_raw, s, tm, tn, (threadIdx.x >> 5) - 1, threadIdx.x & 31);
    } else {
        reg_alloc<224>();
        const int wg = wgi - 1, warp = (threadIdx.x >> 5) & 3, lane = threadIdx.x & 31;
        float acc[2][96];
        TL(1, 0);
        gemm_mainloop<QkvCfg>(s, wg, acc, 1);
        TL(1, 1);
        mbar_wait(s.aux, 0);
        named_bar(1, 256);
        const float qscale = 0.17677669529663687f * 1.4426950408889634f;
        const float2* scs = reinterpret_cast<const float2*>(smem_raw + QkvCfg::AUX_OFF);
        const float2* sst = reinterpret_cast<const float2*>(smem_raw + QkvCfg::AUX_OFF + 768);
        float mean[4], rstd[4];
#pragma unroll
        for (int i = 0; i < 4; i++) { const float2 t = sst[wg * 128 + (i >> 1) * 64 + warp * 16 + (i & 1) * 8 + (lane >> 2)]; mean[i] = -t.x; rstd[i] = t.y; }
#pragma unroll
        for (int sub = 0; sub < 6; sub++) {
            float nrm[4];
#pragma unroll
            for (int m = 0; m < 2; m++) {
                const int arow = wg * 128 + m * 64 + warp * 16 + ((lane >> 3) & 1) * 8 + (lane & 7);
                const float r0 = (sub < 2) ? rstd[2 * m] * qscale : rstd[2 * m], r1 = (sub < 2) ? rstd[2 * m + 1] * qscale : rstd[2 * m + 1];
                float v[16];
#pragma unroll
                for (int j = 0; j < 4; j++) {
                    const float2 cs = scs[(sub * 4 + j) * 4 + (lane & 3)];
                    v[4 * j] = fmaf(mean[2 * m], cs.x, acc[m][sub * 16 + 4 * j]) * r0;
                    v[4 * j + 1] = fmaf(mean[2 * m], cs.y, acc[m][sub * 16 + 4 * j + 1]) * r0;
                    v[4 * j + 2] = fmaf(mean[2 * m + 1], cs.x, acc[m][sub * 16 + 4 * j + 2]) * r1;
                    v[4 * j + 3] = fmaf(mean[2 * m + 1], cs.y, acc[m][sub * 16 + 4 * j + 3]) * r1;
                }
                float n0 = 0.f, n1 = 0.f;
#pragma unroll
                for (int j = 0; j < 4; j++) {
                    n0 = fmaf(v[4 * j], v[4 * j], fmaf(v[4 * j + 1], v[4 * j + 1], n0));
                    n1 = fmaf(v[4 * j + 2], v[4 * j + 2], fmaf(v[4 * j + 3], v[4 * j + 3], n1));
                }
                nrm[2 * m] = n0; nrm[2 * m + 1] = n1;
#pragma unroll
                for (int jp = 0; jp < 2; jp++) {
                    const int chunk = jp * 2 + (lane >> 4);
                    const uint32_t addr = s.base + sub * 16384 + arow * 64 + ((chunk ^ ((arow >> 1) & 3)) << 4);
                    stmatrix_x4(addr, pack_bf16(v[8 * jp], v[8 * jp + 1]), pack_bf16(v[8 * jp + 2], v[8 * jp + 3]),
                                pack_bf16(v[8 * jp + 4], v[8 * jp + 5]), pack_bf16(v[8 * jp + 6], v[8 * jp + 7]));
                }
            }
            hand_over(2 + sub * 2 + wg);
            const bool odd = lane & 1, up = lane & 2;
            const float s0 = (odd ? nrm[2] : nrm[0]) + __shfl_xor_sync(0xffffffffu, odd ? nrm[0] : nrm[2], 1);
            const float s1 = (odd ? nrm[3] : nrm[1]) + __shfl_xor_sync(0xffffffffu, odd ? nrm[1] : nrm[3], 1);
            const float full = (up ? s1 : s0) + __shfl_xor_sync(0xffffffffu, up ? s0 : s1, 2);
            const uint32_t mx = __reduce_max_sync(0xffffffffu, __float_as_uint(full));
            if (lane == 0) g_norm[((sub >> 1) * NH + tn * 2 + (sub & 1)) * 64 + (tm * 2 + wg) * 4 + warp] = mx;
        }
        TL(1, 5);
    }
}

struct AttnParams { CUtensorMap kv, kv2, o; bf16* optr; const uint8_t* pf_wo; const uint8_t* pf_w1; const uint8_t* pf_x; };
constexpr int AT_STAGES = 8, AT_STAGE_BYTES = 16384, AT_Q_OFF = AT_STAGES * AT_STAGE_BYTES, AT_ONES_OFF = AT_Q_OFF + 32768, AT_STG_OFF = AT_ONES_OFF + 1024, AT_BAR_OFF = AT_STG_OFF + 16384, AT_SMEM = AT_BAR_OFF + 256;
constexpr uint32_t AT_BASE = 1024;
constexpr int AT_TILES = 32;

__device__ __forceinline__ float ex2_poly(float x) {
    const float magic = 12582912.f;
    const float t = x + magic;
    const float f = x - (t - magic);
    float p = fmaf(f, 0.05550410866f, 0.24022650695f);
    p = fmaf(p, f, 0.69314718056f);
    p = fmaf(p, f, 1.0f);
    return __int_as_float(__float_as_int(p) + (__float_as_int(t) << 23));
}

__device__ __forceinline__ uint32_t fma_bf16x2(uint32_t a, uint32_t b, uint32_t c) { uint32_t d; asm("fma.rn.bf16x2 %0, %1, %2, %3;" : "=r"(d) : "r"(a), "r"(b), "r"(c)); return d; }
__device__ __forceinline__ uint32_t ex2_pair(float x0, float x1, uint32_t c3) {
    const float m0 = 12582912.f, m1 = 12582912.f - 64.f;
    const float t0 = x0 + m0, t1 = x1 + m1;
    const uint32_t f = pack_bf16(x0 - (t0 - m0), x1 - (t1 - m1));
    uint32_t p = fma_bf16x2(f, c3, 0xBE763E76u);
    p = fma_bf16x2(p, f, 0xBF313F31u);
    p = fma_bf16x2(p, f, 0xBF803F80u);
    return p + (__float_as_uint(t1) << 23) + (__float_as_uint(t0) << 7);
}
constexpr uint32_t FX_LEAD = EXP_FX == 2 ? 0x3EAB3EABu : 0x3DA03DA0u;
__device__ __forceinline__ uint32_t ex2_pair_fx(float x0, float x1, uint32_t c3, uint32_t one2) {
    const float m = 65663.f;
    const uint32_t w = __byte_perm(__float_as_uint(x0 + m), __float_as_uint(x1 + m), 0x5410);
    uint32_t g, r;
    asm("lop3.b32 %0, %1, 0x007F007F, %2, 0xEA;" : "=r"(g) : "r"(w), "r"(one2));
    uint32_t p;
    if (EXP_FX == 2) {
        p = fma_bf16x2(g, c3, 0xBC5DBC5Du);
        p = fma_bf16x2(p, g, 0x3F2F3F2Fu);
    } else {
        p = fma_bf16x2(g, c3, 0xBBF0BBF0u);
        p = fma_bf16x2(p, g, 0x3EF33EF3u);
        p = fma_bf16x2(p, g, 0x3EE93EE9u);
    }
    asm("lop3.b32 %0, %1, %2, 0xFF80FF80, 0xE4;" : "=r"(r) : "r"(w), "r"(p));
    return r;
}
template <uint32_t MASK> __device__ __forceinline__ uint32_t attn_exp2(float x0, float x1, int i, uint32_t c3) {
    if (EXP_FX) return ((MASK >> i) & 1) ? ex2_pair_fx(x0, x1, c3, c3 ^ (FX_LEAD ^ 0x3F803F80u)) : pack_bf16(ex2(x0), ex2(x1));
    return ((MASK >> i) & 1) ? ex2_pair(x0, x1, c3) : pack_bf16(ex2(x0), ex2(x1));
}
template <uint32_t MASK> __device__ __forceinline__ float attn_exp(float x, int i) { return ((MASK >> (i & 31)) & 1) ? ex2_poly(x) : ex2(x); }
__device__ __forceinline__ void attn_issue_tile(const AttnParams& p, uint32_t base, uint32_t full0, int g, int head) {
    const int st = g % AT_STAGES, key0 = (g & 15) * 128;
    const uint32_t bar = full0 + 8 * st, dst = base + st * AT_STAGE_BYTES;
    mbar_expect_tx(bar, AT_STAGE_BYTES);
    tma_ld3(dst, &p.kv2, bar, 0, head * SEQ + key0, 1);
}
__device__ __forceinline__ void attn_qk(float (&sacc)[32], uint32_t q_lo, uint32_t k_lo) {
    mma_qk0(sacc, q_lo, k_lo);
    mma_qk1(sacc, q_lo + 2, k_lo + 2, 1);
}
constexpr uint32_t PV_STEP = 64u - (64u << 16);
__device__ __forceinline__ void attn_pv(float (&o)[20], const uint32_t (&pr)[16], uint32_t v_lo, int first) {
#pragma unroll
    for (int kk = 0; kk < 4; kk++)
        mma_pv(o, pr[4 * kk], pr[4 * kk + 1], pr[4 * kk + 2], pr[4 * kk + 3], v_lo + kk * PV_STEP, (kk > 0) || !first);
}
__device__ __forceinline__ void attn_store_o(const float (&o)[20], const AttnParams& p, uint32_t base, int head, int row0, int lane) {
    const float r0 = 1.f / o[16], r1 = 1.f / o[18];
    {
        uint32_t a[4], b[4];
#pragma unroll
        for (int j = 0; j < 4; j++) { a[j] = pack_bf16(o[4 * j] * r0, o[4 * j + 1] * r0); b[j] = pack_bf16(o[4 * j + 2] * r1, o[4 * j + 3] * r1); }
        const bool odd = lane & 1, up = lane & 2;
#pragma unroll
        for (int h = 0; h < 2; h++) {
            uint32_t t = __shfl_xor_sync(0xffffffffu, odd ? a[2 * h] : a[2 * h + 1], 1); if (odd) a[2 * h] = t; else a[2 * h + 1] = t;
            t = __shfl_xor_sync(0xffffffffu, odd ? b[2 * h] : b[2 * h + 1], 1); if (odd) b[2 * h] = t; else b[2 * h + 1] = t;
        }
#pragma unroll
        for (int h = 0; h < 2; h++) {
            uint32_t t = __shfl_xor_sync(0xffffffffu, up ? a[h] : a[h + 2], 2); if (up) a[h] = t; else a[h + 2] = t;
            t = __shfl_xor_sync(0xffffffffu, up ? b[h] : b[h + 2], 2); if (up) b[h] = t; else b[h + 2] = t;
        }
        uint4* op = reinterpret_cast<uint4*>(p.optr + (size_t)(row0 + (lane >> 2)) * DM + head * HD) + (lane & 3);
        op[0] = make_uint4(a[0], a[1], a[2], a[3]);
        op[8 * (DM / 8)] = make_uint4(b[0], b[1], b[2], b[3]);
        return;
    }
    const uint32_t stg = base + AT_STG_OFF + (threadIdx.x >> 5) * 1024;
    const int arow = ((lane >> 3) & 1) * 8 + (lane & 7);
    if (lane == 0) tma_st_wait();
    __syncwarp();
#pragma unroll
    for (int jp = 0; jp < 2; jp++) {
        const int chunk = jp * 2 + (lane >> 4);
        stmatrix_x4(stg + arow * 64 + ((chunk ^ ((arow >> 1) & 3)) << 4), pack_bf16(o[8 * jp] * r0, o[8 * jp + 1] * r0), pack_bf16(o[8 * jp + 2] * r1, o[8 * jp + 3] * r1),
                    pack_bf16(o[8 * jp + 4] * r0, o[8 * jp + 5] * r0), pack_bf16(o[8 * jp + 6] * r1, o[8 * jp + 7] * r1));
    }
    fence_proxy_async();
    __syncwarp();
    if (lane == 0) { tma_st2(&p.o, stg, head * HD, row0); tma_st_commit(); }
}
__device__ __forceinline__ void attn_refill(const AttnParams& p, uint32_t base, uint32_t full0, uint32_t empty0, int g, int head) {
    if (threadIdx.x == 0 && g >= 4 && g + 4 < AT_TILES) {
        const int gp = g - 4;
        mbar_wait(empty0 + 8 * (gp % AT_STAGES), (gp / AT_STAGES) & 1);
        attn_issue_tile(p, base, full0, g + 4, head);
    }
    __syncwarp();
}

__device__ __forceinline__ void attn_fast(const AttnParams& p, uint32_t base, uint32_t full0, uint32_t empty0, int head, int qchunk) {
    const int wg = __shfl_sync(0xffffffffu, threadIdx.x >> 7, 0), warp = (threadIdx.x >> 5) & 3, lane = threadIdx.x & 31;
    const int warp_id = __shfl_sync(0xffffffffu, threadIdx.x >> 5, 0);
    const uint32_t k_lo0 = desc_lo(base, 16), v_lo0 = desc_lo(base + 8192, AT_ONES_OFF - 8192);
    const uint32_t q_lo0 = desc_lo(base + AT_Q_OFF + wg * 64 * 64, 16);
    uint32_t c3;
    asm volatile("ld.shared.u32 %0, [%1];" : "=r"(c3) : "r"(base + AT_ONES_OFF));
    c3 ^= 0x3F803F80u ^ (EXP_FX ? FX_LEAD : 0xBD693D69u);
#pragma unroll 1
    for (int pass = 0; pass < 2; pass++) {
    const uint32_t q = q_lo0 + pass * (256 * 64 >> 4);
    float o[20];
#pragma unroll
    for (int i = 0; i < 20; i++) o[i] = 0.f;
    if (PF_W1 == 3 && pass == 1 && threadIdx.x < 128 + 140) {
        const int l = threadIdx.x;
        prefetch_line(l < 128 ? p.pf_wo + ((size_t)blockIdx.x * 128 + l) * 128 : p.pf_w1 + ((size_t)blockIdx.x * 140 + (l - 128)) * 128);
    }
#pragma unroll 1
    for (uint32_t par = 0; par < 2; par++) {
        const int rev = pass * 2 + par;
        if (PF_W1 == 1 && threadIdx.x < 256) {
            const int l = rev * 256 + threadIdx.x;
            prefetch_line(l < 128 ? p.pf_wo + ((size_t)blockIdx.x * 128 + l) * 128 : p.pf_w1 + ((size_t)blockIdx.x * 896 + (l - 128)) * 128);
        }
        if (PF_W1 == 2 && rev == PF_REV && threadIdx.x < 128 + 140) {
            const int l = threadIdx.x;
            prefetch_line(l < 128 ? p.pf_wo + ((size_t)blockIdx.x * 128 + l) * 128 : p.pf_w1 + ((size_t)blockIdx.x * 140 + (l - 128)) * 128);
        }
#pragma unroll
        for (int st = 0; st < AT_STAGES; st++) {
            if (warp_id == (st & 3) * 5) {
                const int g = rev * AT_STAGES + st;
                if (lane == 0 && g >= 4 && g + 4 < AT_TILES) {
                    mbar_wait(empty0 + 8 * ((st + 4) % AT_STAGES), (st >= 4) ? par : (par ^ 1));
                    attn_issue_tile(p, base, full0, g + 4, head);
                }
                __syncwarp();
            }
            mbar_wait(full0 + 8 * st, par);
            float sc[64];
            uint32_t pa[16], pb[16];
            AT(0);
            wg_fence();
            mma_qkw0(sc, q, k_lo0 + st * (AT_STAGE_BYTES >> 4));
            mma_qkw1(sc, q + 2, k_lo0 + st * (AT_STAGE_BYTES >> 4) + 2, 1);
            wg_commit();
            wg_wait<0>();
            fence_regs(sc);
            AT(1);
            if (lane == 0 && (st > 0 || rev > 0)) mbar_arrive(empty0 + 8 * ((st + AT_STAGES - 1) % AT_STAGES));
#pragma unroll
            for (int i = 0; i < 16; i++) pa[i] = PAIR_POLY ? attn_exp2<PMASK_A>(sc[2 * i], sc[2 * i + 1], i, c3) : pack_bf16(attn_exp<POLY_MASK>(sc[2 * i], 2 * i), attn_exp<POLY_MASK>(sc[2 * i + 1], 2 * i + 1));
            wg_fence();
            attn_pv(o, pa, v_lo0 + st * 16 * PV_STEP, 0);
            wg_commit();
            AT(2);
#pragma unroll
            for (int i = 0; i < 16; i++) pb[i] = PAIR_POLY ? attn_exp2<PMASK_B>(sc[32 + 2 * i], sc[32 + 2 * i + 1], i, c3) : pack_bf16(attn_exp<POLY_MASK_B>(sc[32 + 2 * i], 2 * i), attn_exp<POLY_MASK_B>(sc[32 + 2 * i + 1], 2 * i + 1));
            wg_wait<0>();
            wg_fence();
            attn_pv(o, pb, v_lo0 + (st * 16 + 4) * PV_STEP, 0);
            wg_commit();
            AT(3);
        }
    }
    wg_wait<0>();
    fence_regs(o);
    attn_store_o(o, p, base, head, qchunk * 512 + pass * 256 + wg * 64 + warp * 16, lane);
    }
}

template <uint32_t MASK>
__device__ __forceinline__ void attn_piece(float (&o)[20], const float* sc, uint32_t c3, uint32_t v_lo) {
    uint32_t pr[8];
#pragma unroll
    for (int i = 0; i < 8; i++) pr[i] = attn_exp2<MASK>(sc[2 * i], sc[2 * i + 1], i, c3);
    wg_fence();
    mma_pv(o, pr[0], pr[1], pr[2], pr[3], v_lo, 1);
    mma_pv(o, pr[4], pr[5], pr[6], pr[7], v_lo + PV_STEP, 1);
    wg_commit();
}
__device__ __forceinline__ void attn_fast2(const AttnParams& p, uint32_t base, uint32_t full0, uint32_t empty0, int head, int qchunk) {
    const int wg = __shfl_sync(0xffffffffu, threadIdx.x >> 7, 0), warp = (threadIdx.x >> 5) & 3, lane = threadIdx.x & 31;
    const int warp_id = __shfl_sync(0xffffffffu, threadIdx.x >> 5, 0);
    const uint32_t dbase = IMM_DESC ? AT_BASE : base;
    const uint32_t k_lo0 = desc_lo(dbase, 16), v_lo0 = desc_lo(dbase + 8192, AT_ONES_OFF - 8192);
    const uint32_t q_lo0 = desc_lo(dbase + AT_Q_OFF, 16) + wg * (64 * 64 >> 4);
    uint32_t c3;
    asm volatile("ld.shared.u32 %0, [%1];" : "=r"(c3) : "r"(base + AT_ONES_OFF));
    c3 ^= 0x3F803F80u ^ (EXP_FX ? FX_LEAD : 0xBD693D69u);
    float sa[32], sb[32];
    mbar_wait(full0, 0);
    wg_fence();
    attn_qk(sa, q_lo0, k_lo0);
    wg_commit();
    wg_wait<0>();
    fence_regs(sa);
#pragma unroll 1
    for (int pass = 0; pass < 2; pass++) {
    const uint32_t q = q_lo0 + pass * (256 * 64 >> 4);
    float o[20];
#pragma unroll
    for (int i = 0; i < 20; i++) o[i] = 0.f;
#pragma unroll 1
    for (uint32_t par = 0; par < 2; par++) {
        const int rev = pass * 2 + par;
        const uint32_t qw = par ? q_lo0 + (256 * 64 >> 4) : q;
#pragma unroll
        for (int st = 0; st < AT_STAGES; st++) {
            if (warp_id == (st & 3) * 5) {
                const int g = rev * AT_STAGES + st;
                if (lane == 0 && g >= 4 && g + 4 < AT_TILES) {
                    mbar_wait(empty0 + 8 * ((st + 4) % AT_STAGES), (st >= 4) ? par : (par ^ 1));
                    attn_issue_tile(p, base, full0, g + 4, head);
                }
                __syncwarp();
            }
            const uint32_t kb = k_lo0 + st * (AT_STAGE_BYTES >> 4), vb = v_lo0 + st * 16 * PV_STEP;
            wg_fence();
            attn_qk(sb, q, kb + 256);
            wg_commit();
            wg_wait<2>();
            fence_regs(sa);
            attn_piece<QMASK_0>(o, sa, c3, vb);
            wg_wait<2>();
            if (lane == 0 && (st > 0 || rev > 0)) mbar_arrive(empty0 + 8 * ((st + AT_STAGES - 1) % AT_STAGES));
            attn_piece<QMASK_1>(o, sa + 16, c3, vb + 2 * PV_STEP);
            const int nx = (st + 1) % AT_STAGES;
            if (st + 1 < AT_STAGES) mbar_wait(full0 + 8 * nx, par);
            else if (rev < 3) mbar_wait(full0, par ^ 1);
            wg_fence();
            attn_qk(sa, st + 1 < AT_STAGES ? q : qw, k_lo0 + nx * (AT_STAGE_BYTES >> 4));
            wg_commit();
            wg_wait<2>();
            fence_regs(sb);
            attn_piece<QMASK_2>(o, sb, c3, vb + 4 * PV_STEP);
            wg_wait<2>();
            attn_piece<QMASK_3>(o, sb + 16, c3, vb + 6 * PV_STEP);
        }
        wg_wait<0>();
        fence_regs(sa);
        fence_regs(o);
    }
    attn_store_o(o, p, base, head, qchunk * 512 + pass * 256 + wg * 64 + warp * 16, lane);
    }
}

__device__ __forceinline__ void attn_safe(const AttnParams& p, uint32_t base, uint32_t full0, uint32_t empty0, int head, int qchunk) {
    const int wg = __shfl_sync(0xffffffffu, threadIdx.x >> 7, 0), warp = (threadIdx.x >> 5) & 3, lane = threadIdx.x & 31;
    const uint32_t k_lo0 = desc_lo(base, 16), v_lo0 = desc_lo(base + 8192, AT_ONES_OFF - 8192);
#pragma unroll 1
    for (int pass = 0; pass < 2; pass++) {
        const uint32_t q = desc_lo(base + AT_Q_OFF + (pass * 256 + wg * 64) * 64, 16);
        float o[20];
#pragma unroll
        for (int i = 0; i < 20; i++) o[i] = 0.f;
        float m0 = -INFINITY, m1 = -INFINITY;
#pragma unroll 1
        for (int t = 0; t < 32; t++) {
            const int g = pass * 16 + (t >> 1), half = t & 1;
            const int st = g % AT_STAGES;
            const uint32_t kb = k_lo0 + st * (AT_STAGE_BYTES >> 4), vb = v_lo0 + st * 16 * PV_STEP;
            if (half == 0) { attn_refill(p, base, full0, empty0, g, head); mbar_wait(full0 + 8 * st, (g / AT_STAGES) & 1); }
            float cur[32];
            wg_fence();
            attn_qk(cur, q, kb + half * 256);
            wg_commit();
            wg_wait<0>();
            fence_regs(cur);
            float x0 = cur[0], x1 = cur[2];
#pragma unroll
            for (int i = 0; i < 8; i++) { x0 = fmaxf(x0, fmaxf(cur[4 * i], cur[4 * i + 1])); x1 = fmaxf(x1, fmaxf(cur[4 * i + 2], cur[4 * i + 3])); }
            x0 = fmaxf(x0, __shfl_xor_sync(0xffffffffu, x0, 1)); x1 = fmaxf(x1, __shfl_xor_sync(0xffffffffu, x1, 1));
            x0 = fmaxf(x0, __shfl_xor_sync(0xffffffffu, x0, 2)); x1 = fmaxf(x1, __shfl_xor_sync(0xffffffffu, x1, 2));
            const float n0 = fmaxf(m0, x0), n1 = fmaxf(m1, x1);
            const float a0 = ex2(m0 - n0), a1 = ex2(m1 - n1);
            m0 = n0; m1 = n1;
            uint32_t pr[16];
#pragma unroll
            for (int i = 0; i < 8; i++) {
                pr[2 * i] = pack_bf16(ex2(cur[4 * i] - n0), ex2(cur[4 * i + 1] - n0));
                pr[2 * i + 1] = pack_bf16(ex2(cur[4 * i + 2] - n1), ex2(cur[4 * i + 3] - n1));
            }
#pragma unroll
            for (int i = 0; i < 5; i++) { o[4 * i] *= a0; o[4 * i + 1] *= a0; o[4 * i + 2] *= a1; o[4 * i + 3] *= a1; }
            wg_fence();
            attn_pv(o, pr, vb + half * 4 * PV_STEP, 0);
            wg_commit();
            wg_wait<0>();
            fence_regs(o);
            if (half == 1 && lane == 0) mbar_arrive(empty0 + 8 * st);
        }
        attn_store_o(o, p, base, head, qchunk * 512 + pass * 256 + wg * 64 + warp * 16, lane);
    }
}

__global__ void __launch_bounds__(512, 1) attn_kernel(const __grid_constant__ AttnParams p) {
    extern __shared__ __align__(1024) uint8_t smem_raw[];
    TL(2, 4);
    pdl_launch();
    const uint32_t base = smem_u32(smem_raw);
    const uint32_t full0 = base + AT_BAR_OFF, empty0 = full0 + 8 * AT_STAGES;
    const int head = blockIdx.x >> 2, qchunk = blockIdx.x & 3;
    if (threadIdx.x == 0) {
        if (base & 1023) __trap();
        prefetch_map(&p.kv);
        for (int i = 0; i < AT_STAGES; i++) { mbar_init(full0 + 8 * i, 1); mbar_init(empty0 + 8 * i, 16); }
        mbar_init(empty0 + 8 * AT_STAGES, 1);
        fence_barrier_init();
    }
    if (threadIdx.x < 256) reinterpret_cast<uint32_t*>(smem_raw + AT_ONES_OFF)[threadIdx.x] = 0x3F803F80u;
    fence_proxy_async();
    __syncthreads();
    pdl_wait();
    TL(2, 0);
    if (threadIdx.x == 0) {
        const uint32_t qbar = empty0 + 8 * AT_STAGES;
        mbar_expect_tx(qbar, 32768);
        for (int i = 0; i < 4; i++) tma_ld2(base + AT_Q_OFF + i * 8192, &p.kv, qbar, 0, head * SEQ + qchunk * 512 + i * 128);
        for (int g = 0; g < AT_STAGES; g++) attn_issue_tile(p, base, full0, g, head);
    }
    __syncwarp();
    const uint2* nrm = reinterpret_cast<const uint2*>(g_norm) + head * 32 + (threadIdx.x & 31);
    const uint2 nq = __ldcg(nrm), nk = __ldcg(nrm + NH * 32), nv = __ldcg(nrm + 2 * NH * 32);
    const float qn = __uint_as_float(__reduce_max_sync(0xffffffffu, max(nq.x, nq.y)));
    const float kn = __uint_as_float(__reduce_max_sync(0xffffffffu, max(nk.x, nk.y)));
    const float vn = __uint_as_float(__reduce_max_sync(0xffffffffu, max(nv.x, nv.y)));
    if (blockIdx.x == 0 && threadIdx.x >= 64 && threadIdx.x < 64 + 24) {
        const int i = threadIdx.x - 64;
        if (i < 8) g_cnt_row[i] = 0; else g_cnt_col[i - 8] = 0;
    }
    if (PF_W1 == 4) {
        const int l = threadIdx.x;
        if (l < 128 + 140) prefetch_line(l < 128 ? p.pf_wo + ((size_t)blockIdx.x * 128 + l) * 128 : p.pf_w1 + ((size_t)blockIdx.x * 140 + (l - 128)) * 128);
        if (PF_X && l >= 256) prefetch_line(p.pf_x + ((size_t)blockIdx.x * 256 + (l - 256)) * 128);
    }
    if (threadIdx.x >= 448) reinterpret_cast<uint4*>(g_hpart)[blockIdx.x * 64 + threadIdx.x - 448] = make_uint4(0, 0, 0, 0);
    const bool bounded = (qn * kn <= 1.0e4f) && (vn <= 1.0e9f) && (base & 0xFFFFFFu) == AT_BASE;
    mbar_wait(empty0 + 8 * AT_STAGES, 0);
    if (bounded) { if (ATTN_PIPE) attn_fast2(p, base, full0, empty0, head, qchunk); else attn_fast(p, base, full0, empty0, head, qchunk); }
    else attn_safe(p, base, full0, empty0, head, qchunk);
    if ((threadIdx.x & 31) == 0) tma_st_wait();
    TL(2, 3);
}

struct ResParams { CUtensorMap a, b, res, out; const bf16* bias; };
template <bool MIX2>
struct ResCfg {
    static constexpr int MB = 1, BN = 128, KSTEPS = MIX2 ? 56 : 16, STAGES = 6, A_BYTES = 16384, B_BYTES = 16384;
    static constexpr int STAGE_BYTES = A_BYTES + B_BYTES, STG_OFF = STAGES * STAGE_BYTES, BAR_OFF = STG_OFF + 32768, SMEM = BAR_OFF + 128;
    static constexpr int AUX_COUNT = 1, PRE = MIX2 ? MIX2_PRE : WO_PRE;
    static constexpr int TLK = MIX2 ? 6 : 3;
    static constexpr bool MC = MIX2 ? MIX2_MC : WO_MC, PAIR = MC || (MIX2 ? MIX2_PAIR : WO_PAIR), ACC_INIT = MIX2 ? MIX2_INIT : WO_INIT;
    static constexpr int SYNC_NS = MIX2 ? MIX2_SYNC : WO_SYNC;
    static __device__ __forceinline__ void prefetch(const ResParams&, int) {}
    static __device__ __forceinline__ void load_w(const ResParams& p, uint32_t sb, uint32_t bar, int k, int tm, int tn) {
        if (MIX2) {
            if (MC) tma_ld3_mc(sb + (tn & 1) * 8192, &p.a, bar, 0, k * 64, tm * 2 + (tn & 1));
            else tma_ld3(sb, &p.a, bar, 0, k * 64, tm * 2);
        } else tma_ld3(sb + A_BYTES, &p.b, bar, 0, k * 64, tn * 2);
    }
    static __device__ __forceinline__ void load_x(const ResParams& p, uint32_t sb, uint32_t bar, int k, int tm, int tn) {
        if (MIX2) tma_ld2(sb + A_BYTES, &p.b, bar, k * 64, tn * 128);
        else if (MC) tma_ld2_mc(sb + (tn & 1) * 8192, &p.a, bar, k * 64, tm * 128 + (tn & 1) * 64);
        else tma_ld2(sb, &p.a, bar, k * 64, tm * 128);
    }
    static __device__ __forceinline__ void load_aux(const ResParams& p, const GemmSmem& s, int tm, int tn) {
        mbar_expect_tx(s.aux, 32768);
        tma_ld2(s.base + STG_OFF, &p.res, s.aux, tn * 128, tm * 128);
        tma_ld2(s.base + STG_OFF + 16384, &p.res, s.aux, tn * 128 + 64, tm * 128);
    }
    static __device__ __forceinline__ uint32_t desc_a(uint32_t sb, int wg, int m, int kk) {
        return MIX2 ? desc_lo(sb + wg * 8192 + kk * 2048, 8192) : desc_lo(sb + wg * 8192 + kk * 32, 16);
    }
    static __device__ __forceinline__ uint32_t desc_b(uint32_t sb, int kk) {
        return MIX2 ? desc_lo(sb + A_BYTES + kk * 32, 16) : desc_lo(sb + A_BYTES + kk * 2048, 8192);
    }
    static __device__ __forceinline__ void mma(float (&d)[64], uint32_t a, uint32_t b, int sc) {
        if (MIX2) mma_mix2(d, a, b, sc); else mma_wo(d, a, b, sc);
    }
};
template <bool MIX2>
__global__ void __launch_bounds__(384, 1) res_gemm_kernel(const __grid_constant__ ResParams p) {
    using C = ResCfg<MIX2>;
    extern __shared__ __align__(1024) uint8_t smem_raw[];
    TL(MIX2 ? 6 : 3, 4);
    if (!MIX2) pdl_launch();
    constexpr bool MAP = MIX2 ? MIX2_MAP : WO_MAP;
    const int tm = MAP ? blockIdx.x >> 3 : blockIdx.x & 15, tn = MAP ? blockIdx.x & 7 : blockIdx.x >> 4;
    if (threadIdx.x == 0) { prefetch_map(&p.a); prefetch_map(&p.b); prefetch_map(&p.res); prefetch_map(&p.out); }
    const GemmSmem s = gemm_setup<C>(smem_raw);
    const int wgi = __shfl_sync(0xffffffffu, threadIdx.x >> 7, 0);
    if (wgi == 0) {
        reg_dealloc<40>();
        if (threadIdx.x < 32) {
            if (threadIdx.x == 0) gemm_producer<C>(s, p, tm, tn);
            __syncwarp();
#pragma unroll 1
            for (int i = 0; i < 4; i++) {
                const int b = i >> 1, wg = i & 1;
                named_bar(2 + i, 160);
                if (threadIdx.x == 0) tma_st2(&p.out, s.base + C::STG_OFF + b * 16384 + wg * 8192, tn * 128 + b * 64, tm * 128 + wg * 64);
            }
            if (threadIdx.x == 0) { tma_st_commit(); tma_st_wait(); TL(MIX2 ? 6 : 3, 3); }
        }
    } else {
        reg_alloc<232>();
        const int wg = wgi - 1, warp = (threadIdx.x >> 5) & 3, lane = threadIdx.x & 31;
        const int r0 = wg * 64 + warp * 16 + (lane >> 2);
        const int arow = wg * 64 + warp * 16 + ((lane >> 3) & 1) * 8 + (lane & 7);
        const uint32_t stg = s.base + C::STG_OFF + arow * 128;
        float acc[1][64];
        auto residual = [&]() {
            float a0 = 1.f, a1 = 1.f, c0 = 0.f, c1 = 0.f;
            if (MIX2) {
                const float2 t0 = __ldcg(&g_rowln[tm * 128 + r0]), t1 = __ldcg(&g_rowln[tm * 128 + r0 + 8]);
                a0 = t0.y; a1 = t1.y;
                c0 = t0.x + __bfloat162float(p.bias[tm * 128 + r0]); c1 = t1.x + __bfloat162float(p.bias[tm * 128 + r0 + 8]);
            }
            return make_float4(a0, a1, c0, c1);
        };
        auto apply = [&](const float4 ac) {
            mbar_wait(s.aux, 0);
#pragma unroll
            for (int jp = 0; jp < 8; jp++) {
                const int chunk = jp * 2 + (lane >> 4);
                uint32_t r[4];
                ldmatrix_x4(stg + (chunk >> 3) * 16384 + (((chunk & 7) ^ (arow & 7)) << 4), r);
#pragma unroll
                for (int i = 0; i < 4; i++) {
                    const float a = (i & 1) ? ac.y : ac.x, c = (i & 1) ? ac.w : ac.z;
                    const float v0 = MIX2 ? fmaf(bf_lo(r[i]), a, c) : bf_lo(r[i]), v1 = MIX2 ? fmaf(bf_hi(r[i]), a, c) : bf_hi(r[i]);
                    acc[0][jp * 8 + 2 * i] = C::ACC_INIT ? v0 : acc[0][jp * 8 + 2 * i] + v0;
                    acc[0][jp * 8 + 2 * i + 1] = C::ACC_INIT ? v1 : acc[0][jp * 8 + 2 * i + 1] + v1;
                }
            }
        };
        const float4 ac = residual();
        if (C::ACC_INIT) apply(ac);
        pdl_wait();
        TL(MIX2 ? 6 : 3, 0);
        gemm_mainloop<C>(s, wg, acc, MIX2 ? 6 : 3);
        TL(MIX2 ? 6 : 3, 1);
        if (!C::ACC_INIT) apply(ac);
        float sc0 = 1.f, sc1 = 1.f, of0 = 0.f, of1 = 0.f;
        if (!MIX2) {
            float s0 = 0.f, s1 = 0.f;
#pragma unroll
            for (int j = 0; j < 16; j++) { s0 += acc[0][4 * j] + acc[0][4 * j + 1]; s1 += acc[0][4 * j + 2] + acc[0][4 * j + 3]; }
            s0 += __shfl_xor_sync(0xffffffffu, s0, 1); s1 += __shfl_xor_sync(0xffffffffu, s1, 1);
            s0 += __shfl_xor_sync(0xffffffffu, s0, 2); s1 += __shfl_xor_sync(0xffffffffu, s1, 2);
            const float m0 = s0 * (1.f / 128), m1 = s1 * (1.f / 128);
            float q0 = 0.f, q1 = 0.f;
#pragma unroll
            for (int j = 0; j < 16; j++) {
                const float a = acc[0][4 * j] - m0, b = acc[0][4 * j + 1] - m0, c = acc[0][4 * j + 2] - m1, d = acc[0][4 * j + 3] - m1;
                q0 = fmaf(a, a, fmaf(b, b, q0)); q1 = fmaf(c, c, fmaf(d, d, q1));
            }
            q0 += __shfl_xor_sync(0xffffffffu, q0, 1); q1 += __shfl_xor_sync(0xffffffffu, q1, 1);
            q0 += __shfl_xor_sync(0xffffffffu, q0, 2); q1 += __shfl_xor_sync(0xffffffffu, q1, 2);
            const int wrow = tm * 128 + wg * 64 + warp * 16;
            if ((lane & 3) < 2) {
                const float m = (lane & 1) ? m1 : m0, q = (lane & 1) ? q1 : q0;
                const unsigned long long w = ((unsigned long long)(__float_as_uint(q) | 0x80000000u) << 32) | __float_as_uint(m);
                asm volatile("st.relaxed.gpu.global.u64 [%0], %1;" :: "l"(g_hpart + tn * SEQ + wrow + (lane >> 2) + (lane & 1) * 8), "l"(w) : "memory");
            }
            TL(3, 5);
            TKC(13);
            const unsigned long long* part = g_hpart + (lane >> 2) * SEQ + wrow + (lane & 3) * 4;
            unsigned long long t[4];
            int it = 0;
            bool ok;
            do {
                asm volatile("ld.relaxed.gpu.global.v2.u64 {%0, %1}, [%2];" : "=l"(t[0]), "=l"(t[1]) : "l"(part) : "memory");
                asm volatile("ld.relaxed.gpu.global.v2.u64 {%0, %1}, [%2];" : "=l"(t[2]), "=l"(t[3]) : "l"(part + 2) : "memory");
                ok = (long long)(t[0] & t[1] & t[2] & t[3]) < 0;
                if (++it > (1 << 20)) __trap();
            } while (!__all_sync(0xffffffffu, ok));
            TKC(14);
            float mt[4], qt[4];
#pragma unroll
            for (int i = 0; i < 4; i++) {
                const float mi = __uint_as_float((uint32_t)t[i]), qi = __uint_as_float((uint32_t)(t[i] >> 32) & 0x7FFFFFFFu);
                float m = mi;
                m += __shfl_xor_sync(0xffffffffu, m, 4); m += __shfl_xor_sync(0xffffffffu, m, 8); m += __shfl_xor_sync(0xffffffffu, m, 16);
                m *= 0.125f;
                float q = fmaf(128.f * (mi - m), mi - m, qi);
                q += __shfl_xor_sync(0xffffffffu, q, 4); q += __shfl_xor_sync(0xffffffffu, q, 8); q += __shfl_xor_sync(0xffffffffu, q, 16);
                mt[i] = m; qt[i] = q;
            }
            const int sel = (lane >> 2) & 3;
            const float mean = sel == 0 ? mt[0] : sel == 1 ? mt[1] : sel == 2 ? mt[2] : mt[3];
            const float var = (sel == 0 ? qt[0] : sel == 1 ? qt[1] : sel == 2 ? qt[2] : qt[3]) * (1.f / DM);
            const float r1 = rsqrtf(var + 1e-5f);
            const float r2 = rsqrtf(var * r1 * r1 + 1e-5f);
            const float scale = r1 * r2, off = -mean * scale;
            if (tn == 0 && lane < 16) g_rowln[wrow + 4 * (lane & 3) + sel] = make_float2(mean, 1.f / scale);
            const int ra = lane >> 2, src0 = ((ra & 3) << 2) | (ra >> 2);
            sc0 = __shfl_sync(0xffffffffu, scale, src0); of0 = __shfl_sync(0xffffffffu, off, src0);
            sc1 = __shfl_sync(0xffffffffu, scale, src0 + 2); of1 = __shfl_sync(0xffffffffu, off, src0 + 2);
        }
#pragma unroll
        for (int jp = 0; jp < 8; jp++) {
            const int chunk = jp * 2 + (lane >> 4);
            uint32_t r[4];
#pragma unroll
            for (int i = 0; i < 4; i++) {
                const float sc = (i & 1) ? sc1 : sc0, of = (i & 1) ? of1 : of0;
                const float v0 = acc[0][jp * 8 + 2 * i], v1 = acc[0][jp * 8 + 2 * i + 1];
                r[i] = MIX2 ? pack_bf16(v0, v1) : pack_bf16(fmaf(v0, sc, of), fmaf(v1, sc, of));
            }
            stmatrix_x4(stg + (chunk >> 3) * 16384 + (((chunk & 7) ^ (arow & 7)) << 4), r[0], r[1], r[2], r[3]);
            if ((jp & 3) == 3) hand_over(2 + (jp >> 2) * 2 + wg);
        }
        if (MIX2) TL(6, 5);
        TKC(15);
    }
}

struct Mix1Params { CUtensorMap hn, w1, out; const bf16* bias; const uint8_t* pf; };
struct Mix1Cfg {
    static constexpr int MB = 1, BN = 224, KSTEPS = 32, STAGES = 5, A_BYTES = 16384, B_BYTES = 28672;
    static constexpr int STAGE_BYTES = A_BYTES + B_BYTES, BIAS_OFF = STAGES * STAGE_BYTES, BAR_OFF = BIAS_OFF + 1024, SMEM = BAR_OFF + 128;
    static constexpr int AUX_COUNT = 1, PRE = MIX1_PRE;
    static constexpr int TLK = 5;
    static constexpr bool MC = MIX1_MC, PAIR = MC || MIX1_PAIR, ACC_INIT = false;
    static constexpr int SYNC_NS = MIX1_SYNC;
    static __device__ __forceinline__ void load_w(const Mix1Params& p, uint32_t sb, uint32_t bar, int k, int tm, int tn) {
        if (MC) tma_ld3_mc(sb + A_BYTES + (tm & 1) * (B_BYTES / 2), &p.w1, bar, 0, k * 64 + (tm & 1) * 32, tn * 7);
        else { tma_ld3(sb + A_BYTES, &p.w1, bar, 0, k * 64, tn * 7); tma_ld3(sb + A_BYTES + B_BYTES / 2, &p.w1, bar, 0, k * 64 + 32, tn * 7); }
    }
    static __device__ __forceinline__ void prefetch(const Mix1Params& p, int k) {}
    static __device__ __forceinline__ void load_x(const Mix1Params& p, uint32_t sb, uint32_t bar, int k, int tm, int tn) { tma_ld3(sb, &p.hn, bar, 0, k * 64, tm * 2); }
    static __device__ __forceinline__ void load_aux(const Mix1Params&, const GemmSmem&, int, int) {}
    static __device__ __forceinline__ uint32_t desc_a(uint32_t sb, int wg, int m, int kk) { return desc_lo(sb + wg * 8192 + kk * 2048, 8192); }
    static __device__ __forceinline__ uint32_t desc_b(uint32_t sb, int kk) { return desc_lo(sb + A_BYTES + (kk >> 1) * (B_BYTES / 2) + (kk & 1) * 1024, 2048); }
    static __device__ __forceinline__ void mma(float (&d)[112], uint32_t a, uint32_t b, int sc) { mma_mix1(d, a, b, sc); }
};
__global__ void __launch_bounds__(384, 1) mix1_kernel(const __grid_constant__ Mix1Params p) {
    using C = Mix1Cfg;
    extern __shared__ __align__(1024) uint8_t smem_raw[];
    TL(5, 4);
    const int tm = blockIdx.x & 7, tn = blockIdx.x >> 3;
    if (threadIdx.x == 0) { prefetch_map(&p.hn); prefetch_map(&p.w1); prefetch_map(&p.out); }
    float* sbias = reinterpret_cast<float*>(smem_raw + C::BIAS_OFF);
    const GemmSmem s = gemm_setup<C>(smem_raw);
    const int wgi = __shfl_sync(0xffffffffu, threadIdx.x >> 7, 0);
    if (wgi == 0) {
        reg_dealloc<40>();
        if (threadIdx.x < 32) {
            if (threadIdx.x == 0) gemm_producer<C>(s, p, tm, tn);
            __syncwarp();
#pragma unroll 1
            for (int i = 0; i < 14; i++) {
                const int b = i >> 1, wg = i & 1;
                named_bar(2 + i, 160);
                if (threadIdx.x == 0) tma_st3(&p.out, s.base + wg * 28672 + b * 4096, 0, tm * 128 + wg * 64, tn * 7 + b);
            }
            if (threadIdx.x == 0) { tma_st_commit(); tma_st_wait(); TL(5, 3); }
        } else if (PF_W2 && threadIdx.x >= 32 && threadIdx.x < 64) {
            pdl_wait();
            __nanosleep(PF_W2_DELAY);
            if (PF_W2 == 1) {
#pragma unroll 1
            for (int i = 0; i < 28; i++) {
                prefetch_line(p.pf + ((size_t)blockIdx.x * 896 + i * 32 + (threadIdx.x & 31)) * 128);
                __nanosleep(300);
            }
            } else {
#pragma unroll 1
            for (int i = 0; i < 4; i++) prefetch_line(p.pf + ((size_t)blockIdx.x * 128 + i * 32 + (threadIdx.x & 31)) * 128);
            }
        }
    } else {
        reg_alloc<232>();
        const int wg = wgi - 1, warp = (threadIdx.x >> 5) & 3, lane = threadIdx.x & 31;
        float acc[1][112];
        const int bi = threadIdx.x - 128;
        const bf16 bias = p.bias[tn * 224 + (bi < 224 ? bi : 0)];
        pdl_wait();
        pdl_launch();
        TL(5, 0);
        gemm_mainloop<C>(s, wg, acc, 5);
        TL(5, 1);
        if (bi < 224) sbias[bi] = __bfloat162float(bias);
        named_bar(1, 256);
        const int arow = warp * 16 + ((lane >> 3) & 1) * 8 + (lane & 7);
        const uint32_t stg = s.base + wg * 28672;
#pragma unroll
        for (int jp = 0; jp < 14; jp++) {
            float v[8];
#pragma unroll
            for (int h = 0; h < 2; h++) {
                const float2 bb = *reinterpret_cast<const float2*>(sbias + (jp * 2 + h) * 8 + (lane & 3) * 2);
#pragma unroll
                for (int i = 0; i < 4; i++) {
                    const float x = acc[0][jp * 8 + h * 4 + i] + ((i & 1) ? bb.y : bb.x);
                    const float inner = x * fmaf(x * x, 0.0356774081363f, 0.7978845608029f);
                    const float hx = 0.5f * x;
                    v[h * 4 + i] = fmaf(hx, tanh_fast(inner), hx);
                }
            }
            const int j = jp * 2 + (lane >> 4);
            const uint32_t addr = stg + (j >> 2) * 4096 + arow * 64 + (((j & 3) ^ ((arow >> 1) & 3)) << 4);
            stmatrix_x4(addr, pack_bf16(v[0], v[1]), pack_bf16(v[2], v[3]), pack_bf16(v[4], v[5]), pack_bf16(v[6], v[7]));
            if (jp & 1) hand_over(2 + (jp >> 1) * 2 + wg);
        }
        TL(5, 5);
    }
}

typedef CUresult (*EncodeFn)(CUtensorMap*, CUtensorMapDataType, cuuint32_t, void*, const cuuint64_t*, const cuuint64_t*, const cuuint32_t*,
                             const cuuint32_t*, CUtensorMapInterleave, CUtensorMapSwizzle, CUtensorMapL2promotion, CUtensorMapFloatOOBfill);
EncodeFn g_encode;

void make_map(CUtensorMap* m, const void* ptr, int rank, const uint64_t* dims, const uint64_t* strides_bytes, const uint32_t* box, CUtensorMapSwizzle swz) {
    cuuint64_t d[5], st[5]; cuuint32_t b[5], es[5];
    for (int i = 0; i < rank; i++) { d[i] = dims[i]; b[i] = box[i]; es[i] = 1; }
    for (int i = 0; i + 1 < rank; i++) st[i] = strides_bytes[i];
    CUresult r = g_encode(m, CU_TENSOR_MAP_DATA_TYPE_BFLOAT16, rank, const_cast<void*>(ptr), d, st, b, es, CU_TENSOR_MAP_INTERLEAVE_NONE, swz,
                          CU_TENSOR_MAP_L2_PROMOTION_L2_128B, CU_TENSOR_MAP_FLOAT_OOB_FILL_NONE);
    if (r != CUDA_SUCCESS) fprintf(stderr, "cuTensorMapEncodeTiled failed: %d\n", (int)r);
}
void map2d(CUtensorMap* m, const void* ptr, uint64_t cols, uint64_t rows, uint32_t bc, uint32_t br, CUtensorMapSwizzle swz) {
    uint64_t dims[2] = {cols, rows}, st[1] = {cols * 2}; uint32_t box[2] = {bc, br};
    make_map(m, ptr, 2, dims, st, box, swz);
}
void map3d(CUtensorMap* m, const void* ptr, uint64_t cols, uint64_t rows, uint32_t inner, uint32_t br, uint32_t nblk, CUtensorMapSwizzle swz) {
    uint64_t dims[3] = {inner, rows, cols / inner}, st[2] = {cols * 2, (uint64_t)inner * 2}; uint32_t box[3] = {inner, br, nblk};
    make_map(m, ptr, 3, dims, st, box, swz);
}

template <class... KArgs, class... Args>
void launch(void (*kern)(KArgs...), int grid, int block, int smem, bool pdl, bool pair, Args&&... args) {
    cudaLaunchConfig_t cfg = {};
    cfg.gridDim = dim3(grid); cfg.blockDim = dim3(block); cfg.dynamicSmemBytes = smem; cfg.stream = 0;
    cudaLaunchAttribute at[2];
    int n = 0;
    if (pdl) { at[n].id = cudaLaunchAttributeProgrammaticStreamSerialization; at[n].val.programmaticStreamSerializationAllowed = 1; n++; }
    if (pair) { at[n].id = cudaLaunchAttributeClusterDimension; at[n].val.clusterDim.x = 2; at[n].val.clusterDim.y = 1; at[n].val.clusterDim.z = 1; n++; }
    cfg.attrs = at; cfg.numAttrs = n;
    cudaError_t e = cudaLaunchKernelEx(&cfg, kern, KArgs(args)...);
    if (e != cudaSuccess) fprintf(stderr, "launch failed: %s\n", cudaGetErrorString(e));
}

struct HostState {
    bool ready;
    const void* key[9];
    QkvParams qkv; AttnParams attn; ResParams wo, mix2; Mix1Params mix1;
    bf16 *qkvp, *o, *hn, *u;
};
HostState g_hs;

}

#define USE_PDL 1

extern "C" void kernel_launch(void* const* d_in, const int* in_sizes, int n_in, void* d_out, int out_size) {
    const bf16* x = (const bf16*)d_in[0];
    const bf16* wqkv = (const bf16*)d_in[1];
    const bf16* wo = (const bf16*)d_in[2];
    const bf16* w1 = (const bf16*)d_in[4];
    const bf16* b1 = (const bf16*)d_in[5];
    const bf16* w2 = (const bf16*)d_in[6];
    const bf16* b2 = (const bf16*)d_in[7];
    HostState& hs = g_hs;
    bool same = hs.ready;
    for (int i = 0; i < 8 && same; i++) same = (hs.key[i] == d_in[i]);
    same = same && hs.key[8] == d_out;
    if (!same) {
        if (!g_encode) {
            void* fn = nullptr; cudaDriverEntryPointQueryResult qr;
            cudaGetDriverEntryPoint("cuTensorMapEncodeTiled", &fn, cudaEnableDefault, &qr);
            g_encode = (EncodeFn)fn;
            cudaFuncSetAttribute(qkv_kernel, cudaFuncAttributeMaxDynamicSharedMemorySize, QkvCfg::SMEM);
            cudaFuncSetAttribute(attn_kernel, cudaFuncAttributeMaxDynamicSharedMemorySize, AT_SMEM);
            cudaFuncSetAttribute(res_gemm_kernel<false>, cudaFuncAttributeMaxDynamicSharedMemorySize, ResCfg<false>::SMEM);
            cudaFuncSetAttribute(res_gemm_kernel<true>, cudaFuncAttributeMaxDynamicSharedMemorySize, ResCfg<true>::SMEM);
            cudaFuncSetAttribute(mix1_kernel, cudaFuncAttributeMaxDynamicSharedMemorySize, Mix1Cfg::SMEM);
        }
        cudaGetSymbolAddress((void**)&hs.qkvp, g_qkv); cudaGetSymbolAddress((void**)&hs.o, g_o);
        cudaGetSymbolAddress((void**)&hs.hn, g_hn); cudaGetSymbolAddress((void**)&hs.u, g_u);
        const CUtensorMapSwizzle S128 = CU_TENSOR_MAP_SWIZZLE_128B, S64 = CU_TENSOR_MAP_SWIZZLE_64B;
        map2d(&hs.qkv.x, x, DM, SEQ, 64, 256, S128);
        hs.qkv.xp = x; hs.qkv.wp = wqkv;
        {
            uint64_t dims[4] = {64, (uint64_t)DM, 3, 16}, st[3] = {3 * DM * 2, DM * 2, 128}; uint32_t box[4] = {64, 64, 3, 1};
            make_map(&hs.qkv.w, wqkv, 4, dims, st, box, S128);
        }
        map2d(&hs.qkv.out, hs.qkvp, HD, 3 * NH * SEQ, 32, 128, S64);
        hs.attn.kv = hs.qkv.out;
        map2d(&hs.attn.o, hs.o, DM, SEQ, 32, 16, S64); hs.attn.optr = hs.o;
        {
            uint64_t dims[3] = {(uint64_t)HD, (uint64_t)NH * SEQ, 3}, st[2] = {HD * 2, (uint64_t)NH * SEQ * HD * 2}; uint32_t box[3] = {32, 128, 2};
            make_map(&hs.attn.kv2, hs.qkvp, 3, dims, st, box, S64);
        }
        map2d(&hs.wo.a, hs.o, DM, SEQ, 64, ResCfg<false>::MC ? 64 : 128, S128);
        map3d(&hs.wo.b, wo, DM, DM, 64, 64, 2, S128);
        map2d(&hs.wo.res, x, DM, SEQ, 64, 128, S128);
        map2d(&hs.wo.out, hs.hn, DM, SEQ, 64, 64, S128);
        hs.wo.bias = nullptr;
        map3d(&hs.mix1.hn, hs.hn, DM, SEQ, 64, 64, 2, S128);
        map3d(&hs.mix1.w1, w1, FF, SEQ, 32, 32, 7, S64);
        hs.mix1.pf = (const uint8_t*)w2;
        hs.attn.pf_wo = (const uint8_t*)wo; hs.attn.pf_w1 = (const uint8_t*)w1; hs.attn.pf_x = (const uint8_t*)x;
        map3d(&hs.mix1.out, hs.u, FF, DM, 32, 64, 1, S64);
        hs.mix1.bias = b1;
        map3d(&hs.mix2.a, w2, SEQ, FF, 64, 64, ResCfg<true>::MC ? 1 : 2, S128);
        map2d(&hs.mix2.b, hs.u, FF, DM, 64, 128, S128);
        map2d(&hs.mix2.res, hs.hn, DM, SEQ, 64, 128, S128);
        map2d(&hs.mix2.out, d_out, DM, SEQ, 64, 64, S128);
        hs.mix2.bias = b2;
        for (int i = 0; i < 8; i++) hs.key[i] = d_in[i];
        hs.key[8] = d_out;
        hs.ready = true;
    }
    const bool pdl = USE_PDL;
    const int G = 128;
    launch(qkv_kernel, G, 384, QkvCfg::SMEM, false, QkvCfg::PAIR, hs.qkv);
    launch(attn_kernel, 128, 512, AT_SMEM, pdl, false, hs.attn);
    launch(res_gemm_kernel<false>, G, 384, ResCfg<false>::SMEM, pdl, ResCfg<false>::PAIR, hs.wo);
    launch(mix1_kernel, G, 384, Mix1Cfg::SMEM, pdl, Mix1Cfg::PAIR, hs.mix1);
    launch(res_gemm_kernel<true>, G, 384, ResCfg<true>::SMEM, pdl, ResCfg<true>::PAIR, hs.mix2);
}
```

```cpp
#include <cuda_runtime.h>
#include <cuda_bf16.h>
#include <cuda.h>
#include <stdint.h>
#include <stdio.h>

typedef __nv_bfloat16 bf16;

namespace {

#define SKEW 0
#define POLY_MASK_B POLY_MASK
#define POLY_MASK 0x12492449u
#define MIX1_MC true
#define MIX2_MC false
#define WO_MC false
#define MIX1_PAIR false
#define MIX2_PAIR true
#define WO_PAIR true
#define MIX2_MAP 1
#define WO_MAP 1
#define WO_SYNC 0
#define MIX1_SYNC 0
#define MIX2_SYNC 0
#define MIX1_PRE 2
#define WO_PRE 1
#define MIX2_PRE 1
#define PF_W1 4
#define PF_W2_DELAY 10000
#define WO_INIT true
#define MIX2_INIT true
#define O_DIRECT 1
#define PAIR_POLY 1
#define PMASK_A 0x4924
#define PMASK_B PMASK_A
#define ATTN_PIPE 1
#define QMASK_0 0xF0
#define QMASK_1 0xF0
#define QMASK_2 0xF0
#define QMASK_3 0xF0
#define EXP_FX 2
#define IMM_DESC 1
#define QT_N 3
#define QT_STEP 2
#define MIX1_TK 0
#define QKV_PRE 0
#define QKV_EARLY 1
#define PF_X 0
#define PF_REV 3
#define PF_W2 2
constexpr int SEQ = 2048, DM = 1024, NH = 32, HD = 32, FF = 3584;

__device__ __align__(1024) bf16 g_qkv[3 * NH * SEQ * HD];
__device__ __align__(1024) bf16 g_o[SEQ * DM];
__device__ __align__(1024) bf16 g_hn[SEQ * DM];
__device__ __align__(1024) bf16 g_u[DM * FF];
__device__ __align__(16) uint32_t g_norm[3 * NH * 128];
__device__ float2 g_rowstat[SEQ];
__device__ float g_colsum[8 * 3 * DM];
__device__ float2 g_rowln[SEQ];
__device__ __align__(16) unsigned long long g_hpart[SEQ * 8];
__device__ uint32_t g_cnt_row[8], g_cnt_col[16];

#define TL(kern, slot)
#define AT(slot)

__device__ __forceinline__ uint32_t smem_u32(const void* p) { return (uint32_t)__cvta_generic_to_shared(p); }
__device__ __forceinline__ void mbar_init(uint32_t bar, uint32_t cnt) { asm volatile("mbarrier.init.shared::cta.b64 [%0], %1;" :: "r"(bar), "r"(cnt) : "memory"); }
__device__ __forceinline__ void mbar_expect_tx(uint32_t bar, uint32_t bytes) { asm volatile("mbarrier.arrive.expect_tx.shared::cta.b64 _, [%0], %1;" :: "r"(bar), "r"(bytes) : "memory"); }
__device__ __forceinline__ void mbar_arrive(uint32_t bar) { asm volatile("mbarrier.arrive.shared::cta.b64 _, [%0];" :: "r"(bar) : "memory"); }
__device__ __forceinline__ void mbar_wait(uint32_t bar, uint32_t parity) {
    asm volatile("{\n.reg .pred p;\nWAIT_%=:\nmbarrier.try_wait.parity.shared::cta.b64 p, [%0], %1;\n@p bra DONE_%=;\nbra WAIT_%=;\nDONE_%=:\n}" :: "r"(bar), "r"(parity) : "memory");
}
__device__ __forceinline__ void fence_barrier_init() { asm volatile("fence.mbarrier_init.release.cluster;" ::: "memory"); }
__device__ __forceinline__ void fence_proxy_async() { asm volatile("fence.proxy.async.shared::cta;" ::: "memory"); }
__device__ __forceinline__ void pdl_launch() { asm volatile("griddepcontrol.launch_dependents;" ::: "memory"); }
__device__ __forceinline__ void pdl_wait() { asm volatile("griddepcontrol.wait;" ::: "memory"); }
__device__ __forceinline__ void named_bar(int id, int n) { asm volatile("bar.sync %0, %1;" :: "r"(id), "r"(n) : "memory"); }
__device__ __forceinline__ void named_arrive(int id, int n) { asm volatile("bar.arrive %0, %1;" :: "r"(id), "r"(n) : "memory"); }
__device__ __forceinline__ void hand_over(int id) { named_arrive(id, 160); }
__device__ __forceinline__ void take_over(int id) { named_bar(id, 160); fence_proxy_async(); }
__device__ __forceinline__ void prefetch_map(const CUtensorMap* m) { asm volatile("prefetch.tensormap [%0];" :: "l"(m) : "memory"); }

__device__ __forceinline__ void tma_ld2(uint32_t dst, const CUtensorMap* m, uint32_t bar, int c0, int c1) {
    asm volatile("cp.async.bulk.tensor.2d.shared::cluster.global.mbarrier::complete_tx::bytes [%0], [%1, {%3, %4}], [%2];"
                 :: "r"(dst), "l"(m), "r"(bar), "r"(c0), "r"(c1) : "memory");
}
__device__ __forceinline__ void tma_ld3(uint32_t dst, const CUtensorMap* m, uint32_t bar, int c0, int c1, int c2) {
    asm volatile("cp.async.bulk.tensor.3d.shared::cluster.global.mbarrier::complete_tx::bytes [%0], [%1, {%3, %4, %5}], [%2];"
                 :: "r"(dst), "l"(m), "r"(bar), "r"(c0), "r"(c1), "r"(c2) : "memory");
}
__device__ __forceinline__ void tma_ld4(uint32_t dst, const CUtensorMap* m, uint32_t bar, int c0, int c1, int c2, int c3) {
    asm volatile("cp.async.bulk.tensor.4d.shared::cluster.global.mbarrier::complete_tx::bytes [%0], [%1, {%3, %4, %5, %6}], [%2];"
                 :: "r"(dst), "l"(m), "r"(bar), "r"(c0), "r"(c1), "r"(c2), "r"(c3) : "memory");
}
__device__ __forceinline__ void tma_ld3_mc(uint32_t dst, const CUtensorMap* m, uint32_t bar, int c0, int c1, int c2) {
    asm volatile("cp.async.bulk.tensor.3d.shared::cluster.global.mbarrier::complete_tx::bytes.multicast::cluster [%0], [%1, {%3, %4, %5}], [%2], %6;"
                 :: "r"(dst), "l"(m), "r"(bar), "r"(c0), "r"(c1), "r"(c2), "h"((uint16_t)3) : "memory");
}
__device__ __forceinline__ void tma_ld2_mc(uint32_t dst, const CUtensorMap* m, uint32_t bar, int c0, int c1) {
    asm volatile("cp.async.bulk.tensor.2d.shared::cluster.global.mbarrier::complete_tx::bytes.multicast::cluster [%0], [%1, {%3, %4}], [%2], %5;"
                 :: "r"(dst), "l"(m), "r"(bar), "r"(c0), "r"(c1), "h"((uint16_t)3) : "memory");
}
__device__ __forceinline__ void prefetch_line(const void* p) { asm volatile("prefetch.global.L2 [%0];" :: "l"(p)); }
__device__ __forceinline__ void l2_prefetch(const void* p, uint32_t bytes) { asm volatile("cp.async.bulk.prefetch.L2.global [%0], %1;" :: "l"(p), "r"(bytes) : "memory"); }
__device__ __forceinline__ uint32_t mapa(uint32_t addr, uint32_t cta) { uint32_t r; asm("mapa.shared::cluster.u32 %0, %1, %2;" : "=r"(r) : "r"(addr), "r"(cta)); return r; }
__device__ __forceinline__ void mbar_arrive_cluster(uint32_t bar) { asm volatile("mbarrier.arrive.shared::cluster.b64 _, [%0];" :: "r"(bar) : "memory"); }
__device__ __forceinline__ void cluster_arrive() { asm volatile("barrier.cluster.arrive.relaxed.aligned;" ::: "memory"); }
__device__ __forceinline__ void cluster_wait() { asm volatile("barrier.cluster.wait.aligned;" ::: "memory"); }
__device__ __forceinline__ void tma_st2(const CUtensorMap* m, uint32_t src, int c0, int c1) {
    asm volatile("cp.async.bulk.tensor.2d.global.shared::cta.bulk_group [%0, {%2, %3}], [%1];" :: "l"(m), "r"(src), "r"(c0), "r"(c1) : "memory");
}
__device__ __forceinline__ void tma_st3(const CUtensorMap* m, uint32_t src, int c0, int c1, int c2) {
    asm volatile("cp.async.bulk.tensor.3d.global.shared::cta.bulk_group [%0, {%2, %3, %4}], [%1];" :: "l"(m), "r"(src), "r"(c0), "r"(c1), "r"(c2) : "memory");
}
__device__ __forceinline__ void tma_st_commit() { asm volatile("cp.async.bulk.commit_group;" ::: "memory"); }
__device__ __forceinline__ void tma_st_wait() { asm volatile("cp.async.bulk.wait_group.read 0;" ::: "memory"); }

__device__ __forceinline__ void wg_fence() { asm volatile("wgmma.fence.sync.aligned;" ::: "memory"); }
__device__ __forceinline__ void wg_commit() { asm volatile("wgmma.commit_group.sync.aligned;" ::: "memory"); }
template <int N> __device__ __forceinline__ void wg_wait() { asm volatile("wgmma.wait_group.sync.aligned %0;" :: "n"(N) : "memory"); }
template <int R> __device__ __forceinline__ void reg_alloc() { asm volatile("setmaxnreg.inc.sync.aligned.u32 %0;" :: "n"(R)); }
template <int R> __device__ __forceinline__ void reg_dealloc() { asm volatile("setmaxnreg.dec.sync.aligned.u32 %0;" :: "n"(R)); }
template <int N> __device__ __forceinline__ void fence_regs(float (&d)[N]) {
#pragma unroll
    for (int i = 0; i < N; i++) asm volatile("" : "+f"(d[i]) :: "memory");
}

__device__ __forceinline__ uint32_t desc_lo(uint32_t addr, uint32_t lbo) { return ((addr & 0x3FFFFu) >> 4) | ((lbo >> 4) << 16); }
__device__ __forceinline__ uint32_t pack_bf16(float lo, float hi) { uint32_t d; asm("cvt.rn.bf16x2.f32 %0, %1, %2;" : "=r"(d) : "f"(hi), "f"(lo)); return d; }
__device__ __forceinline__ float bf_lo(uint32_t v) { return __uint_as_float(v << 16); }
__device__ __forceinline__ float bf_hi(uint32_t v) { return __uint_as_float(v & 0xFFFF0000u); }
__device__ __forceinline__ void stmatrix_x4(uint32_t addr, uint32_t r0, uint32_t r1, uint32_t r2, uint32_t r3) {
    asm volatile("stmatrix.sync.aligned.m8n8.x4.shared.b16 [%0], {%1, %2, %3, %4};" :: "r"(addr), "r"(r0), "r"(r1), "r"(r2), "r"(r3));
}
__device__ __forceinline__ void ldmatrix_x4(uint32_t addr, uint32_t (&r)[4]) {
    asm volatile("ldmatrix.sync.aligned.m8n8.x4.shared.b16 {%0, %1, %2, %3}, [%4];" : "=r"(r[0]), "=r"(r[1]), "=r"(r[2]), "=r"(r[3]) : "r"(addr) : "memory");
}
__device__ __forceinline__ float ex2(float x) { float y; asm("ex2.approx.ftz.f32 %0, %1;" : "=f"(y) : "f"(x)); return y; }
__device__ __forceinline__ float tanh_fast(float x) { float y; asm("tanh.approx.f32 %0, %1;" : "=f"(y) : "f"(x)); return y; }

__device__ __forceinline__ void mma_qkv(float (&d)[96], uint32_t alo, uint32_t blo, int scale_d) {
    asm volatile("{\n.reg .pred p;\n.reg .b64 da, db;\nsetp.ne.b32 p, %98, 0;\nmov.b64 da, {%96, 0x40000040};\nmov.b64 db, {%97, 0x40000040};\n"
        "wgmma.mma_async.sync.aligned.m64n192k16.f32.bf16.bf16 {"
        "%0, %1, %2, %3, %4, %5, %6, %7, %8, %9, %10, %11, %12, %13, %14, %15, %16, %17, %18, %19, %20, %21, %22, %23, %24, %25, %26, %27, %28, %29, %30, %31,  "
        "%32, %33, %34, %35, %36, %37, %38, %39, %40, %41, %42, %43, %44, %45, %46, %47, %48, %49, %50, %51, %52, %53, %54, %55, %56, %57, %58, %59, %60, %61,  "
        "%62, %63, %64, %65, %66, %67, %68, %69, %70, %71, %72, %73, %74, %75, %76, %77, %78, %79, %80, %81, %82, %83, %84, %85, %86, %87, %88, %89, %90, %91,  "
        "%92, %93, %94, %95 "
        "}, da, db, p, 1, 1, 0, 1;\n}\n"
        : "+f"(d[0]), "+f"(d[1]), "+f"(d[2]), "+f"(d[3]), "+f"(d[4]), "+f"(d[5]), "+f"(d[6]), "+f"(d[7]), "+f"(d[8]), "+f"(d[9]), "+f"(d[10]), "+f"(d[11]),
          "+f"(d[12]), "+f"(d[13]), "+f"(d[14]), "+f"(d[15]), "+f"(d[16]), "+f"(d[17]), "+f"(d[18]), "+f"(d[19]), "+f"(d[20]), "+f"(d[21]), "+f"(d[22]),
          "+f"(d[23]), "+f"(d[24]), "+f"(d[25]), "+f"(d[26]), "+f"(d[27]), "+f"(d[28]), "+f"(d[29]), "+f"(d[30]), "+f"(d[31]), "+f"(d[32]), "+f"(d[33]),
          "+f"(d[34]), "+f"(d[35]), "+f"(d[36]), "+f"(d[37]), "+f"(d[38]), "+f"(d[39]), "+f"(d[40]), "+f"(d[41]), "+f"(d[42]), "+f"(d[43]), "+f"(d[44]),
          "+f"(d[45]), "+f"(d[46]), "+f"(d[47]), "+f"(d[48]), "+f"(d[49]), "+f"(d[50]), "+f"(d[51]), "+f"(d[52]), "+f"(d[53]), "+f"(d[54]), "+f"(d[55]),
          "+f"(d[56]), "+f"(d[57]), "+f"(d[58]), "+f"(d[59]), "+f"(d[60]), "+f"(d[61]), "+f"(d[62]), "+f"(d[63]), "+f"(d[64]), "+f"(d[65]), "+f"(d[66]),
          "+f"(d[67]), "+f"(d[68]), "+f"(d[69]), "+f"(d[70]), "+f"(d[71]), "+f"(d[72]), "+f"(d[73]), "+f"(d[74]), "+f"(d[75]), "+f"(d[76]), "+f"(d[77]),
          "+f"(d[78]), "+f"(d[79]), "+f"(d[80]), "+f"(d[81]), "+f"(d[82]), "+f"(d[83]), "+f"(d[84]), "+f"(d[85]), "+f"(d[86]), "+f"(d[87]), "+f"(d[88]),
          "+f"(d[89]), "+f"(d[90]), "+f"(d[91]), "+f"(d[92]), "+f"(d[93]), "+f"(d[94]), "+f"(d[95])
        : "r"(alo), "r"(blo), "r"(scale_d));
}
__device__ __forceinline__ void mma_wo(float (&d)[64], uint32_t alo, uint32_t blo, int scale_d) {
    asm volatile("{\n.reg .pred p;\n.reg .b64 da, db;\nsetp.ne.b32 p, %66, 0;\nmov.b64 da, {%64, 0x40000040};\nmov.b64 db, {%65, 0x40000040};\n"
        "wgmma.mma_async.sync.aligned.m64n128k16.f32.bf16.bf16 {"
        "%0, %1, %2, %3, %4, %5, %6, %7, %8, %9, %10, %11, %12, %13, %14, %15, %16, %17, %18, %19, %20, %21, %22, %23, %24, %25, %26, %27, %28, %29, %30, %31,  "
        "%32, %33, %34, %35, %36, %37, %38, %39, %40, %41, %42, %43, %44, %45, %46, %47, %48, %49, %50, %51, %52, %53, %54, %55, %56, %57, %58, %59, %60, %61,  "
        "%62, %63 "
        "}, da, db, p, 1, 1, 0, 1;\n}\n"
        : "+f"(d[0]), "+f"(d[1]), "+f"(d[2]), "+f"(d[3]), "+f"(d[4]), "+f"(d[5]), "+f"(d[6]), "+f"(d[7]), "+f"(d[8]), "+f"(d[9]), "+f"(d[10]), "+f"(d[11]),
          "+f"(d[12]), "+f"(d[13]), "+f"(d[14]), "+f"(d[15]), "+f"(d[16]), "+f"(d[17]), "+f"(d[18]), "+f"(d[19]), "+f"(d[20]), "+f"(d[21]), "+f"(d[22]),
          "+f"(d[23]), "+f"(d[24]), "+f"(d[25]), "+f"(d[26]), "+f"(d[27]), "+f"(d[28]), "+f"(d[29]), "+f"(d[30]), "+f"(d[31]), "+f"(d[32]), "+f"(d[33]),
          "+f"(d[34]), "+f"(d[35]), "+f"(d[36]), "+f"(d[37]), "+f"(d[38]), "+f"(d[39]), "+f"(d[40]), "+f"(d[41]), "+f"(d[42]), "+f"(d[43]), "+f"(d[44]),
          "+f"(d[45]), "+f"(d[46]), "+f"(d[47]), "+f"(d[48]), "+f"(d[49]), "+f"(d[50]), "+f"(d[51]), "+f"(d[52]), "+f"(d[53]), "+f"(d[54]), "+f"(d[55]),
          "+f"(d[56]), "+f"(d[57]), "+f"(d[58]), "+f"(d[59]), "+f"(d[60]), "+f"(d[61]), "+f"(d[62]), "+f"(d[63])
        : "r"(alo), "r"(blo), "r"(scale_d));
}
__device__ __forceinline__ void mma_mix2(float (&d)[64], uint32_t alo, uint32_t blo, int scale_d) {
    asm volatile("{\n.reg .pred p;\n.reg .b64 da, db;\nsetp.ne.b32 p, %66, 0;\nmov.b64 da, {%64, 0x40000040};\nmov.b64 db, {%65, 0x40000040};\n"
        "wgmma.mma_async.sync.aligned.m64n128k16.f32.bf16.bf16 {"
        "%0, %1, %2, %3, %4, %5, %6, %7, %8, %9, %10, %11, %12, %13, %14, %15, %16, %17, %18, %19, %20, %21, %22, %23, %24, %25, %26, %27, %28, %29, %30, %31,  "
        "%32, %33, %34, %35, %36, %37, %38, %39, %40, %41, %42, %43, %44, %45, %46, %47, %48, %49, %50, %51, %52, %53, %54, %55, %56, %57, %58, %59, %60, %61,  "
        "%62, %63 "
        "}, da, db, p, 1, 1, 1, 0;\n}\n"
        : "+f"(d[0]), "+f"(d[1]), "+f"(d[2]), "+f"(d[3]), "+f"(d[4]), "+f"(d[5]), "+f"(d[6]), "+f"(d[7]), "+f"(d[8]), "+f"(d[9]), "+f"(d[10]), "+f"(d[11]),
          "+f"(d[12]), "+f"(d[13]), "+f"(d[14]), "+f"(d[15]), "+f"(d[16]), "+f"(d[17]), "+f"(d[18]), "+f"(d[19]), "+f"(d[20]), "+f"(d[21]), "+f"(d[22]),
          "+f"(d[23]), "+f"(d[24]), "+f"(d[25]), "+f"(d[26]), "+f"(d[27]), "+f"(d[28]), "+f"(d[29]), "+f"(d[30]), "+f"(d[31]), "+f"(d[32]), "+f"(d[33]),
          "+f"(d[34]), "+f"(d[35]), "+f"(d[36]), "+f"(d[37]), "+f"(d[38]), "+f"(d[39]), "+f"(d[40]), "+f"(d[41]), "+f"(d[42]), "+f"(d[43]), "+f"(d[44]),
          "+f"(d[45]), "+f"(d[46]), "+f"(d[47]), "+f"(d[48]), "+f"(d[49]), "+f"(d[50]), "+f"(d[51]), "+f"(d[52]), "+f"(d[53]), "+f"(d[54]), "+f"(d[55]),
          "+f"(d[56]), "+f"(d[57]), "+f"(d[58]), "+f"(d[59]), "+f"(d[60]), "+f"(d[61]), "+f"(d[62]), "+f"(d[63])
        : "r"(alo), "r"(blo), "r"(scale_d));
}
__device__ __forceinline__ void mma_mix1(float (&d)[112], uint32_t alo, uint32_t blo, int scale_d) {
    asm volatile("{\n.reg .pred p;\n.reg .b64 da, db;\nsetp.ne.b32 p, %114, 0;\nmov.b64 da, {%112, 0x40000040};\nmov.b64 db, {%113, 0x80000020};\n"
        "wgmma.mma_async.sync.aligned.m64n224k16.f32.bf16.bf16 {"
        "%0, %1, %2, %3, %4, %5, %6, %7, %8, %9, %10, %11, %12, %13, %14, %15, %16, %17, %18, %19, %20, %21, %22, %23, %24, %25, %26, %27, %28, %29, %30, %31,  "
        "%32, %33, %34, %35, %36, %37, %38, %39, %40, %41, %42, %43, %44, %45, %46, %47, %48, %49, %50, %51, %52, %53, %54, %55, %56, %57, %58, %59, %60, %61,  "
        "%62, %63, %64, %65, %66, %67, %68, %69, %70, %71, %72, %73, %74, %75, %76, %77, %78, %79, %80, %81, %82, %83, %84, %85, %86, %87, %88, %89, %90, %91,  "
        "%92, %93, %94, %95, %96, %97, %98, %99, %100, %101, %102, %103, %104, %105, %106, %107, %108, %109, %110, %111 "
        "}, da, db, p, 1, 1, 1, 1;\n}\n"
        : "+f"(d[0]), "+f"(d[1]), "+f"(d[2]), "+f"(d[3]), "+f"(d[4]), "+f"(d[5]), "+f"(d[6]), "+f"(d[7]), "+f"(d[8]), "+f"(d[9]), "+f"(d[10]), "+f"(d[11]),
          "+f"(d[12]), "+f"(d[13]), "+f"(d[14]), "+f"(d[15]), "+f"(d[16]), "+f"(d[17]), "+f"(d[18]), "+f"(d[19]), "+f"(d[20]), "+f"(d[21]), "+f"(d[22]),
          "+f"(d[23]), "+f"(d[24]), "+f"(d[25]), "+f"(d[26]), "+f"(d[27]), "+f"(d[28]), "+f"(d[29]), "+f"(d[30]), "+f"(d[31]), "+f"(d[32]), "+f"(d[33]),
          "+f"(d[34]), "+f"(d[35]), "+f"(d[36]), "+f"(d[37]), "+f"(d[38]), "+f"(d[39]), "+f"(d[40]), "+f"(d[41]), "+f"(d[42]), "+f"(d[43]), "+f"(d[44]),
          "+f"(d[45]), "+f"(d[46]), "+f"(d[47]), "+f"(d[48]), "+f"(d[49]), "+f"(d[50]), "+f"(d[51]), "+f"(d[52]), "+f"(d[53]), "+f"(d[54]), "+f"(d[55]),
          "+f"(d[56]), "+f"(d[57]), "+f"(d[58]), "+f"(d[59]), "+f"(d[60]), "+f"(d[61]), "+f"(d[62]), "+f"(d[63]), "+f"(d[64]), "+f"(d[65]), "+f"(d[66]),
          "+f"(d[67]), "+f"(d[68]), "+f"(d[69]), "+f"(d[70]), "+f"(d[71]), "+f"(d[72]), "+f"(d[73]), "+f"(d[74]), "+f"(d[75]), "+f"(d[76]), "+f"(d[77]),
          "+f"(d[78]), "+f"(d[79]), "+f"(d[80]), "+f"(d[81]), "+f"(d[82]), "+f"(d[83]), "+f"(d[84]), "+f"(d[85]), "+f"(d[86]), "+f"(d[87]), "+f"(d[88]),
          "+f"(d[89]), "+f"(d[90]), "+f"(d[91]), "+f"(d[92]), "+f"(d[93]), "+f"(d[94]), "+f"(d[95]), "+f"(d[96]), "+f"(d[97]), "+f"(d[98]), "+f"(d[99]),
          "+f"(d[100]), "+f"(d[101]), "+f"(d[102]), "+f"(d[103]), "+f"(d[104]), "+f"(d[105]), "+f"(d[106]), "+f"(d[107]), "+f"(d[108]), "+f"(d[109]),
          "+f"(d[110]), "+f"(d[111])
        : "r"(alo), "r"(blo), "r"(scale_d));
}
__device__ __forceinline__ void mma_qk0(float (&d)[32], uint32_t alo, uint32_t blo) {
    asm volatile("{\n.reg .pred p;\n.reg .b64 da, db;\nsetp.ne.b32 p, 0, 0;\nmov.b64 da, {%32, 0x80000020};\nmov.b64 db, {%33, 0x80000020};\n"
        "wgmma.mma_async.sync.aligned.m64n64k16.f32.bf16.bf16 {"
        "%0, %1, %2, %3, %4, %5, %6, %7, %8, %9, %10, %11, %12, %13, %14, %15, %16, %17, %18, %19, %20, %21, %22, %23, %24, %25, %26, %27, %28, %29, %30, %31 "
        "}, da, db, p, 1, 1, 0, 0;\n}\n"
        : "=f"(d[0]), "=f"(d[1]), "=f"(d[2]), "=f"(d[3]), "=f"(d[4]), "=f"(d[5]), "=f"(d[6]), "=f"(d[7]), "=f"(d[8]), "=f"(d[9]), "=f"(d[10]), "=f"(d[11]),
          "=f"(d[12]), "=f"(d[13]), "=f"(d[14]), "=f"(d[15]), "=f"(d[16]), "=f"(d[17]), "=f"(d[18]), "=f"(d[19]), "=f"(d[20]), "=f"(d[21]), "=f"(d[22]),
          "=f"(d[23]), "=f"(d[24]), "=f"(d[25]), "=f"(d[26]), "=f"(d[27]), "=f"(d[28]), "=f"(d[29]), "=f"(d[30]), "=f"(d[31])
        : "r"(alo), "r"(blo));
}
__device__ __forceinline__ void mma_qk1(float (&d)[32], uint32_t alo, uint32_t blo, int scale_d) {
    asm volatile("{\n.reg .pred p;\n.reg .b64 da, db;\nsetp.ne.b32 p, %34, 0;\nmov.b64 da, {%32, 0x80000020};\nmov.b64 db, {%33, 0x80000020};\n"
        "wgmma.mma_async.sync.aligned.m64n64k16.f32.bf16.bf16 {"
        "%0, %1, %2, %3, %4, %5, %6, %7, %8, %9, %10, %11, %12, %13, %14, %15, %16, %17, %18, %19, %20, %21, %22, %23, %24, %25, %26, %27, %28, %29, %30, %31 "
        "}, da, db, p, 1, 1, 0, 0;\n}\n"
        : "+f"(d[0]), "+f"(d[1]), "+f"(d[2]), "+f"(d[3]), "+f"(d[4]), "+f"(d[5]), "+f"(d[6]), "+f"(d[7]), "+f"(d[8]), "+f"(d[9]), "+f"(d[10]), "+f"(d[11]),
          "+f"(d[12]), "+f"(d[13]), "+f"(d[14]), "+f"(d[15]), "+f"(d[16]), "+f"(d[17]), "+f"(d[18]), "+f"(d[19]), "+f"(d[20]), "+f"(d[21]), "+f"(d[22]),
          "+f"(d[23]), "+f"(d[24]), "+f"(d[25]), "+f"(d[26]), "+f"(d[27]), "+f"(d[28]), "+f"(d[29]), "+f"(d[30]), "+f"(d[31])
        : "r"(alo), "r"(blo), "r"(scale_d));
}
__device__ __forceinline__ void mma_qkw0(float (&d)[64], uint32_t alo, uint32_t blo) {
    asm volatile("{\n.reg .pred p;\n.reg .b64 da, db;\nsetp.ne.b32 p, 0, 0;\nmov.b64 da, {%64, 0x80000020};\nmov.b64 db, {%65, 0x80000020};\n"
        "wgmma.mma_async.sync.aligned.m64n128k16.f32.bf16.bf16 {"
        "%0, %1, %2, %3, %4, %5, %6, %7, %8, %9, %10, %11, %12, %13, %14, %15, %16, %17, %18, %19, %20, %21, %22, %23, %24, %25, %26, %27, %28, %29, %30, %31,  "
        "%32, %33, %34, %35, %36, %37, %38, %39, %40, %41, %42, %43, %44, %45, %46, %47, %48, %49, %50, %51, %52, %53, %54, %55, %56, %57, %58, %59, %60, %61,  "
        "%62, %63 "
        "}, da, db, p, 1, 1, 0, 0;\n}\n"
        : "=f"(d[0]), "=f"(d[1]), "=f"(d[2]), "=f"(d[3]), "=f"(d[4]), "=f"(d[5]), "=f"(d[6]), "=f"(d[7]), "=f"(d[8]), "=f"(d[9]), "=f"(d[10]), "=f"(d[11]),
          "=f"(d[12]), "=f"(d[13]), "=f"(d[14]), "=f"(d[15]), "=f"(d[16]), "=f"(d[17]), "=f"(d[18]), "=f"(d[19]), "=f"(d[20]), "=f"(d[21]), "=f"(d[22]),
          "=f"(d[23]), "=f"(d[24]), "=f"(d[25]), "=f"(d[26]), "=f"(d[27]), "=f"(d[28]), "=f"(d[29]), "=f"(d[30]), "=f"(d[31]), "=f"(d[32]), "=f"(d[33]),
          "=f"(d[34]), "=f"(d[35]), "=f"(d[36]), "=f"(d[37]), "=f"(d[38]), "=f"(d[39]), "=f"(d[40]), "=f"(d[41]), "=f"(d[42]), "=f"(d[43]), "=f"(d[44]),
          "=f"(d[45]), "=f"(d[46]), "=f"(d[47]), "=f"(d[48]), "=f"(d[49]), "=f"(d[50]), "=f"(d[51]), "=f"(d[52]), "=f"(d[53]), "=f"(d[54]), "=f"(d[55]),
          "=f"(d[56]), "=f"(d[57]), "=f"(d[58]), "=f"(d[59]), "=f"(d[60]), "=f"(d[61]), "=f"(d[62]), "=f"(d[63])
        : "r"(alo), "r"(blo));
}
__device__ __forceinline__ void mma_qkw1(float (&d)[64], uint32_t alo, uint32_t blo, int scale_d) {
    asm volatile("{\n.reg .pred p;\n.reg .b64 da, db;\nsetp.ne.b32 p, %66, 0;\nmov.b64 da, {%64, 0x80000020};\nmov.b64 db, {%65, 0x80000020};\n"
        "wgmma.mma_async.sync.aligned.m64n128k16.f32.bf16.bf16 {"
        "%0, %1, %2, %3, %4, %5, %6, %7, %8, %9, %10, %11, %12, %13, %14, %15, %16, %17, %18, %19, %20, %21, %22, %23, %24, %25, %26, %27, %28, %29, %30, %31,  "
        "%32, %33, %34, %35, %36, %37, %38, %39, %40, %41, %42, %43, %44, %45, %46, %47, %48, %49, %50, %51, %52, %53, %54, %55, %56, %57, %58, %59, %60, %61,  "
        "%62, %63 "
        "}, da, db, p, 1, 1, 0, 0;\n}\n"
        : "+f"(d[0]), "+f"(d[1]), "+f"(d[2]), "+f"(d[3]), "+f"(d[4]), "+f"(d[5]), "+f"(d[6]), "+f"(d[7]), "+f"(d[8]), "+f"(d[9]), "+f"(d[10]), "+f"(d[11]),
          "+f"(d[12]), "+f"(d[13]), "+f"(d[14]), "+f"(d[15]), "+f"(d[16]), "+f"(d[17]), "+f"(d[18]), "+f"(d[19]), "+f"(d[20]), "+f"(d[21]), "+f"(d[22]),
          "+f"(d[23]), "+f"(d[24]), "+f"(d[25]), "+f"(d[26]), "+f"(d[27]), "+f"(d[28]), "+f"(d[29]), "+f"(d[30]), "+f"(d[31]), "+f"(d[32]), "+f"(d[33]),
          "+f"(d[34]), "+f"(d[35]), "+f"(d[36]), "+f"(d[37]), "+f"(d[38]), "+f"(d[39]), "+f"(d[40]), "+f"(d[41]), "+f"(d[42]), "+f"(d[43]), "+f"(d[44]),
          "+f"(d[45]), "+f"(d[46]), "+f"(d[47]), "+f"(d[48]), "+f"(d[49]), "+f"(d[50]), "+f"(d[51]), "+f"(d[52]), "+f"(d[53]), "+f"(d[54]), "+f"(d[55]),
          "+f"(d[56]), "+f"(d[57]), "+f"(d[58]), "+f"(d[59]), "+f"(d[60]), "+f"(d[61]), "+f"(d[62]), "+f"(d[63])
        : "r"(alo), "r"(blo), "r"(scale_d));
}
__device__ __forceinline__ void mma_pv(float (&d)[20], uint32_t a0, uint32_t a1, uint32_t a2, uint32_t a3, uint32_t blo, int scale_d) {
    asm volatile("{\n.reg .pred p;\n.reg .b64 da, db;\nsetp.ne.b32 p, %25, 0;\nmov.b64 db, {%24, 0x80000020};\n"
        "wgmma.mma_async.sync.aligned.m64n40k16.f32.bf16.bf16 {"
        "%0, %1, %2, %3, %4, %5, %6, %7, %8, %9, %10, %11, %12, %13, %14, %15, %16, %17, %18, %19 "
        "}, {%20, %21, %22, %23}, db, p, 1, 1, 1;\n}\n"
        : "+f"(d[0]), "+f"(d[1]), "+f"(d[2]), "+f"(d[3]), "+f"(d[4]), "+f"(d[5]), "+f"(d[6]), "+f"(d[7]), "+f"(d[8]), "+f"(d[9]), "+f"(d[10]), "+f"(d[11]),
          "+f"(d[12]), "+f"(d[13]), "+f"(d[14]), "+f"(d[15]), "+f"(d[16]), "+f"(d[17]), "+f"(d[18]), "+f"(d[19])
        : "r"(a0), "r"(a1), "r"(a2), "r"(a3), "r"(blo), "r"(scale_d));
}

__device__ __forceinline__ float warp_sum(float v) {
#pragma unroll
    for (int o = 16; o > 0; o >>= 1) v += __shfl_xor_sync(0xffffffffu, v, o);
    return v;
}

struct GemmSmem { uint32_t base, full0, empty0, aux; };

struct NoEarly { __device__ __forceinline__ void operator()(const GemmSmem&) const {} };
template <class C, class E = NoEarly>
__device__ __forceinline__ GemmSmem gemm_setup(uint8_t* smem_raw, E early = E()) {
    GemmSmem s;
    s.base = smem_u32(smem_raw);
    s.full0 = s.base + C::BAR_OFF; s.empty0 = s.full0 + 8 * C::STAGES; s.aux = s.empty0 + 8 * C::STAGES;
    if (threadIdx.x == 0) {
        if (s.base & 1023) __trap();
        for (int i = 0; i < C::STAGES; i++) { mbar_init(s.full0 + 8 * i, 1); mbar_init(s.empty0 + 8 * i, C::MC ? 16 : 8); }
        mbar_init(s.aux, C::AUX_COUNT);
        fence_barrier_init();
        early(s);
    }
    __syncthreads();
    if (C::MC) { cluster_arrive(); cluster_wait(); }
    return s;
}

#define TK(slot)
#define TKC(slot)
#define TKW(slot)
template <class C, bool FILLED = false, class P>
__device__ __forceinline__ void gemm_producer(const GemmSmem& s, const P& p, int tm, int tn) {
    TK(8);
    if (!FILLED) {
    if (C::ACC_INIT) C::load_aux(p, s, tm, tn);
#pragma unroll 1
    for (int k = 0; k < C::PRE; k++) {
        mbar_expect_tx(s.full0 + 8 * k, C::STAGE_BYTES);
        C::load_w(p, s.base + k * C::STAGE_BYTES, s.full0 + 8 * k, k, tm, tn);
    }
    TK(9);
    pdl_wait();
    TK(10);
#pragma unroll 1
    for (int k = 0; k < C::STAGES; k++) {
        if (k >= C::PRE) mbar_expect_tx(s.full0 + 8 * k, C::STAGE_BYTES);
        C::load_x(p, s.base + k * C::STAGE_BYTES, s.full0 + 8 * k, k, tm, tn);
        if (k >= C::PRE) C::load_w(p, s.base + k * C::STAGE_BYTES, s.full0 + 8 * k, k, tm, tn);
    }
    TK(11);
    if (!C::ACC_INIT) C::load_aux(p, s, tm, tn);
    }
    int st = 0; uint32_t ph = 0;
#pragma unroll 1
    for (int k = C::STAGES; k < C::KSTEPS; k++) {
        mbar_wait(s.empty0 + 8 * st, ph);
        mbar_expect_tx(s.full0 + 8 * st, C::STAGE_BYTES);
        C::load_x(p, s.base + st * C::STAGE_BYTES, s.full0 + 8 * st, k, tm, tn);
        C::load_w(p, s.base + st * C::STAGE_BYTES, s.full0 + 8 * st, k, tm, tn);
        C::prefetch(p, k);
        if (++st == C::STAGES) { st = 0; ph ^= 1; }
    }
}

template <class C, int KEND = C::KSTEPS>
__device__ __forceinline__ void gemm_mainloop(const GemmSmem& s, int wg, float (&acc)[C::MB][C::BN / 2], int tlk = 0) {
    const int lane = threadIdx.x & 31;
    if constexpr (C::SYNC_NS > 0) {
        unsigned long long t0, t1; asm volatile("mov.u64 %0, %%globaltimer;" : "=l"(t0));
        do { asm volatile("mov.u64 %0, %%globaltimer;" : "=l"(t1)); } while (t1 - t0 < C::SYNC_NS);
    }
    int st = 0; uint32_t ph = 0;
    int prev = 0;
    const uint32_t rel0 = C::MC ? mapa(s.empty0, lane & 1) : s.empty0;
#pragma unroll
    for (int m = 0; m < C::MB; m++) fence_regs(acc[m]);
#pragma unroll 1
    for (int k = 0; k < KEND; k++) {
        mbar_wait(s.full0 + 8 * st, ph);
        const uint32_t sb = s.base + st * C::STAGE_BYTES;
        wg_fence();
#pragma unroll
        for (int kk = 0; kk < 4; kk++) {
#pragma unroll
            for (int m = 0; m < C::MB; m++) C::mma(acc[m], C::desc_a(sb, wg, m, kk), C::desc_b(sb, kk), C::ACC_INIT || (k | kk) != 0);
        }
        wg_commit();
        if (k > 0) {
            wg_wait<1>();
            if (k <= C::KSTEPS - C::STAGES) {
                if (C::MC) { if (lane < 2) mbar_arrive_cluster(rel0 + 8 * prev); }
                else if (lane == 0) mbar_arrive(rel0 + 8 * prev);
            }
        }
        prev = st;
        if (++st == C::STAGES) { st = 0; ph ^= 1; }
    }
    if (KEND == C::KSTEPS) {
        wg_wait<0>();
#pragma unroll
        for (int m = 0; m < C::MB; m++) fence_regs(acc[m]);
    }
}

struct QkvParams { CUtensorMap x, w, out, out64; const bf16* xp; const bf16* wp; };
struct QkvCfg {
    static constexpr int MB = 2, BN = 192, KSTEPS = 16, STAGES = 4, A_BYTES = 32768, B_BYTES = 24576;
    static constexpr int STAGE_BYTES = A_BYTES + B_BYTES, BAR_OFF = STAGES * STAGE_BYTES, AUX_OFF = BAR_OFF + 128, SMEM = AUX_OFF + 2816;
    static constexpr int AUX_COUNT = 3, PRE = QKV_PRE;
    static constexpr int TLK = 1;
    static constexpr bool MC = false, PAIR = false, ACC_INIT = false;
    static constexpr int SYNC_NS = 0;
    static __device__ __forceinline__ void prefetch(const QkvParams&, int) {}
    static __device__ __forceinline__ void load_w(const QkvParams& p, uint32_t sb, uint32_t bar, int k, int tm, int tn) { tma_ld4(sb + A_BYTES, &p.w, bar, 0, k * 64, 0, tn); }
    static __device__ __forceinline__ void load_x(const QkvParams& p, uint32_t sb, uint32_t bar, int k, int tm, int tn) { tma_ld2(sb, &p.x, bar, k * 64, tm * 256); }
    static __device__ __forceinline__ void load_aux(const QkvParams&, const GemmSmem&, int, int) {}
    static __device__ __forceinline__ uint32_t desc_a(uint32_t sb, int wg, int m, int kk) { return desc_lo(sb + (wg * 128 + m * 64) * 128 + kk * 32, 16); }
    static __device__ __forceinline__ uint32_t desc_b(uint32_t sb, int kk) { return desc_lo(sb + A_BYTES + kk * 2048, 8192); }
    static __device__ __forceinline__ void mma(float (&d)[96], uint32_t a, uint32_t b, int sc) { mma_qkv(d, a, b, sc); }
};

__device__ __forceinline__ void spin_until(const uint32_t* cnt, uint32_t target) {
    uint32_t v; int it = 0;
    do {
        asm volatile("ld.acquire.gpu.global.u32 %0, [%1];" : "=r"(v) : "l"(cnt) : "memory");
        if (++it > (1 << 22)) __trap();
    } while (v < target);
}
__device__ __forceinline__ void publish(uint32_t* cnt) { asm volatile("red.release.gpu.global.add.u32 [%0], 1;" :: "l"(cnt) : "memory"); }

__device__ __forceinline__ void qkv_aux(const QkvParams& p, uint8_t* smem_raw, const GemmSmem& s, int tm, int tn, int w, int lane) {
    for (int r = w; r < 16; r += 3) {
        const int row = tm * 256 + tn * 16 + r;
        const uint4* src = reinterpret_cast<const uint4*>(p.xp + (size_t)row * DM);
        uint32_t v[16];
#pragma unroll
        for (int i = 0; i < 4; i++) { const uint4 t = __ldg(src + lane + 32 * i); v[4 * i] = t.x; v[4 * i + 1] = t.y; v[4 * i + 2] = t.z; v[4 * i + 3] = t.w; }
        float sum = 0.f;
#pragma unroll
        for (int i = 0; i < 16; i++) sum += bf_lo(v[i]) + bf_hi(v[i]);
        const float mean = warp_sum(sum) * (1.f / DM);
        float q = 0.f;
#pragma unroll
        for (int i = 0; i < 16; i++) { const float a = bf_lo(v[i]) - mean, b = bf_hi(v[i]) - mean; q += a * a + b * b; }
        const float rstd = rsqrtf(warp_sum(q) * (1.f / DM) + 1e-5f);
        if (lane == 0) g_rowstat[row] = make_float2(mean, rstd);
    }
    __syncwarp();
    if (lane == 0) publish(&g_cnt_row[tm]);
    {
        const uint4* src = reinterpret_cast<const uint4*>(p.wp + (size_t)(tm * 128 + (lane >> 3)) * (3 * DM) + w * DM + tn * 64) + (lane & 7);
        float a[8];
#pragma unroll
        for (int i = 0; i < 8; i++) a[i] = 0.f;
#pragma unroll 1
        for (int j = 0; j < 32; j += 8) {
            uint4 t[8];
#pragma unroll
            for (int i = 0; i < 8; i++) t[i] = __ldg(src + (size_t)(j + i) * 4 * (3 * DM / 8));
#pragma unroll
            for (int i = 0; i < 8; i++) {
                a[0] += bf_lo(t[i].x); a[1] += bf_hi(t[i].x); a[2] += bf_lo(t[i].y); a[3] += bf_hi(t[i].y);
                a[4] += bf_lo(t[i].z); a[5] += bf_hi(t[i].z); a[6] += bf_lo(t[i].w); a[7] += bf_hi(t[i].w);
            }
        }
#pragma unroll
        for (int i = 0; i < 8; i++) { a[i] += __shfl_xor_sync(0xffffffffu, a[i], 8); a[i] += __shfl_xor_sync(0xffffffffu, a[i], 16); }
        if (lane < 8) {
            float4* dst = reinterpret_cast<float4*>(g_colsum + tm * (3 * DM) + tn * 192 + w * 64 + lane * 8);
            dst[0] = make_float4(a[0], a[1], a[2], a[3]); dst[1] = make_float4(a[4], a[5], a[6], a[7]);
        }
        __syncwarp();
        if (lane == 0) publish(&g_cnt_col[tn]);
    }
    float* scs = reinterpret_cast<float*>(smem_raw + QkvCfg::AUX_OFF);
    float2* sst = reinterpret_cast<float2*>(smem_raw + QkvCfg::AUX_OFF + 768);
    const int t = w * 32 + lane;
    spin_until(&g_cnt_row[tm], 16 * 3);
    for (int r = t; r < 256; r += 96) sst[r] = __ldcg(&g_rowstat[tm * 256 + r]);
    spin_until(&g_cnt_col[tn], 8 * 3);
    {
        float2 c = make_float2(0.f, 0.f);
#pragma unroll
        for (int i = 0; i < 8; i++) { const float2 u = __ldcg(reinterpret_cast<const float2*>(g_colsum + i * (3 * DM) + tn * 192) + t); c.x += u.x; c.y += u.y; }
        reinterpret_cast<float2*>(scs)[t] = c;
    }
    __syncwarp();
    if (lane == 0) mbar_arrive(s.aux);
}

__device__ __forceinline__ uint32_t qkv_stage_off(int wg, int m) { return (wg & m) ? QkvCfg::STAGE_BYTES : wg * 24576; }
__device__ __forceinline__ void qkv_store(const QkvParams& p, const GemmSmem& s, int tm, int tn, int wg) {
    const bool leader = (threadIdx.x & 31) == 0;
#pragma unroll 1
    for (int m = 0; m < 2; m++) {
#pragma unroll 1
        for (int g = 0; g < 3; g++) {
            take_over((wg & m) ? 12 + g : 2 + wg * 3 + g);
            if (leader) {
#pragma unroll
                for (int h = 0; h < 2; h++)
                    tma_st2(&p.out64, s.base + qkv_stage_off(wg, m) + (g * 2 + h) * 4096, 0, g * (NH * SEQ) + (tn * 2 + h) * SEQ + tm * 256 + wg * 128 + m * 64);
            }
        }
        if (leader) tma_st_commit();
        if (m == 0 && wg == 0) { if (leader) tma_st_wait(); __syncwarp(); named_arrive(10, 160); }
        if (m == 1 && leader) tma_st_wait();
    }
}

__global__ void __launch_bounds__(384, 1) qkv_kernel(const __grid_constant__ QkvParams p) {
    extern __shared__ __align__(1024) uint8_t smem_raw[];
    TL(1, 4);
    pdl_launch();
    const int tm = blockIdx.x & 7, tn = blockIdx.x >> 3;
    auto fill = [&](const GemmSmem& g) {
        if (QKV_EARLY) {
#pragma unroll 1
            for (int k = 0; k < QkvCfg::STAGES; k++) {
                mbar_expect_tx(g.full0 + 8 * k, QkvCfg::STAGE_BYTES);
                QkvCfg::load_x(p, g.base + k * QkvCfg::STAGE_BYTES, g.full0 + 8 * k, k, tm, tn);
                QkvCfg::load_w(p, g.base + k * QkvCfg::STAGE_BYTES, g.full0 + 8 * k, k, tm, tn);
            }
        }
        prefetch_map(&p.out64);
    };
    const GemmSmem s = gemm_setup<QkvCfg>(smem_raw, fill);
    const int wgi = __shfl_sync(0xffffffffu, threadIdx.x >> 7, 0);
    if (wgi == 0) {
        reg_dealloc<56>();
        if (threadIdx.x < 32) {
            if (threadIdx.x == 0) gemm_producer<QkvCfg, QKV_EARLY>(s, p, tm, tn);
            __syncwarp();
            qkv_store(p, s, tm, tn, 0);
        } else {
            qkv_aux(p, smem_raw, s, tm, tn, (threadIdx.x >> 5) - 1, threadIdx.x & 31);
            if (threadIdx.x < 64) { qkv_store(p, s, tm, tn, 1); if (threadIdx.x == 32) TL(1, 3); }
        }
    } else {
        reg_alloc<224>();
        using C = QkvCfg;
        const int wg = wgi - 1, warp = (threadIdx.x >> 5) & 3, lane = threadIdx.x & 31;
        float acc[2][96];
        TL(1, 0);
        gemm_mainloop<C, 13>(s, wg, acc, 1);
        auto tail_mma = [&](int m, int i, int n) {
#pragma unroll
            for (int j = i; j < i + n; j++) {
                const uint32_t sb = s.base + ((13 + j / 4) % C::STAGES) * C::STAGE_BYTES;
                C::mma(acc[m], C::desc_a(sb, wg, m, j & 3), C::desc_b(sb, j & 3), 1);
            }
            wg_commit();
        };
        if (wg == 1) {
            wg_wait<0>();
            named_arrive(9, 256);
            named_bar(8, 256);
        }
#pragma unroll
        for (int k = 13; k < 16; k++) { mbar_wait(s.full0 + 8 * (k % C::STAGES), 1); wg_fence(); tail_mma(0, (k - 13) * 4, 4); }
        if (wg == 0) { wg_wait<3>(); named_arrive(8, 256); }
        tail_mma(1, 0, QT_N);
        const float qscale = 0.17677669529663687f * 1.4426950408889634f;
        const float2* scs = reinterpret_cast<const float2*>(smem_raw + C::AUX_OFF);
        const float2* sst = reinterpret_cast<const float2*>(smem_raw + C::AUX_OFF + 768);
        const int arow = warp * 16 + ((lane >> 3) & 1) * 8 + (lane & 7);
        auto piece = [&](int m, int sub, float mean0, float mean1, float r0, float r1) {
            float v[16];
#pragma unroll
            for (int j = 0; j < 4; j++) {
                const float2 cs = scs[(sub * 4 + j) * 4 + (lane & 3)];
                v[4 * j] = fmaf(mean0, cs.x, acc[m][sub * 16 + 4 * j]) * r0;
                v[4 * j + 1] = fmaf(mean0, cs.y, acc[m][sub * 16 + 4 * j + 1]) * r0;
                v[4 * j + 2] = fmaf(mean1, cs.x, acc[m][sub * 16 + 4 * j + 2]) * r1;
                v[4 * j + 3] = fmaf(mean1, cs.y, acc[m][sub * 16 + 4 * j + 3]) * r1;
            }
#pragma unroll
            for (int jp = 0; jp < 2; jp++) {
                const int chunk = jp * 2 + (lane >> 4);
                const uint32_t addr = s.base + qkv_stage_off(wg, m) + sub * 4096 + arow * 64 + ((chunk ^ ((arow >> 1) & 3)) << 4);
                stmatrix_x4(addr, pack_bf16(v[8 * jp], v[8 * jp + 1]), pack_bf16(v[8 * jp + 2], v[8 * jp + 3]),
                            pack_bf16(v[8 * jp + 4], v[8 * jp + 5]), pack_bf16(v[8 * jp + 6], v[8 * jp + 7]));
            }
            if (sub & 1) hand_over(((wg & m) ? 12 : 2 + wg * 3) + (sub >> 1));
            float n0 = 0.f, n1 = 0.f;
#pragma unroll
            for (int j = 0; j < 4; j++) {
                n0 = fmaf(v[4 * j], v[4 * j], fmaf(v[4 * j + 1], v[4 * j + 1], n0));
                n1 = fmaf(v[4 * j + 2], v[4 * j + 2], fmaf(v[4 * j + 3], v[4 * j + 3], n1));
            }
            const bool odd = lane & 1;
            float full = (odd ? n1 : n0) + __shfl_xor_sync(0xffffffffu, odd ? n0 : n1, 1);
            full += __shfl_xor_sync(0xffffffffu, full, 2);
            const uint32_t mx = __reduce_max_sync(0xffffffffu, __float_as_uint(full));
            if (lane == 0) g_norm[((sub >> 1) * NH + tn * 2 + (sub & 1)) * 128 + (tm * 2 + wg) * 8 + m * 4 + warp] = mx;
        };
        mbar_wait(s.aux, 0);
        const float2 t0 = sst[wg * 128 + warp * 16 + (lane >> 2)], t1 = sst[wg * 128 + warp * 16 + 8 + (lane >> 2)];
        const float2 t2 = sst[wg * 128 + 64 + warp * 16 + (lane >> 2)], t3 = sst[wg * 128 + 64 + warp * 16 + 8 + (lane >> 2)];
        wg_wait<1>();
        fence_regs(acc[0]);
        TKC(12);
        if (wg == 0) named_bar(9, 256);
#pragma unroll
        for (int sub = 0; sub < 6; sub++) {
            const int done = QT_N + sub * QT_STEP;
            if (done < 12) tail_mma(1, done, (sub == 5 || done + QT_STEP > 12) ? 12 - done : QT_STEP);
            const float qs = sub < 2 ? qscale : 1.f;
            piece(0, sub, -t0.x, -t1.x, t0.y * qs, t1.y * qs);
        }
        TKC(13);
        wg_wait<0>();
        fence_regs(acc[1]);
        TL(1, 1);
        if (wg == 0) {
            named_arrive(11, 256);
            named_bar(10, 160);
        } else named_bar(11, 256);
#pragma unroll
        for (int sub = 0; sub < 6; sub++) {
            const float qs = sub < 2 ? qscale : 1.f;
            piece(1, sub, -t2.x, -t3.x, t2.y * qs, t3.y * qs);
        }
        TL(1, 5);
    }
}

struct AttnParams { CUtensorMap kv, kv2, o; bf16* optr; const uint8_t* pf_wo; const uint8_t* pf_w1; const uint8_t* pf_b1; };
constexpr int AT_STAGES = 8, AT_STAGE_BYTES = 16384, AT_Q_OFF = AT_STAGES * AT_STAGE_BYTES, AT_ONES_OFF = AT_Q_OFF + 32768, AT_STG_OFF = AT_ONES_OFF + 1024, AT_BAR_OFF = AT_STG_OFF + 16384, AT_SMEM = AT_BAR_OFF + 256;
constexpr uint32_t AT_BASE = 1024;
constexpr int AT_TILES = 32;

__device__ __forceinline__ float ex2_poly(float x) {
    const float magic = 12582912.f;
    const float t = x + magic;
    const float f = x - (t - magic);
    float p = fmaf(f, 0.05550410866f, 0.24022650695f);
    p = fmaf(p, f, 0.69314718056f);
    p = fmaf(p, f, 1.0f);
    return __int_as_float(__float_as_int(p) + (__float_as_int(t) << 23));
}

__device__ __forceinline__ uint32_t fma_bf16x2(uint32_t a, uint32_t b, uint32_t c) { uint32_t d; asm("fma.rn.bf16x2 %0, %1, %2, %3;" : "=r"(d) : "r"(a), "r"(b), "r"(c)); return d; }
__device__ __forceinline__ uint32_t ex2_pair(float x0, float x1, uint32_t c3) {
    const float m0 = 12582912.f, m1 = 12582912.f - 64.f;
    const float t0 = x0 + m0, t1 = x1 + m1;
    const uint32_t f = pack_bf16(x0 - (t0 - m0), x1 - (t1 - m1));
    uint32_t p = fma_bf16x2(f, c3, 0xBE763E76u);
    p = fma_bf16x2(p, f, 0xBF313F31u);
    p = fma_bf16x2(p, f, 0xBF803F80u);
    return p + (__float_as_uint(t1) << 23) + (__float_as_uint(t0) << 7);
}
constexpr uint32_t FX_LEAD = EXP_FX == 2 ? 0x3EAB3EABu : 0x3DA03DA0u;
__device__ __forceinline__ uint32_t ex2_pair_fx(float x0, float x1, uint32_t c3, uint32_t one2) {
    const float m = 65663.f;
    const uint32_t w = __byte_perm(__float_as_uint(x0 + m), __float_as_uint(x1 + m), 0x5410);
    uint32_t g, r;
    asm("lop3.b32 %0, %1, 0x007F007F, %2, 0xEA;" : "=r"(g) : "r"(w), "r"(one2));
    uint32_t p;
    if (EXP_FX == 2) {
        p = fma_bf16x2(g, c3, 0xBC5DBC5Du);
        p = fma_bf16x2(p, g, 0x3F2F3F2Fu);
    } else {
        p = fma_bf16x2(g, c3, 0xBBF0BBF0u);
        p = fma_bf16x2(p, g, 0x3EF33EF3u);
        p = fma_bf16x2(p, g, 0x3EE93EE9u);
    }
    asm("lop3.b32 %0, %1, %2, 0xFF80FF80, 0xE4;" : "=r"(r) : "r"(w), "r"(p));
    return r;
}
template <uint32_t MASK> __device__ __forceinline__ uint32_t attn_exp2(float x0, float x1, int i, uint32_t c3) {
    if (EXP_FX) return ((MASK >> i) & 1) ? ex2_pair_fx(x0, x1, c3, c3 ^ (FX_LEAD ^ 0x3F803F80u)) : pack_bf16(ex2(x0), ex2(x1));
    return ((MASK >> i) & 1) ? ex2_pair(x0, x1, c3) : pack_bf16(ex2(x0), ex2(x1));
}
template <uint32_t MASK> __device__ __forceinline__ float attn_exp(float x, int i) { return ((MASK >> (i & 31)) & 1) ? ex2_poly(x) : ex2(x); }
__device__ __forceinline__ void attn_issue_tile(const AttnParams& p, uint32_t base, uint32_t full0, int g, int head) {
    const int st = g % AT_STAGES, key0 = (g & 15) * 128;
    const uint32_t bar = full0 + 8 * st, dst = base + st * AT_STAGE_BYTES;
    mbar_expect_tx(bar, AT_STAGE_BYTES);
    tma_ld3(dst, &p.kv2, bar, 0, head * SEQ + key0, 1);
}
__device__ __forceinline__ void attn_qk(float (&sacc)[32], uint32_t q_lo, uint32_t k_lo) {
    mma_qk0(sacc, q_lo, k_lo);
    mma_qk1(sacc, q_lo + 2, k_lo + 2, 1);
}
constexpr uint32_t PV_STEP = 64u - (64u << 16);
__device__ __forceinline__ void attn_pv(float (&o)[20], const uint32_t (&pr)[16], uint32_t v_lo, int first) {
#pragma unroll
    for (int kk = 0; kk < 4; kk++)
        mma_pv(o, pr[4 * kk], pr[4 * kk + 1], pr[4 * kk + 2], pr[4 * kk + 3], v_lo + kk * PV_STEP, (kk > 0) || !first);
}
__device__ __forceinline__ void attn_store_o(const float (&o)[20], const AttnParams& p, uint32_t base, int head, int row0, int lane) {
    const float r0 = 1.f / o[16], r1 = 1.f / o[18];
    {
        uint32_t a[4], b[4];
#pragma unroll
        for (int j = 0; j < 4; j++) { a[j] = pack_bf16(o[4 * j] * r0, o[4 * j + 1] * r0); b[j] = pack_bf16(o[4 * j + 2] * r1, o[4 * j + 3] * r1); }
        const bool odd = lane & 1, up = lane & 2;
#pragma unroll
        for (int h = 0; h < 2; h++) {
            uint32_t t = __shfl_xor_sync(0xffffffffu, odd ? a[2 * h] : a[2 * h + 1], 1); if (odd) a[2 * h] = t; else a[2 * h + 1] = t;
            t = __shfl_xor_sync(0xffffffffu, odd ? b[2 * h] : b[2 * h + 1], 1); if (odd) b[2 * h] = t; else b[2 * h + 1] = t;
        }
#pragma unroll
        for (int h = 0; h < 2; h++) {
            uint32_t t = __shfl_xor_sync(0xffffffffu, up ? a[h] : a[h + 2], 2); if (up) a[h] = t; else a[h + 2] = t;
            t = __shfl_xor_sync(0xffffffffu, up ? b[h] : b[h + 2], 2); if (up) b[h] = t; else b[h + 2] = t;
        }
        uint4* op = reinterpret_cast<uint4*>(p.optr + (size_t)(row0 + (lane >> 2)) * DM + head * HD) + (lane & 3);
        op[0] = make_uint4(a[0], a[1], a[2], a[3]);
        op[8 * (DM / 8)] = make_uint4(b[0], b[1], b[2], b[3]);
        return;
    }
    const uint32_t stg = base + AT_STG_OFF + (threadIdx.x >> 5) * 1024;
    const int arow = ((lane >> 3) & 1) * 8 + (lane & 7);
    if (lane == 0) tma_st_wait();
    __syncwarp();
#pragma unroll
    for (int jp = 0; jp < 2; jp++) {
        const int chunk = jp * 2 + (lane >> 4);
        stmatrix_x4(stg + arow * 64 + ((chunk ^ ((arow >> 1) & 3)) << 4), pack_bf16(o[8 * jp] * r0, o[8 * jp + 1] * r0), pack_bf16(o[8 * jp + 2] * r1, o[8 * jp + 3] * r1),
                    pack_bf16(o[8 * jp + 4] * r0, o[8 * jp + 5] * r0), pack_bf16(o[8 * jp + 6] * r1, o[8 * jp + 7] * r1));
    }
    fence_proxy_async();
    __syncwarp();
    if (lane == 0) { tma_st2(&p.o, stg, head * HD, row0); tma_st_commit(); }
}
__device__ __forceinline__ void attn_refill(const AttnParams& p, uint32_t base, uint32_t full0, uint32_t empty0, int g, int head) {
    if (threadIdx.x == 0 && g >= 4 && g + 4 < AT_TILES) {
        const int gp = g - 4;
        mbar_wait(empty0 + 8 * (gp % AT_STAGES), (gp / AT_STAGES) & 1);
        attn_issue_tile(p, base, full0, g + 4, head);
    }
    __syncwarp();
}

__device__ __forceinline__ void attn_fast(const AttnParams& p, uint32_t base, uint32_t full0, uint32_t empty0, int head, int qchunk) {
    const int wg = __shfl_sync(0xffffffffu, threadIdx.x >> 7, 0), warp = (threadIdx.x >> 5) & 3, lane = threadIdx.x & 31;
    const int warp_id = __shfl_sync(0xffffffffu, threadIdx.x >> 5, 0);
    const uint32_t k_lo0 = desc_lo(base, 16), v_lo0 = desc_lo(base + 8192, AT_ONES_OFF - 8192);
    const uint32_t q_lo0 = desc_lo(base + AT_Q_OFF + wg * 64 * 64, 16);
    uint32_t c3;
    asm volatile("ld.shared.u32 %0, [%1];" : "=r"(c3) : "r"(base + AT_ONES_OFF));
    c3 ^= 0x3F803F80u ^ (EXP_FX ? FX_LEAD : 0xBD693D69u);
#pragma unroll 1
    for (int pass = 0; pass < 2; pass++) {
    const uint32_t q = q_lo0 + pass * (256 * 64 >> 4);
    float o[20];
#pragma unroll
    for (int i = 0; i < 20; i++) o[i] = 0.f;
    if (PF_W1 == 3 && pass == 1 && threadIdx.x < 128 + 140) {
        const int l = threadIdx.x;
        prefetch_line(l < 128 ? p.pf_wo + ((size_t)blockIdx.x * 128 + l) * 128 : p.pf_w1 + ((size_t)blockIdx.x * 140 + (l - 128)) * 128);
    }
#pragma unroll 1
    for (uint32_t par = 0; par < 2; par++) {
        const int rev = pass * 2 + par;
        if (PF_W1 == 1 && threadIdx.x < 256) {
            const int l = rev * 256 + threadIdx.x;
            prefetch_line(l < 128 ? p.pf_wo + ((size_t)blockIdx.x * 128 + l) * 128 : p.pf_w1 + ((size_t)blockIdx.x * 896 + (l - 128)) * 128);
        }
        if (PF_W1 == 2 && rev == PF_REV && threadIdx.x < 128 + 140) {
            const int l = threadIdx.x;
            prefetch_line(l < 128 ? p.pf_wo + ((size_t)blockIdx.x * 128 + l) * 128 : p.pf_w1 + ((size_t)blockIdx.x * 140 + (l - 128)) * 128);
        }
#pragma unroll
        for (int st = 0; st < AT_STAGES; st++) {
            if (warp_id == (st & 3) * 5) {
                const int g = rev * AT_STAGES + st;
                if (lane == 0 && g >= 4 && g + 4 < AT_TILES) {
                    mbar_wait(empty0 + 8 * ((st + 4) % AT_STAGES), (st >= 4) ? par : (par ^ 1));
                    attn_issue_tile(p, base, full0, g + 4, head);
                }
                __syncwarp();
            }
            mbar_wait(full0 + 8 * st, par);
            float sc[64];
            uint32_t pa[16], pb[16];
            AT(0);
            wg_fence();
            mma_qkw0(sc, q, k_lo0 + st * (AT_STAGE_BYTES >> 4));
            mma_qkw1(sc, q + 2, k_lo0 + st * (AT_STAGE_BYTES >> 4) + 2, 1);
            wg_commit();
            wg_wait<0>();
            fence_regs(sc);
            AT(1);
            if (lane == 0 && (st > 0 || rev > 0)) mbar_arrive(empty0 + 8 * ((st + AT_STAGES - 1) % AT_STAGES));
#pragma unroll
            for (int i = 0; i < 16; i++) pa[i] = PAIR_POLY ? attn_exp2<PMASK_A>(sc[2 * i], sc[2 * i + 1], i, c3) : pack_bf16(attn_exp<POLY_MASK>(sc[2 * i], 2 * i), attn_exp<POLY_MASK>(sc[2 * i + 1], 2 * i + 1));
            wg_fence();
            attn_pv(o, pa, v_lo0 + st * 16 * PV_STEP, 0);
            wg_commit();
            AT(2);
#pragma unroll
            for (int i = 0; i < 16; i++) pb[i] = PAIR_POLY ? attn_exp2<PMASK_B>(sc[32 + 2 * i], sc[32 + 2 * i + 1], i, c3) : pack_bf16(attn_exp<POLY_MASK_B>(sc[32 + 2 * i], 2 * i), attn_exp<POLY_MASK_B>(sc[32 + 2 * i + 1], 2 * i + 1));
            wg_wait<0>();
            wg_fence();
            attn_pv(o, pb, v_lo0 + (st * 16 + 4) * PV_STEP, 0);
            wg_commit();
            AT(3);
        }
    }
    wg_wait<0>();
    fence_regs(o);
    attn_store_o(o, p, base, head, qchunk * 512 + pass * 256 + wg * 64 + warp * 16, lane);
    }
}

template <uint32_t MASK>
__device__ __forceinline__ void attn_piece(float (&o)[20], const float* sc, uint32_t c3, uint32_t v_lo) {
    uint32_t pr[8];
#pragma unroll
    for (int i = 0; i < 8; i++) pr[i] = attn_exp2<MASK>(sc[2 * i], sc[2 * i + 1], i, c3);
    wg_fence();
    mma_pv(o, pr[0], pr[1], pr[2], pr[3], v_lo, 1);
    mma_pv(o, pr[4], pr[5], pr[6], pr[7], v_lo + PV_STEP, 1);
    wg_commit();
}
__device__ __forceinline__ void attn_fast2(const AttnParams& p, uint32_t base, uint32_t full0, uint32_t empty0, int head, int qchunk) {
    const int wg = __shfl_sync(0xffffffffu, threadIdx.x >> 7, 0), warp = (threadIdx.x >> 5) & 3, lane = threadIdx.x & 31;
    const int warp_id = __shfl_sync(0xffffffffu, threadIdx.x >> 5, 0);
    const uint32_t dbase = IMM_DESC ? AT_BASE : base;
    const uint32_t k_lo0 = desc_lo(dbase, 16), v_lo0 = desc_lo(dbase + 8192, AT_ONES_OFF - 8192);
    const uint32_t q_lo0 = desc_lo(dbase + AT_Q_OFF, 16) + wg * (64 * 64 >> 4);
    uint32_t c3;
    asm volatile("ld.shared.u32 %0, [%1];" : "=r"(c3) : "r"(base + AT_ONES_OFF));
    c3 ^= 0x3F803F80u ^ (EXP_FX ? FX_LEAD : 0xBD693D69u);
    float sa[32], sb[32];
    mbar_wait(full0, 0);
    wg_fence();
    attn_qk(sa, q_lo0, k_lo0);
    wg_commit();
    wg_wait<0>();
    fence_regs(sa);
#pragma unroll 1
    for (int pass = 0; pass < 2; pass++) {
    const uint32_t q = q_lo0 + pass * (256 * 64 >> 4);
    float o[20];
#pragma unroll
    for (int i = 0; i < 20; i++) o[i] = 0.f;
#pragma unroll 1
    for (uint32_t par = 0; par < 2; par++) {
        const int rev = pass * 2 + par;
        const uint32_t qw = par ? q_lo0 + (256 * 64 >> 4) : q;
#pragma unroll
        for (int st = 0; st < AT_STAGES; st++) {
            if (warp_id == (st & 3) * 5) {
                const int g = rev * AT_STAGES + st;
                if (lane == 0 && g >= 4 && g + 4 < AT_TILES) {
                    mbar_wait(empty0 + 8 * ((st + 4) % AT_STAGES), (st >= 4) ? par : (par ^ 1));
                    attn_issue_tile(p, base, full0, g + 4, head);
                }
                __syncwarp();
            }
            const uint32_t kb = k_lo0 + st * (AT_STAGE_BYTES >> 4), vb = v_lo0 + st * 16 * PV_STEP;
            wg_fence();
            attn_qk(sb, q, kb + 256);
            wg_commit();
            wg_wait<2>();
            fence_regs(sa);
            attn_piece<QMASK_0>(o, sa, c3, vb);
            wg_wait<2>();
            if (lane == 0 && (st > 0 || rev > 0)) mbar_arrive(empty0 + 8 * ((st + AT_STAGES - 1) % AT_STAGES));
            attn_piece<QMASK_1>(o, sa + 16, c3, vb + 2 * PV_STEP);
            const int nx = (st + 1) % AT_STAGES;
            if (st + 1 < AT_STAGES) mbar_wait(full0 + 8 * nx, par);
            else if (rev < 3) mbar_wait(full0, par ^ 1);
            wg_fence();
            attn_qk(sa, st + 1 < AT_STAGES ? q : qw, k_lo0 + nx * (AT_STAGE_BYTES >> 4));
            wg_commit();
            wg_wait<2>();
            fence_regs(sb);
            attn_piece<QMASK_2>(o, sb, c3, vb + 4 * PV_STEP);
            wg_wait<2>();
            attn_piece<QMASK_3>(o, sb + 16, c3, vb + 6 * PV_STEP);
        }
        wg_wait<0>();
        fence_regs(sa);
        fence_regs(o);
    }
    attn_store_o(o, p, base, head, qchunk * 512 + pass * 256 + wg * 64 + warp * 16, lane);
    }
}

__device__ __forceinline__ void attn_safe(const AttnParams& p, uint32_t base, uint32_t full0, uint32_t empty0, int head, int qchunk) {
    const int wg = __shfl_sync(0xffffffffu, threadIdx.x >> 7, 0), warp = (threadIdx.x >> 5) & 3, lane = threadIdx.x & 31;
    const uint32_t k_lo0 = desc_lo(base, 16), v_lo0 = desc_lo(base + 8192, AT_ONES_OFF - 8192);
#pragma unroll 1
    for (int pass = 0; pass < 2; pass++) {
        const uint32_t q = desc_lo(base + AT_Q_OFF + (pass * 256 + wg * 64) * 64, 16);
        float o[20];
#pragma unroll
        for (int i = 0; i < 20; i++) o[i] = 0.f;
        float m0 = -INFINITY, m1 = -INFINITY;
#pragma unroll 1
        for (int t = 0; t < 32; t++) {
            const int g = pass * 16 + (t >> 1), half = t & 1;
            const int st = g % AT_STAGES;
            const uint32_t kb = k_lo0 + st * (AT_STAGE_BYTES >> 4), vb = v_lo0 + st * 16 * PV_STEP;
            if (half == 0) { attn_refill(p, base, full0, empty0, g, head); mbar_wait(full0 + 8 * st, (g / AT_STAGES) & 1); }
            float cur[32];
            wg_fence();
            attn_qk(cur, q, kb + half * 256);
            wg_commit();
            wg_wait<0>();
            fence_regs(cur);
            float x0 = cur[0], x1 = cur[2];
#pragma unroll
            for (int i = 0; i < 8; i++) { x0 = fmaxf(x0, fmaxf(cur[4 * i], cur[4 * i + 1])); x1 = fmaxf(x1, fmaxf(cur[4 * i + 2], cur[4 * i + 3])); }
            x0 = fmaxf(x0, __shfl_xor_sync(0xffffffffu, x0, 1)); x1 = fmaxf(x1, __shfl_xor_sync(0xffffffffu, x1, 1));
            x0 = fmaxf(x0, __shfl_xor_sync(0xffffffffu, x0, 2)); x1 = fmaxf(x1, __shfl_xor_sync(0xffffffffu, x1, 2));
            const float n0 = fmaxf(m0, x0), n1 = fmaxf(m1, x1);
            const float a0 = ex2(m0 - n0), a1 = ex2(m1 - n1);
            m0 = n0; m1 = n1;
            uint32_t pr[16];
#pragma unroll
            for (int i = 0; i < 8; i++) {
                pr[2 * i] = pack_bf16(ex2(cur[4 * i] - n0), ex2(cur[4 * i + 1] - n0));
                pr[2 * i + 1] = pack_bf16(ex2(cur[4 * i + 2] - n1), ex2(cur[4 * i + 3] - n1));
            }
#pragma unroll
            for (int i = 0; i < 5; i++) { o[4 * i] *= a0; o[4 * i + 1] *= a0; o[4 * i + 2] *= a1; o[4 * i + 3] *= a1; }
            wg_fence();
            attn_pv(o, pr, vb + half * 4 * PV_STEP, 0);
            wg_commit();
            wg_wait<0>();
            fence_regs(o);
            if (half == 1 && lane == 0) mbar_arrive(empty0 + 8 * st);
        }
        attn_store_o(o, p, base, head, qchunk * 512 + pass * 256 + wg * 64 + warp * 16, lane);
    }
}

__global__ void __launch_bounds__(512, 1) attn_kernel(const __grid_constant__ AttnParams p) {
    extern __shared__ __align__(1024) uint8_t smem_raw[];
    TL(2, 4);
    pdl_launch();
    const uint32_t base = smem_u32(smem_raw);
    const uint32_t full0 = base + AT_BAR_OFF, empty0 = full0 + 8 * AT_STAGES;
    const int head = blockIdx.x >> 2, qchunk = blockIdx.x & 3;
    if (threadIdx.x == 0) {
        if (base & 1023) __trap();
        prefetch_map(&p.kv);
        for (int i = 0; i < AT_STAGES; i++) { mbar_init(full0 + 8 * i, 1); mbar_init(empty0 + 8 * i, 16); }
        mbar_init(empty0 + 8 * AT_STAGES, 1);
        fence_barrier_init();
    }
    if (threadIdx.x < 256) reinterpret_cast<uint32_t*>(smem_raw + AT_ONES_OFF)[threadIdx.x] = 0x3F803F80u;
    fence_proxy_async();
    __syncthreads();
    pdl_wait();
    TL(2, 0);
    if (threadIdx.x == 0) {
        const uint32_t qbar = empty0 + 8 * AT_STAGES;
        mbar_expect_tx(qbar, 32768);
        for (int i = 0; i < 4; i++) tma_ld2(base + AT_Q_OFF + i * 8192, &p.kv, qbar, 0, head * SEQ + qchunk * 512 + i * 128);
        for (int g = 0; g < AT_STAGES; g++) attn_issue_tile(p, base, full0, g, head);
    }
    __syncwarp();
    const uint4* nrm = reinterpret_cast<const uint4*>(g_norm) + head * 32 + (threadIdx.x & 31);
    const uint4 nq = __ldcg(nrm), nk = __ldcg(nrm + NH * 32), nv = __ldcg(nrm + 2 * NH * 32);
    const float qn = __uint_as_float(__reduce_max_sync(0xffffffffu, max(max(nq.x, nq.y), max(nq.z, nq.w))));
    const float kn = __uint_as_float(__reduce_max_sync(0xffffffffu, max(max(nk.x, nk.y), max(nk.z, nk.w))));
    const float vn = __uint_as_float(__reduce_max_sync(0xffffffffu, max(max(nv.x, nv.y), max(nv.z, nv.w))));
    if (blockIdx.x == 0 && threadIdx.x >= 64 && threadIdx.x < 64 + 24) {
        const int i = threadIdx.x - 64;
        if (i < 8) g_cnt_row[i] = 0; else g_cnt_col[i - 8] = 0;
    }
    if (PF_W1 == 4) {
        const int l = threadIdx.x;
        if (l < 128 + 140) prefetch_line(l < 128 ? p.pf_wo + ((size_t)blockIdx.x * 128 + l) * 128 : p.pf_w1 + ((size_t)blockIdx.x * 140 + (l - 128)) * 128);
        if (blockIdx.x == 0 && l >= 300 && l < 300 + 56) prefetch_line(p.pf_b1 + (l - 300) * 128);
    }
    if (threadIdx.x >= 448) reinterpret_cast<uint4*>(g_hpart)[blockIdx.x * 64 + threadIdx.x - 448] = make_uint4(0, 0, 0, 0);
    const bool bounded = (qn * kn <= 1.0e4f) && (vn <= 1.0e9f) && (base & 0xFFFFFFu) == AT_BASE;
    mbar_wait(empty0 + 8 * AT_STAGES, 0);
    if (bounded) { if (ATTN_PIPE) attn_fast2(p, base, full0, empty0, head, qchunk); else attn_fast(p, base, full0, empty0, head, qchunk); }
    else attn_safe(p, base, full0, empty0, head, qchunk);
    if ((threadIdx.x & 31) == 0) tma_st_wait();
    TL(2, 3);
}

struct ResParams { CUtensorMap a, b, res, out; const bf16* bias; };
template <bool MIX2>
struct ResCfg {
    static constexpr int MB = 1, BN = 128, KSTEPS = MIX2 ? 56 : 16, STAGES = 6, A_BYTES = 16384, B_BYTES = 16384;
    static constexpr int STAGE_BYTES = A_BYTES + B_BYTES, STG_OFF = STAGES * STAGE_BYTES, BAR_OFF = STG_OFF + 32768, SMEM = BAR_OFF + 128;
    static constexpr int AUX_COUNT = 1, PRE = MIX2 ? MIX2_PRE : WO_PRE;
    static constexpr int TLK = MIX2 ? 6 : 3;
    static constexpr bool MC = MIX2 ? MIX2_MC : WO_MC, PAIR = MC || (MIX2 ? MIX2_PAIR : WO_PAIR), ACC_INIT = MIX2 ? MIX2_INIT : WO_INIT;
    static constexpr int SYNC_NS = MIX2 ? MIX2_SYNC : WO_SYNC;
    static __device__ __forceinline__ void prefetch(const ResParams&, int) {}
    static __device__ __forceinline__ void load_w(const ResParams& p, uint32_t sb, uint32_t bar, int k, int tm, int tn) {
        if (MIX2) {
            if (MC) tma_ld3_mc(sb + (tn & 1) * 8192, &p.a, bar, 0, k * 64, tm * 2 + (tn & 1));
            else tma_ld3(sb, &p.a, bar, 0, k * 64, tm * 2);
        } else tma_ld3(sb + A_BYTES, &p.b, bar, 0, k * 64, tn * 2);
    }
    static __device__ __forceinline__ void load_x(const ResParams& p, uint32_t sb, uint32_t bar, int k, int tm, int tn) {
        if (MIX2) tma_ld2(sb + A_BYTES, &p.b, bar, k * 64, tn * 128);
        else if (MC) tma_ld2_mc(sb + (tn & 1) * 8192, &p.a, bar, k * 64, tm * 128 + (tn & 1) * 64);
        else tma_ld2(sb, &p.a, bar, k * 64, tm * 128);
    }
    static __device__ __forceinline__ void load_aux(const ResParams& p, const GemmSmem& s, int tm, int tn) {
        mbar_expect_tx(s.aux, 32768);
        tma_ld2(s.base + STG_OFF, &p.res, s.aux, tn * 128, tm * 128);
        tma_ld2(s.base + STG_OFF + 16384, &p.res, s.aux, tn * 128 + 64, tm * 128);
    }
    static __device__ __forceinline__ uint32_t desc_a(uint32_t sb, int wg, int m, int kk) {
        return MIX2 ? desc_lo(sb + wg * 8192 + kk * 2048, 8192) : desc_lo(sb + wg * 8192 + kk * 32, 16);
    }
    static __device__ __forceinline__ uint32_t desc_b(uint32_t sb, int kk) {
        return MIX2 ? desc_lo(sb + A_BYTES + kk * 32, 16) : desc_lo(sb + A_BYTES + kk * 2048, 8192);
    }
    static __device__ __forceinline__ void mma(float (&d)[64], uint32_t a, uint32_t b, int sc) {
        if (MIX2) mma_mix2(d, a, b, sc); else mma_wo(d, a, b, sc);
    }
};
template <bool MIX2>
__global__ void __launch_bounds__(384, 1) res_gemm_kernel(const __grid_constant__ ResParams p) {
    using C = ResCfg<MIX2>;
    extern __shared__ __align__(1024) uint8_t smem_raw[];
    TL(MIX2 ? 6 : 3, 4);
    if (!MIX2) pdl_launch();
    constexpr bool MAP = MIX2 ? MIX2_MAP : WO_MAP;
    const int tm = MAP ? blockIdx.x >> 3 : blockIdx.x & 15, tn = MAP ? blockIdx.x & 7 : blockIdx.x >> 4;
    if (threadIdx.x == 0) { prefetch_map(&p.a); prefetch_map(&p.b); prefetch_map(&p.res); prefetch_map(&p.out); }
    const GemmSmem s = gemm_setup<C>(smem_raw);
    const int wgi = __shfl_sync(0xffffffffu, threadIdx.x >> 7, 0);
    if (wgi == 0) {
        reg_dealloc<40>();
        if (threadIdx.x < 32) {
            if (threadIdx.x == 0) gemm_producer<C>(s, p, tm, tn);
            __syncwarp();
#pragma unroll 1
            for (int i = 0; i < 4; i++) {
                const int b = i >> 1, wg = i & 1;
                take_over(2 + i);
                if (threadIdx.x == 0) tma_st2(&p.out, s.base + C::STG_OFF + b * 16384 + wg * 8192, tn * 128 + b * 64, tm * 128 + wg * 64);
            }
            if (threadIdx.x == 0) { tma_st_commit(); tma_st_wait(); TL(MIX2 ? 6 : 3, 3); }
        }
    } else {
        reg_alloc<232>();
        const int wg = wgi - 1, warp = (threadIdx.x >> 5) & 3, lane = threadIdx.x & 31;
        const int r0 = wg * 64 + warp * 16 + (lane >> 2);
        const int arow = wg * 64 + warp * 16 + ((lane >> 3) & 1) * 8 + (lane & 7);
        const uint32_t stg = s.base + C::STG_OFF + arow * 128;
        float acc[1][64];
        auto residual = [&]() {
            float a0 = 1.f, a1 = 1.f, c0 = 0.f, c1 = 0.f;
            if (MIX2) {
                const float2 t0 = __ldcg(&g_rowln[tm * 128 + r0]), t1 = __ldcg(&g_rowln[tm * 128 + r0 + 8]);
                a0 = t0.y; a1 = t1.y;
                c0 = t0.x + __bfloat162float(p.bias[tm * 128 + r0]); c1 = t1.x + __bfloat162float(p.bias[tm * 128 + r0 + 8]);
            }
            return make_float4(a0, a1, c0, c1);
        };
        auto apply = [&](const float4 ac) {
            mbar_wait(s.aux, 0);
#pragma unroll
            for (int jp = 0; jp < 8; jp++) {
                const int chunk = jp * 2 + (lane >> 4);
                uint32_t r[4];
                ldmatrix_x4(stg + (chunk >> 3) * 16384 + (((chunk & 7) ^ (arow & 7)) << 4), r);
#pragma unroll
                for (int i = 0; i < 4; i++) {
                    const float a = (i & 1) ? ac.y : ac.x, c = (i & 1) ? ac.w : ac.z;
                    const float v0 = MIX2 ? fmaf(bf_lo(r[i]), a, c) : bf_lo(r[i]), v1 = MIX2 ? fmaf(bf_hi(r[i]), a, c) : bf_hi(r[i]);
                    acc[0][jp * 8 + 2 * i] = C::ACC_INIT ? v0 : acc[0][jp * 8 + 2 * i] + v0;
                    acc[0][jp * 8 + 2 * i + 1] = C::ACC_INIT ? v1 : acc[0][jp * 8 + 2 * i + 1] + v1;
                }
            }
        };
        const float4 ac = residual();
        if (C::ACC_INIT) apply(ac);
        pdl_wait();
        TL(MIX2 ? 6 : 3, 0);
        gemm_mainloop<C>(s, wg, acc, MIX2 ? 6 : 3);
        TL(MIX2 ? 6 : 3, 1);
        if (!C::ACC_INIT) apply(ac);
        float sc0 = 1.f, sc1 = 1.f, of0 = 0.f, of1 = 0.f;
        if (!MIX2) {
            float s0 = 0.f, s1 = 0.f;
#pragma unroll
            for (int j = 0; j < 16; j++) { s0 += acc[0][4 * j] + acc[0][4 * j + 1]; s1 += acc[0][4 * j + 2] + acc[0][4 * j + 3]; }
            s0 += __shfl_xor_sync(0xffffffffu, s0, 1); s1 += __shfl_xor_sync(0xffffffffu, s1, 1);
            s0 += __shfl_xor_sync(0xffffffffu, s0, 2); s1 += __shfl_xor_sync(0xffffffffu, s1, 2);
            const float m0 = s0 * (1.f / 128), m1 = s1 * (1.f / 128);
            float q0 = 0.f, q1 = 0.f;
#pragma unroll
            for (int j = 0; j < 16; j++) {
                const float a = acc[0][4 * j] - m0, b = acc[0][4 * j + 1] - m0, c = acc[0][4 * j + 2] - m1, d = acc[0][4 * j + 3] - m1;
                q0 = fmaf(a, a, fmaf(b, b, q0)); q1 = fmaf(c, c, fmaf(d, d, q1));
            }
            q0 += __shfl_xor_sync(0xffffffffu, q0, 1); q1 += __shfl_xor_sync(0xffffffffu, q1, 1);
            q0 += __shfl_xor_sync(0xffffffffu, q0, 2); q1 += __shfl_xor_sync(0xffffffffu, q1, 2);
            const int wrow = tm * 128 + wg * 64 + warp * 16;
            if ((lane & 3) < 2) {
                const float m = (lane & 1) ? m1 : m0, q = (lane & 1) ? q1 : q0;
                const unsigned long long w = ((unsigned long long)(__float_as_uint(q) | 0x80000000u) << 32) | __float_as_uint(m);
                asm volatile("st.relaxed.gpu.global.u64 [%0], %1;" :: "l"(g_hpart + tn * SEQ + wrow + (lane >> 2) + (lane & 1) * 8), "l"(w) : "memory");
            }
            TL(3, 5);
            TKC(13);
            const unsigned long long* part = g_hpart + (lane >> 2) * SEQ + wrow + (lane & 3) * 4;
            unsigned long long t[4];
            int it = 0;
            bool ok;
            do {
                asm volatile("ld.relaxed.gpu.global.v2.u64 {%0, %1}, [%2];" : "=l"(t[0]), "=l"(t[1]) : "l"(part) : "memory");
                asm volatile("ld.relaxed.gpu.global.v2.u64 {%0, %1}, [%2];" : "=l"(t[2]), "=l"(t[3]) : "l"(part + 2) : "memory");
                ok = (long long)(t[0] & t[1] & t[2] & t[3]) < 0;
                if (++it > (1 << 20)) __trap();
            } while (!__all_sync(0xffffffffu, ok));
            TKC(14);
            float mt[4], qt[4];
#pragma unroll
            for (int i = 0; i < 4; i++) {
                const float mi = __uint_as_float((uint32_t)t[i]), qi = __uint_as_float((uint32_t)(t[i] >> 32) & 0x7FFFFFFFu);
                float m = mi;
                m += __shfl_xor_sync(0xffffffffu, m, 4); m += __shfl_xor_sync(0xffffffffu, m, 8); m += __shfl_xor_sync(0xffffffffu, m, 16);
                m *= 0.125f;
                float q = fmaf(128.f * (mi - m), mi - m, qi);
                q += __shfl_xor_sync(0xffffffffu, q, 4); q += __shfl_xor_sync(0xffffffffu, q, 8); q += __shfl_xor_sync(0xffffffffu, q, 16);
                mt[i] = m; qt[i] = q;
            }
            const int sel = (lane >> 2) & 3;
            const float mean = sel == 0 ? mt[0] : sel == 1 ? mt[1] : sel == 2 ? mt[2] : mt[3];
            const float var = (sel == 0 ? qt[0] : sel == 1 ? qt[1] : sel == 2 ? qt[2] : qt[3]) * (1.f / DM);
            const float r1 = rsqrtf(var + 1e-5f);
            const float r2 = rsqrtf(var * r1 * r1 + 1e-5f);
            const float scale = 0.5f * r1 * r2, off = -mean * scale;
            if (tn == 0 && lane < 16) g_rowln[wrow + 4 * (lane & 3) + sel] = make_float2(mean, 1.f / scale);
            const int ra = lane >> 2, src0 = ((ra & 3) << 2) | (ra >> 2);
            sc0 = __shfl_sync(0xffffffffu, scale, src0); of0 = __shfl_sync(0xffffffffu, off, src0);
            sc1 = __shfl_sync(0xffffffffu, scale, src0 + 2); of1 = __shfl_sync(0xffffffffu, off, src0 + 2);
        }
#pragma unroll
        for (int jp = 0; jp < 8; jp++) {
            const int chunk = jp * 2 + (lane >> 4);
            uint32_t r[4];
#pragma unroll
            for (int i = 0; i < 4; i++) {
                const float sc = (i & 1) ? sc1 : sc0, of = (i & 1) ? of1 : of0;
                const float v0 = acc[0][jp * 8 + 2 * i], v1 = acc[0][jp * 8 + 2 * i + 1];
                r[i] = MIX2 ? pack_bf16(v0, v1) : pack_bf16(fmaf(v0, sc, of), fmaf(v1, sc, of));
            }
            stmatrix_x4(stg + (chunk >> 3) * 16384 + (((chunk & 7) ^ (arow & 7)) << 4), r[0], r[1], r[2], r[3]);
            if ((jp & 3) == 3) hand_over(2 + (jp >> 2) * 2 + wg);
        }
        if (MIX2) TL(6, 5);
        TKC(15);
    }
}

struct Mix1Params { CUtensorMap hn, w1, out; const bf16* bias; const uint8_t* pf; };
struct Mix1Cfg {
    static constexpr int MB = 1, BN = 224, KSTEPS = 32, STAGES = 5, A_BYTES = 16384, B_BYTES = 28672;
    static constexpr int STAGE_BYTES = A_BYTES + B_BYTES, BIAS_OFF = STAGES * STAGE_BYTES, BAR_OFF = BIAS_OFF + 1024, SMEM = BAR_OFF + 128;
    static constexpr int AUX_COUNT = 1, PRE = MIX1_PRE;
    static constexpr int TLK = 5;
    static constexpr bool MC = MIX1_MC, PAIR = MC || MIX1_PAIR, ACC_INIT = false;
    static constexpr int SYNC_NS = MIX1_SYNC;
    static __device__ __forceinline__ void load_w(const Mix1Params& p, uint32_t sb, uint32_t bar, int k, int tm, int tn) {
        if (MC) tma_ld3_mc(sb + A_BYTES + (tm & 1) * (B_BYTES / 2), &p.w1, bar, 0, k * 64 + (tm & 1) * 32, tn * 7);
        else { tma_ld3(sb + A_BYTES, &p.w1, bar, 0, k * 64, tn * 7); tma_ld3(sb + A_BYTES + B_BYTES / 2, &p.w1, bar, 0, k * 64 + 32, tn * 7); }
    }
    static __device__ __forceinline__ void prefetch(const Mix1Params& p, int k) {}
    static __device__ __forceinline__ void load_x(const Mix1Params& p, uint32_t sb, uint32_t bar, int k, int tm, int tn) { tma_ld3(sb, &p.hn, bar, 0, k * 64, tm * 2); }
    static __device__ __forceinline__ void load_aux(const Mix1Params&, const GemmSmem&, int, int) {}
    static __device__ __forceinline__ uint32_t desc_a(uint32_t sb, int wg, int m, int kk) { return desc_lo(sb + wg * 8192 + kk * 2048, 8192); }
    static __device__ __forceinline__ uint32_t desc_b(uint32_t sb, int kk) { return desc_lo(sb + A_BYTES + (kk >> 1) * (B_BYTES / 2) + (kk & 1) * 1024, 2048); }
    static __device__ __forceinline__ void mma(float (&d)[112], uint32_t a, uint32_t b, int sc) { mma_mix1(d, a, b, sc); }
    static __device__ __forceinline__ uint32_t stage_off(int wg) { return (2 + wg) * STAGE_BYTES; }
};
__global__ void __launch_bounds__(384, 1) mix1_kernel(const __grid_constant__ Mix1Params p) {
    using C = Mix1Cfg;
    extern __shared__ __align__(1024) uint8_t smem_raw[];
    TL(5, 4);
    const int tm = blockIdx.x & 7, tn = blockIdx.x >> 3;
    if (threadIdx.x == 0) { prefetch_map(&p.hn); prefetch_map(&p.w1); prefetch_map(&p.out); }
    const GemmSmem s = gemm_setup<C>(smem_raw);
    const int wgi = __shfl_sync(0xffffffffu, threadIdx.x >> 7, 0);
    if (wgi == 0) {
        reg_dealloc<40>();
        if (threadIdx.x < 32) {
            if (threadIdx.x == 0) gemm_producer<C>(s, p, tm, tn);
            __syncwarp();
#pragma unroll 1
            for (int i = 0; i < 8; i++) {
                const int wg = i >> 2, b = (i & 3) * 2;
                take_over(2 + i);
                if (threadIdx.x == 0) {
                    tma_st3(&p.out, s.base + C::stage_off(wg) + b * 4096, 0, tm * 128 + wg * 64, tn * 7 + b);
                    if (b < 6) tma_st3(&p.out, s.base + C::stage_off(wg) + (b + 1) * 4096, 0, tm * 128 + wg * 64, tn * 7 + b + 1);
                }
            }
            if (threadIdx.x == 0) { tma_st_commit(); tma_st_wait(); TL(5, 3); }
        } else if (PF_W2 && threadIdx.x >= 32 && threadIdx.x < 64) {
            pdl_wait();
            __nanosleep(PF_W2_DELAY);
            if (PF_W2 == 1) {
#pragma unroll 1
            for (int i = 0; i < 28; i++) {
                prefetch_line(p.pf + ((size_t)blockIdx.x * 896 + i * 32 + (threadIdx.x & 31)) * 128);
                __nanosleep(300);
            }
            } else {
#pragma unroll 1
            for (int i = 0; i < 4; i++) prefetch_line(p.pf + ((size_t)blockIdx.x * 128 + i * 32 + (threadIdx.x & 31)) * 128);
            }
        }
    } else {
        reg_alloc<232>();
        const int wg = wgi - 1, warp = (threadIdx.x >> 5) & 3, lane = threadIdx.x & 31;
        float acc[1][112];
        uint32_t bias[28];
        {
            const uint32_t* bp = reinterpret_cast<const uint32_t*>(p.bias + tn * 224) + (lane & 3);
#pragma unroll
            for (int j = 0; j < 28; j++) bias[j] = __ldg(bp + j * 4);
        }
        pdl_wait();
        pdl_launch();
        TL(5, 0);
        gemm_mainloop<C, 28>(s, wg, acc, 5);
        TKW(0);
        if (wg == 1) {
            wg_wait<0>();
            named_arrive(10, 256);
            named_bar(11, 256);
        }
#pragma unroll
        for (int k = 28; k < 32; k++) {
            mbar_wait(s.full0 + 8 * (k % C::STAGES), (k / C::STAGES) & 1);
            const uint32_t sb = s.base + (k % C::STAGES) * C::STAGE_BYTES;
            wg_fence();
#pragma unroll
            for (int kk = 0; kk < 4; kk++) C::mma(acc[0], C::desc_a(sb, wg, 0, kk), C::desc_b(sb, kk), 1);
            wg_commit();
        }
        if (wg == 0) named_arrive(11, 256);
        TKW(1);
        wg_wait<0>();
        fence_regs(acc[0]);
        TKW(2);
        TL(5, 1);
        if (wg == 0) { named_arrive(12, 256); named_bar(10, 256); }
        else named_bar(12, 256);
        const int arow = warp * 16 + ((lane >> 3) & 1) * 8 + (lane & 7);
        const uint32_t stg = s.base + C::stage_off(wg);
#pragma unroll
        for (int jp = 0; jp < 14; jp++) {
            float v[8];
#pragma unroll
            for (int i = 0; i < 8; i++) {
                const uint32_t b2 = bias[jp * 2 + (i >> 2)];
                const float hx = fmaf((i & 1) ? bf_hi(b2) : bf_lo(b2), 0.5f, acc[0][jp * 8 + i]);
                v[i] = fmaf(hx, tanh_fast(hx * fmaf(hx * hx, 8.f * 0.0356774081363f, 2.f * 0.7978845608029f)), hx);
            }
            const int j = jp * 2 + (lane >> 4);
            const uint32_t addr = stg + (j >> 2) * 4096 + arow * 64 + (((j & 3) ^ ((arow >> 1) & 3)) << 4);
            stmatrix_x4(addr, pack_bf16(v[0], v[1]), pack_bf16(v[2], v[3]), pack_bf16(v[4], v[5]), pack_bf16(v[6], v[7]));
            if ((jp & 3) == 3 || jp == 13) hand_over(2 + wg * 4 + (jp >> 2));
        }
        TKW(3);
        TL(5, 5);
    }
}

typedef CUresult (*EncodeFn)(CUtensorMap*, CUtensorMapDataType, cuuint32_t, void*, const cuuint64_t*, const cuuint64_t*, const cuuint32_t*,
                             const cuuint32_t*, CUtensorMapInterleave, CUtensorMapSwizzle, CUtensorMapL2promotion, CUtensorMapFloatOOBfill);
EncodeFn g_encode;

void make_map(CUtensorMap* m, const void* ptr, int rank, const uint64_t* dims, const uint64_t* strides_bytes, const uint32_t* box, CUtensorMapSwizzle swz) {
    cuuint64_t d[5], st[5]; cuuint32_t b[5], es[5];
    for (int i = 0; i < rank; i++) { d[i] = dims[i]; b[i] = box[i]; es[i] = 1; }
    for (int i = 0; i + 1 < rank; i++) st[i] = strides_bytes[i];
    CUresult r = g_encode(m, CU_TENSOR_MAP_DATA_TYPE_BFLOAT16, rank, const_cast<void*>(ptr), d, st, b, es, CU_TENSOR_MAP_INTERLEAVE_NONE, swz,
                          CU_TENSOR_MAP_L2_PROMOTION_L2_128B, CU_TENSOR_MAP_FLOAT_OOB_FILL_NONE);
    if (r != CUDA_SUCCESS) fprintf(stderr, "cuTensorMapEncodeTiled failed: %d\n", (int)r);
}
void map2d(CUtensorMap* m, const void* ptr, uint64_t cols, uint64_t rows, uint32_t bc, uint32_t br, CUtensorMapSwizzle swz) {
    uint64_t dims[2] = {cols, rows}, st[1] = {cols * 2}; uint32_t box[2] = {bc, br};
    make_map(m, ptr, 2, dims, st, box, swz);
}
void map3d(CUtensorMap* m, const void* ptr, uint64_t cols, uint64_t rows, uint32_t inner, uint32_t br, uint32_t nblk, CUtensorMapSwizzle swz) {
    uint64_t dims[3] = {inner, rows, cols / inner}, st[2] = {cols * 2, (uint64_t)inner * 2}; uint32_t box[3] = {inner, br, nblk};
    make_map(m, ptr, 3, dims, st, box, swz);
}

template <class... KArgs, class... Args>
void launch(void (*kern)(KArgs...), int grid, int block, int smem, bool pdl, bool pair, Args&&... args) {
    cudaLaunchConfig_t cfg = {};
    cfg.gridDim = dim3(grid); cfg.blockDim = dim3(block); cfg.dynamicSmemBytes = smem; cfg.stream = 0;
    cudaLaunchAttribute at[2];
    int n = 0;
    if (pdl) { at[n].id = cudaLaunchAttributeProgrammaticStreamSerialization; at[n].val.programmaticStreamSerializationAllowed = 1; n++; }
    if (pair) { at[n].id = cudaLaunchAttributeClusterDimension; at[n].val.clusterDim.x = 2; at[n].val.clusterDim.y = 1; at[n].val.clusterDim.z = 1; n++; }
    cfg.attrs = at; cfg.numAttrs = n;
    cudaError_t e = cudaLaunchKernelEx(&cfg, kern, KArgs(args)...);
    if (e != cudaSuccess) fprintf(stderr, "launch failed: %s\n", cudaGetErrorString(e));
}

struct HostState {
    bool ready;
    const void* key[9];
    QkvParams qkv; AttnParams attn; ResParams wo, mix2; Mix1Params mix1;
    bf16 *qkvp, *o, *hn, *u;
};
HostState g_hs;

}

#define USE_PDL 1

extern "C" void kernel_launch(void* const* d_in, const int* in_sizes, int n_in, void* d_out, int out_size) {
    const bf16* x = (const bf16*)d_in[0];
    const bf16* wqkv = (const bf16*)d_in[1];
    const bf16* wo = (const bf16*)d_in[2];
    const bf16* w1 = (const bf16*)d_in[4];
    const bf16* b1 = (const bf16*)d_in[5];
    const bf16* w2 = (const bf16*)d_in[6];
    const bf16* b2 = (const bf16*)d_in[7];
    HostState& hs = g_hs;
    bool same = hs.ready;
    for (int i = 0; i < 8 && same; i++) same = (hs.key[i] == d_in[i]);
    same = same && hs.key[8] == d_out;
    if (!same) {
        if (!g_encode) {
            void* fn = nullptr; cudaDriverEntryPointQueryResult qr;
            cudaGetDriverEntryPoint("cuTensorMapEncodeTiled", &fn, cudaEnableDefault, &qr);
            g_encode = (EncodeFn)fn;
            cudaFuncSetAttribute(qkv_kernel, cudaFuncAttributeMaxDynamicSharedMemorySize, QkvCfg::SMEM);
            cudaFuncSetAttribute(attn_kernel, cudaFuncAttributeMaxDynamicSharedMemorySize, AT_SMEM);
            cudaFuncSetAttribute(res_gemm_kernel<false>, cudaFuncAttributeMaxDynamicSharedMemorySize, ResCfg<false>::SMEM);
            cudaFuncSetAttribute(res_gemm_kernel<true>, cudaFuncAttributeMaxDynamicSharedMemorySize, ResCfg<true>::SMEM);
            cudaFuncSetAttribute(mix1_kernel, cudaFuncAttributeMaxDynamicSharedMemorySize, Mix1Cfg::SMEM);
        }
        cudaGetSymbolAddress((void**)&hs.qkvp, g_qkv); cudaGetSymbolAddress((void**)&hs.o, g_o);
        cudaGetSymbolAddress((void**)&hs.hn, g_hn); cudaGetSymbolAddress((void**)&hs.u, g_u);
        const CUtensorMapSwizzle S128 = CU_TENSOR_MAP_SWIZZLE_128B, S64 = CU_TENSOR_MAP_SWIZZLE_64B;
        map2d(&hs.qkv.x, x, DM, SEQ, 64, 256, S128);
        hs.qkv.xp = x; hs.qkv.wp = wqkv;
        {
            uint64_t dims[4] = {64, (uint64_t)DM, 3, 16}, st[3] = {3 * DM * 2, DM * 2, 128}; uint32_t box[4] = {64, 64, 3, 1};
            make_map(&hs.qkv.w, wqkv, 4, dims, st, box, S128);
        }
        map2d(&hs.qkv.out, hs.qkvp, HD, 3 * NH * SEQ, 32, 128, S64);
        map2d(&hs.qkv.out64, hs.qkvp, HD, 3 * NH * SEQ, 32, 64, S64);
        hs.attn.kv = hs.qkv.out;
        map2d(&hs.attn.o, hs.o, DM, SEQ, 32, 16, S64); hs.attn.optr = hs.o;
        {
            uint64_t dims[3] = {(uint64_t)HD, (uint64_t)NH * SEQ, 3}, st[2] = {HD * 2, (uint64_t)NH * SEQ * HD * 2}; uint32_t box[3] = {32, 128, 2};
            make_map(&hs.attn.kv2, hs.qkvp, 3, dims, st, box, S64);
        }
        map2d(&hs.wo.a, hs.o, DM, SEQ, 64, ResCfg<false>::MC ? 64 : 128, S128);
        map3d(&hs.wo.b, wo, DM, DM, 64, 64, 2, S128);
        map2d(&hs.wo.res, x, DM, SEQ, 64, 128, S128);
        map2d(&hs.wo.out, hs.hn, DM, SEQ, 64, 64, S128);
        hs.wo.bias = nullptr;
        map3d(&hs.mix1.hn, hs.hn, DM, SEQ, 64, 64, 2, S128);
        map3d(&hs.mix1.w1, w1, FF, SEQ, 32, 32, 7, S64);
        hs.mix1.pf = (const uint8_t*)w2;
        hs.attn.pf_wo = (const uint8_t*)wo; hs.attn.pf_w1 = (const uint8_t*)w1; hs.attn.pf_b1 = (const uint8_t*)b1;
        map3d(&hs.mix1.out, hs.u, FF, DM, 32, 64, 1, S64);
        hs.mix1.bias = b1;
        map3d(&hs.mix2.a, w2, SEQ, FF, 64, 64, ResCfg<true>::MC ? 1 : 2, S128);
        map2d(&hs.mix2.b, hs.u, FF, DM, 64, 128, S128);
        map2d(&hs.mix2.res, hs.hn, DM, SEQ, 64, 128, S128);
        map2d(&hs.mix2.out, d_out, DM, SEQ, 64, 64, S128);
        hs.mix2.bias = b2;
        for (int i = 0; i < 8; i++) hs.key[i] = d_in[i];
        hs.key[8] = d_out;
        hs.ready = true;
    }
    const bool pdl = USE_PDL;
    const int G = 128;
    launch(qkv_kernel, G, 384, QkvCfg::SMEM, false, QkvCfg::PAIR, hs.qkv);
    launch(attn_kernel, 128, 512, AT_SMEM, pdl, false, hs.attn);
    launch(res_gemm_kernel<false>, G, 384, ResCfg<false>::SMEM, pdl, ResCfg<false>::PAIR, hs.wo);
    launch(mix1_kernel, G, 384, Mix1Cfg::SMEM, pdl, Mix1Cfg::PAIR, hs.mix1);
    launch(res_gemm_kernel<true>, G, 384, ResCfg<true>::SMEM, pdl, ResCfg<true>::PAIR, hs.mix2);
}
```

```cpp
#include <cuda_runtime.h>
#include <cuda_bf16.h>
#include <cuda.h>
#include <stdint.h>
#include <stdio.h>

typedef __nv_bfloat16 bf16;

namespace {

#define MIX1_PRE 1
#define WO_PRE 1
#define MIX2_PRE 1
#define PF_W2_DELAY 10000
#define QMASK_0 0xF0
#define QMASK_1 0xF0
#define QMASK_2 0xF0
#define QMASK_3 0xF0
#define MIX1_TK 0
#define QKV3_R1 10
#define QKV2_E0 5
#define QKV3_PF 7
#define MIX2_SKEW 4
#define WO_SKEW 4
#define QKV2_SKEW 1
#define PITCH_PAD 64
constexpr int PITCH = 1024 + PITCH_PAD;
constexpr int SEQ = 2048, DM = 1024, NH = 32, HD = 32, FF = 3584;

__device__ __align__(1024) bf16 g_qkv[3 * NH * SEQ * HD];
__device__ __align__(1024) bf16 g_o[SEQ * PITCH];
__device__ __align__(1024) bf16 g_hn[SEQ * PITCH];
__device__ __align__(1024) bf16 g_u[DM * FF];
__device__ __align__(16) uint32_t g_norm[3 * NH * 128];
__device__ float2 g_rowln[SEQ];
__device__ __align__(16) unsigned long long g_hpart[SEQ * 8];
__device__ __align__(16) unsigned long long g_rowstat2[SEQ];
__device__ __align__(16) uint32_t g_colsum2[8 * 3 * DM];

#define TL(kern, slot)
#define AX(slot)

__device__ __forceinline__ uint32_t smem_u32(const void* p) { return (uint32_t)__cvta_generic_to_shared(p); }
__device__ __forceinline__ void mbar_init(uint32_t bar, uint32_t cnt) { asm volatile("mbarrier.init.shared::cta.b64 [%0], %1;" :: "r"(bar), "r"(cnt) : "memory"); }
__device__ __forceinline__ void mbar_expect_tx(uint32_t bar, uint32_t bytes) { asm volatile("mbarrier.arrive.expect_tx.shared::cta.b64 _, [%0], %1;" :: "r"(bar), "r"(bytes) : "memory"); }
__device__ __forceinline__ void mbar_arrive(uint32_t bar) { asm volatile("mbarrier.arrive.shared::cta.b64 _, [%0];" :: "r"(bar) : "memory"); }
__device__ __forceinline__ void mbar_wait(uint32_t bar, uint32_t parity) {
    asm volatile("{\n.reg .pred p;\nWAIT_%=:\nmbarrier.try_wait.parity.shared::cta.b64 p, [%0], %1;\n@p bra DONE_%=;\nbra WAIT_%=;\nDONE_%=:\n}" :: "r"(bar), "r"(parity) : "memory");
}
__device__ __forceinline__ void fence_barrier_init() { asm volatile("fence.mbarrier_init.release.cluster;" ::: "memory"); }
__device__ __forceinline__ void fence_proxy_async() { asm volatile("fence.proxy.async.shared::cta;" ::: "memory"); }
__device__ __forceinline__ void pdl_launch() { asm volatile("griddepcontrol.launch_dependents;" ::: "memory"); }
__device__ __forceinline__ void pdl_wait() { asm volatile("griddepcontrol.wait;" ::: "memory"); }
__device__ __forceinline__ void named_bar(int id, int n) { asm volatile("bar.sync %0, %1;" :: "r"(id), "r"(n) : "memory"); }
__device__ __forceinline__ void named_arrive(int id, int n) { asm volatile("bar.arrive %0, %1;" :: "r"(id), "r"(n) : "memory"); }
__device__ __forceinline__ void hand_over(int id) { named_arrive(id, 160); }
__device__ __forceinline__ void take_over(int id) { named_bar(id, 160); fence_proxy_async(); }
__device__ __forceinline__ void prefetch_map(const CUtensorMap* m) { asm volatile("prefetch.tensormap [%0];" :: "l"(m) : "memory"); }

__device__ __forceinline__ void tma_ld2(uint32_t dst, const CUtensorMap* m, uint32_t bar, int c0, int c1) {
    asm volatile("cp.async.bulk.tensor.2d.shared::cluster.global.mbarrier::complete_tx::bytes [%0], [%1, {%3, %4}], [%2];"
                 :: "r"(dst), "l"(m), "r"(bar), "r"(c0), "r"(c1) : "memory");
}
__device__ __forceinline__ void tma_ld3(uint32_t dst, const CUtensorMap* m, uint32_t bar, int c0, int c1, int c2) {
    asm volatile("cp.async.bulk.tensor.3d.shared::cluster.global.mbarrier::complete_tx::bytes [%0], [%1, {%3, %4, %5}], [%2];"
                 :: "r"(dst), "l"(m), "r"(bar), "r"(c0), "r"(c1), "r"(c2) : "memory");
}
__device__ __forceinline__ void tma_ld3_mc(uint32_t dst, const CUtensorMap* m, uint32_t bar, int c0, int c1, int c2) {
    asm volatile("cp.async.bulk.tensor.3d.shared::cluster.global.mbarrier::complete_tx::bytes.multicast::cluster [%0], [%1, {%3, %4, %5}], [%2], %6;"
                 :: "r"(dst), "l"(m), "r"(bar), "r"(c0), "r"(c1), "r"(c2), "h"((uint16_t)3) : "memory");
}
__device__ __forceinline__ void tma_ld4_mc(uint32_t dst, const CUtensorMap* m, uint32_t bar, int c0, int c1, int c2, int c3) {
    asm volatile("cp.async.bulk.tensor.4d.shared::cluster.global.mbarrier::complete_tx::bytes.multicast::cluster [%0], [%1, {%3, %4, %5, %6}], [%2], %7;"
                 :: "r"(dst), "l"(m), "r"(bar), "r"(c0), "r"(c1), "r"(c2), "r"(c3), "h"((uint16_t)3) : "memory");
}
__device__ __forceinline__ void prefetch_line(const void* p) { asm volatile("prefetch.global.L2 [%0];" :: "l"(p)); }
__device__ __forceinline__ uint32_t mapa(uint32_t addr, uint32_t cta) { uint32_t r; asm("mapa.shared::cluster.u32 %0, %1, %2;" : "=r"(r) : "r"(addr), "r"(cta)); return r; }
__device__ __forceinline__ void mbar_arrive_cluster(uint32_t bar) { asm volatile("mbarrier.arrive.shared::cluster.b64 _, [%0];" :: "r"(bar) : "memory"); }
__device__ __forceinline__ void cluster_arrive() { asm volatile("barrier.cluster.arrive.relaxed.aligned;" ::: "memory"); }
__device__ __forceinline__ void cluster_wait() { asm volatile("barrier.cluster.wait.aligned;" ::: "memory"); }
__device__ __forceinline__ void tma_st2(const CUtensorMap* m, uint32_t src, int c0, int c1) {
    asm volatile("cp.async.bulk.tensor.2d.global.shared::cta.bulk_group [%0, {%2, %3}], [%1];" :: "l"(m), "r"(src), "r"(c0), "r"(c1) : "memory");
}
__device__ __forceinline__ void tma_st3(const CUtensorMap* m, uint32_t src, int c0, int c1, int c2) {
    asm volatile("cp.async.bulk.tensor.3d.global.shared::cta.bulk_group [%0, {%2, %3, %4}], [%1];" :: "l"(m), "r"(src), "r"(c0), "r"(c1), "r"(c2) : "memory");
}
__device__ __forceinline__ void tma_st_commit() { asm volatile("cp.async.bulk.commit_group;" ::: "memory"); }
__device__ __forceinline__ void tma_st_wait() { asm volatile("cp.async.bulk.wait_group.read 0;" ::: "memory"); }

__device__ __forceinline__ void wg_fence() { asm volatile("wgmma.fence.sync.aligned;" ::: "memory"); }
__device__ __forceinline__ void wg_commit() { asm volatile("wgmma.commit_group.sync.aligned;" ::: "memory"); }
template <int N> __device__ __forceinline__ void wg_wait() { asm volatile("wgmma.wait_group.sync.aligned %0;" :: "n"(N) : "memory"); }
template <int R> __device__ __forceinline__ void reg_alloc() { asm volatile("setmaxnreg.inc.sync.aligned.u32 %0;" :: "n"(R)); }
template <int R> __device__ __forceinline__ void reg_dealloc() { asm volatile("setmaxnreg.dec.sync.aligned.u32 %0;" :: "n"(R)); }
template <int N> __device__ __forceinline__ void fence_regs(float (&d)[N]) {
#pragma unroll
    for (int i = 0; i < N; i++) asm volatile("" : "+f"(d[i]) :: "memory");
}

__device__ __forceinline__ uint32_t desc_lo(uint32_t addr, uint32_t lbo) { return ((addr & 0x3FFFFu) >> 4) | ((lbo >> 4) << 16); }
__device__ __forceinline__ uint32_t pack_bf16(float lo, float hi) { uint32_t d; asm("cvt.rn.bf16x2.f32 %0, %1, %2;" : "=r"(d) : "f"(hi), "f"(lo)); return d; }
__device__ __forceinline__ float bf_lo(uint32_t v) { return __uint_as_float(v << 16); }
__device__ __forceinline__ float bf_hi(uint32_t v) { return __uint_as_float(v & 0xFFFF0000u); }
__device__ __forceinline__ void stmatrix_x4(uint32_t addr, uint32_t r0, uint32_t r1, uint32_t r2, uint32_t r3) {
    asm volatile("stmatrix.sync.aligned.m8n8.x4.shared.b16 [%0], {%1, %2, %3, %4};" :: "r"(addr), "r"(r0), "r"(r1), "r"(r2), "r"(r3));
}
__device__ __forceinline__ void ldmatrix_x4(uint32_t addr, uint32_t (&r)[4]) {
    asm volatile("ldmatrix.sync.aligned.m8n8.x4.shared.b16 {%0, %1, %2, %3}, [%4];" : "=r"(r[0]), "=r"(r[1]), "=r"(r[2]), "=r"(r[3]) : "r"(addr) : "memory");
}
__device__ __forceinline__ float ex2(float x) { float y; asm("ex2.approx.ftz.f32 %0, %1;" : "=f"(y) : "f"(x)); return y; }
__device__ __forceinline__ float tanh_fast(float x) { float y; asm("tanh.approx.f32 %0, %1;" : "=f"(y) : "f"(x)); return y; }

__device__ __forceinline__ void mma_qkv(float (&d)[96], uint32_t alo, uint32_t blo, int scale_d) {
    asm volatile("{\n.reg .pred p;\n.reg .b64 da, db;\nsetp.ne.b32 p, %98, 0;\nmov.b64 da, {%96, 0x40000040};\nmov.b64 db, {%97, 0x40000040};\n"
        "wgmma.mma_async.sync.aligned.m64n192k16.f32.bf16.bf16 {"
        "%0, %1, %2, %3, %4, %5, %6, %7, %8, %9, %10, %11, %12, %13, %14, %15, %16, %17, %18, %19, %20, %21, %22, %23, %24, %25, %26, %27, %28, %29, %30, %31,  "
        "%32, %33, %34, %35, %36, %37, %38, %39, %40, %41, %42, %43, %44, %45, %46, %47, %48, %49, %50, %51, %52, %53, %54, %55, %56, %57, %58, %59, %60, %61,  "
        "%62, %63, %64, %65, %66, %67, %68, %69, %70, %71, %72, %73, %74, %75, %76, %77, %78, %79, %80, %81, %82, %83, %84, %85, %86, %87, %88, %89, %90, %91,  "
        "%92, %93, %94, %95 "
        "}, da, db, p, 1, 1, 0, 1;\n}\n"
        : "+f"(d[0]), "+f"(d[1]), "+f"(d[2]), "+f"(d[3]), "+f"(d[4]), "+f"(d[5]), "+f"(d[6]), "+f"(d[7]), "+f"(d[8]), "+f"(d[9]), "+f"(d[10]), "+f"(d[11]),
          "+f"(d[12]), "+f"(d[13]), "+f"(d[14]), "+f"(d[15]), "+f"(d[16]), "+f"(d[17]), "+f"(d[18]), "+f"(d[19]), "+f"(d[20]), "+f"(d[21]), "+f"(d[22]),
          "+f"(d[23]), "+f"(d[24]), "+f"(d[25]), "+f"(d[26]), "+f"(d[27]), "+f"(d[28]), "+f"(d[29]), "+f"(d[30]), "+f"(d[31]), "+f"(d[32]), "+f"(d[33]),
          "+f"(d[34]), "+f"(d[35]), "+f"(d[36]), "+f"(d[37]), "+f"(d[38]), "+f"(d[39]), "+f"(d[40]), "+f"(d[41]), "+f"(d[42]), "+f"(d[43]), "+f"(d[44]),
          "+f"(d[45]), "+f"(d[46]), "+f"(d[47]), "+f"(d[48]), "+f"(d[49]), "+f"(d[50]), "+f"(d[51]), "+f"(d[52]), "+f"(d[53]), "+f"(d[54]), "+f"(d[55]),
          "+f"(d[56]), "+f"(d[57]), "+f"(d[58]), "+f"(d[59]), "+f"(d[60]), "+f"(d[61]), "+f"(d[62]), "+f"(d[63]), "+f"(d[64]), "+f"(d[65]), "+f"(d[66]),
          "+f"(d[67]), "+f"(d[68]), "+f"(d[69]), "+f"(d[70]), "+f"(d[71]), "+f"(d[72]), "+f"(d[73]), "+f"(d[74]), "+f"(d[75]), "+f"(d[76]), "+f"(d[77]),
          "+f"(d[78]), "+f"(d[79]), "+f"(d[80]), "+f"(d[81]), "+f"(d[82]), "+f"(d[83]), "+f"(d[84]), "+f"(d[85]), "+f"(d[86]), "+f"(d[87]), "+f"(d[88]),
          "+f"(d[89]), "+f"(d[90]), "+f"(d[91]), "+f"(d[92]), "+f"(d[93]), "+f"(d[94]), "+f"(d[95])
        : "r"(alo), "r"(blo), "r"(scale_d));
}
__device__ __forceinline__ void mma_wo(float (&d)[64], uint32_t alo, uint32_t blo, int scale_d) {
    asm volatile("{\n.reg .pred p;\n.reg .b64 da, db;\nsetp.ne.b32 p, %66, 0;\nmov.b64 da, {%64, 0x40000040};\nmov.b64 db, {%65, 0x40000040};\n"
        "wgmma.mma_async.sync.aligned.m64n128k16.f32.bf16.bf16 {"
        "%0, %1, %2, %3, %4, %5, %6, %7, %8, %9, %10, %11, %12, %13, %14, %15, %16, %17, %18, %19, %20, %21, %22, %23, %24, %25, %26, %27, %28, %29, %30, %31,  "
        "%32, %33, %34, %35, %36, %37, %38, %39, %40, %41, %42, %43, %44, %45, %46, %47, %48, %49, %50, %51, %52, %53, %54, %55, %56, %57, %58, %59, %60, %61,  "
        "%62, %63 "
        "}, da, db, p, 1, 1, 0, 1;\n}\n"
        : "+f"(d[0]), "+f"(d[1]), "+f"(d[2]), "+f"(d[3]), "+f"(d[4]), "+f"(d[5]), "+f"(d[6]), "+f"(d[7]), "+f"(d[8]), "+f"(d[9]), "+f"(d[10]), "+f"(d[11]),
          "+f"(d[12]), "+f"(d[13]), "+f"(d[14]), "+f"(d[15]), "+f"(d[16]), "+f"(d[17]), "+f"(d[18]), "+f"(d[19]), "+f"(d[20]), "+f"(d[21]), "+f"(d[22]),
          "+f"(d[23]), "+f"(d[24]), "+f"(d[25]), "+f"(d[26]), "+f"(d[27]), "+f"(d[28]), "+f"(d[29]), "+f"(d[30]), "+f"(d[31]), "+f"(d[32]), "+f"(d[33]),
          "+f"(d[34]), "+f"(d[35]), "+f"(d[36]), "+f"(d[37]), "+f"(d[38]), "+f"(d[39]), "+f"(d[40]), "+f"(d[41]), "+f"(d[42]), "+f"(d[43]), "+f"(d[44]),
          "+f"(d[45]), "+f"(d[46]), "+f"(d[47]), "+f"(d[48]), "+f"(d[49]), "+f"(d[50]), "+f"(d[51]), "+f"(d[52]), "+f"(d[53]), "+f"(d[54]), "+f"(d[55]),
          "+f"(d[56]), "+f"(d[57]), "+f"(d[58]), "+f"(d[59]), "+f"(d[60]), "+f"(d[61]), "+f"(d[62]), "+f"(d[63])
        : "r"(alo), "r"(blo), "r"(scale_d));
}
__device__ __forceinline__ void mma_mix2(float (&d)[64], uint32_t alo, uint32_t blo, int scale_d) {
    asm volatile("{\n.reg .pred p;\n.reg .b64 da, db;\nsetp.ne.b32 p, %66, 0;\nmov.b64 da, {%64, 0x40000040};\nmov.b64 db, {%65, 0x40000040};\n"
        "wgmma.mma_async.sync.aligned.m64n128k16.f32.bf16.bf16 {"
        "%0, %1, %2, %3, %4, %5, %6, %7, %8, %9, %10, %11, %12, %13, %14, %15, %16, %17, %18, %19, %20, %21, %22, %23, %24, %25, %26, %27, %28, %29, %30, %31,  "
        "%32, %33, %34, %35, %36, %37, %38, %39, %40, %41, %42, %43, %44, %45, %46, %47, %48, %49, %50, %51, %52, %53, %54, %55, %56, %57, %58, %59, %60, %61,  "
        "%62, %63 "
        "}, da, db, p, 1, 1, 1, 0;\n}\n"
        : "+f"(d[0]), "+f"(d[1]), "+f"(d[2]), "+f"(d[3]), "+f"(d[4]), "+f"(d[5]), "+f"(d[6]), "+f"(d[7]), "+f"(d[8]), "+f"(d[9]), "+f"(d[10]), "+f"(d[11]),
          "+f"(d[12]), "+f"(d[13]), "+f"(d[14]), "+f"(d[15]), "+f"(d[16]), "+f"(d[17]), "+f"(d[18]), "+f"(d[19]), "+f"(d[20]), "+f"(d[21]), "+f"(d[22]),
          "+f"(d[23]), "+f"(d[24]), "+f"(d[25]), "+f"(d[26]), "+f"(d[27]), "+f"(d[28]), "+f"(d[29]), "+f"(d[30]), "+f"(d[31]), "+f"(d[32]), "+f"(d[33]),
          "+f"(d[34]), "+f"(d[35]), "+f"(d[36]), "+f"(d[37]), "+f"(d[38]), "+f"(d[39]), "+f"(d[40]), "+f"(d[41]), "+f"(d[42]), "+f"(d[43]), "+f"(d[44]),
          "+f"(d[45]), "+f"(d[46]), "+f"(d[47]), "+f"(d[48]), "+f"(d[49]), "+f"(d[50]), "+f"(d[51]), "+f"(d[52]), "+f"(d[53]), "+f"(d[54]), "+f"(d[55]),
          "+f"(d[56]), "+f"(d[57]), "+f"(d[58]), "+f"(d[59]), "+f"(d[60]), "+f"(d[61]), "+f"(d[62]), "+f"(d[63])
        : "r"(alo), "r"(blo), "r"(scale_d));
}
__device__ __forceinline__ void mma_mix1(float (&d)[112], uint32_t alo, uint32_t blo, int scale_d) {
    asm volatile("{\n.reg .pred p;\n.reg .b64 da, db;\nsetp.ne.b32 p, %114, 0;\nmov.b64 da, {%112, 0x40000040};\nmov.b64 db, {%113, 0x80000020};\n"
        "wgmma.mma_async.sync.aligned.m64n224k16.f32.bf16.bf16 {"
        "%0, %1, %2, %3, %4, %5, %6, %7, %8, %9, %10, %11, %12, %13, %14, %15, %16, %17, %18, %19, %20, %21, %22, %23, %24, %25, %26, %27, %28, %29, %30, %31,  "
        "%32, %33, %34, %35, %36, %37, %38, %39, %40, %41, %42, %43, %44, %45, %46, %47, %48, %49, %50, %51, %52, %53, %54, %55, %56, %57, %58, %59, %60, %61,  "
        "%62, %63, %64, %65, %66, %67, %68, %69, %70, %71, %72, %73, %74, %75, %76, %77, %78, %79, %80, %81, %82, %83, %84, %85, %86, %87, %88, %89, %90, %91,  "
        "%92, %93, %94, %95, %96, %97, %98, %99, %100, %101, %102, %103, %104, %105, %106, %107, %108, %109, %110, %111 "
        "}, da, db, p, 1, 1, 1, 1;\n}\n"
        : "+f"(d[0]), "+f"(d[1]), "+f"(d[2]), "+f"(d[3]), "+f"(d[4]), "+f"(d[5]), "+f"(d[6]), "+f"(d[7]), "+f"(d[8]), "+f"(d[9]), "+f"(d[10]), "+f"(d[11]),
          "+f"(d[12]), "+f"(d[13]), "+f"(d[14]), "+f"(d[15]), "+f"(d[16]), "+f"(d[17]), "+f"(d[18]), "+f"(d[19]), "+f"(d[20]), "+f"(d[21]), "+f"(d[22]),
          "+f"(d[23]), "+f"(d[24]), "+f"(d[25]), "+f"(d[26]), "+f"(d[27]), "+f"(d[28]), "+f"(d[29]), "+f"(d[30]), "+f"(d[31]), "+f"(d[32]), "+f"(d[33]),
          "+f"(d[34]), "+f"(d[35]), "+f"(d[36]), "+f"(d[37]), "+f"(d[38]), "+f"(d[39]), "+f"(d[40]), "+f"(d[41]), "+f"(d[42]), "+f"(d[43]), "+f"(d[44]),
          "+f"(d[45]), "+f"(d[46]), "+f"(d[47]), "+f"(d[48]), "+f"(d[49]), "+f"(d[50]), "+f"(d[51]), "+f"(d[52]), "+f"(d[53]), "+f"(d[54]), "+f"(d[55]),
          "+f"(d[56]), "+f"(d[57]), "+f"(d[58]), "+f"(d[59]), "+f"(d[60]), "+f"(d[61]), "+f"(d[62]), "+f"(d[63]), "+f"(d[64]), "+f"(d[65]), "+f"(d[66]),
          "+f"(d[67]), "+f"(d[68]), "+f"(d[69]), "+f"(d[70]), "+f"(d[71]), "+f"(d[72]), "+f"(d[73]), "+f"(d[74]), "+f"(d[75]), "+f"(d[76]), "+f"(d[77]),
          "+f"(d[78]), "+f"(d[79]), "+f"(d[80]), "+f"(d[81]), "+f"(d[82]), "+f"(d[83]), "+f"(d[84]), "+f"(d[85]), "+f"(d[86]), "+f"(d[87]), "+f"(d[88]),
          "+f"(d[89]), "+f"(d[90]), "+f"(d[91]), "+f"(d[92]), "+f"(d[93]), "+f"(d[94]), "+f"(d[95]), "+f"(d[96]), "+f"(d[97]), "+f"(d[98]), "+f"(d[99]),
          "+f"(d[100]), "+f"(d[101]), "+f"(d[102]), "+f"(d[103]), "+f"(d[104]), "+f"(d[105]), "+f"(d[106]), "+f"(d[107]), "+f"(d[108]), "+f"(d[109]),
          "+f"(d[110]), "+f"(d[111])
        : "r"(alo), "r"(blo), "r"(scale_d));
}
__device__ __forceinline__ void mma_qk0(float (&d)[32], uint32_t alo, uint32_t blo) {
    asm volatile("{\n.reg .pred p;\n.reg .b64 da, db;\nsetp.ne.b32 p, 0, 0;\nmov.b64 da, {%32, 0x80000020};\nmov.b64 db, {%33, 0x80000020};\n"
        "wgmma.mma_async.sync.aligned.m64n64k16.f32.bf16.bf16 {"
        "%0, %1, %2, %3, %4, %5, %6, %7, %8, %9, %10, %11, %12, %13, %14, %15, %16, %17, %18, %19, %20, %21, %22, %23, %24, %25, %26, %27, %28, %29, %30, %31 "
        "}, da, db, p, 1, 1, 0, 0;\n}\n"
        : "=f"(d[0]), "=f"(d[1]), "=f"(d[2]), "=f"(d[3]), "=f"(d[4]), "=f"(d[5]), "=f"(d[6]), "=f"(d[7]), "=f"(d[8]), "=f"(d[9]), "=f"(d[10]), "=f"(d[11]),
          "=f"(d[12]), "=f"(d[13]), "=f"(d[14]), "=f"(d[15]), "=f"(d[16]), "=f"(d[17]), "=f"(d[18]), "=f"(d[19]), "=f"(d[20]), "=f"(d[21]), "=f"(d[22]),
          "=f"(d[23]), "=f"(d[24]), "=f"(d[25]), "=f"(d[26]), "=f"(d[27]), "=f"(d[28]), "=f"(d[29]), "=f"(d[30]), "=f"(d[31])
        : "r"(alo), "r"(blo));
}
__device__ __forceinline__ void mma_qk1(float (&d)[32], uint32_t alo, uint32_t blo, int scale_d) {
    asm volatile("{\n.reg .pred p;\n.reg .b64 da, db;\nsetp.ne.b32 p, %34, 0;\nmov.b64 da, {%32, 0x80000020};\nmov.b64 db, {%33, 0x80000020};\n"
        "wgmma.mma_async.sync.aligned.m64n64k16.f32.bf16.bf16 {"
        "%0, %1, %2, %3, %4, %5, %6, %7, %8, %9, %10, %11, %12, %13, %14, %15, %16, %17, %18, %19, %20, %21, %22, %23, %24, %25, %26, %27, %28, %29, %30, %31 "
        "}, da, db, p, 1, 1, 0, 0;\n}\n"
        : "+f"(d[0]), "+f"(d[1]), "+f"(d[2]), "+f"(d[3]), "+f"(d[4]), "+f"(d[5]), "+f"(d[6]), "+f"(d[7]), "+f"(d[8]), "+f"(d[9]), "+f"(d[10]), "+f"(d[11]),
          "+f"(d[12]), "+f"(d[13]), "+f"(d[14]), "+f"(d[15]), "+f"(d[16]), "+f"(d[17]), "+f"(d[18]), "+f"(d[19]), "+f"(d[20]), "+f"(d[21]), "+f"(d[22]),
          "+f"(d[23]), "+f"(d[24]), "+f"(d[25]), "+f"(d[26]), "+f"(d[27]), "+f"(d[28]), "+f"(d[29]), "+f"(d[30]), "+f"(d[31])
        : "r"(alo), "r"(blo), "r"(scale_d));
}
__device__ __forceinline__ void mma_pv(float (&d)[20], uint32_t a0, uint32_t a1, uint32_t a2, uint32_t a3, uint32_t blo, int scale_d) {
    asm volatile("{\n.reg .pred p;\n.reg .b64 da, db;\nsetp.ne.b32 p, %25, 0;\nmov.b64 db, {%24, 0x80000020};\n"
        "wgmma.mma_async.sync.aligned.m64n40k16.f32.bf16.bf16 {"
        "%0, %1, %2, %3, %4, %5, %6, %7, %8, %9, %10, %11, %12, %13, %14, %15, %16, %17, %18, %19 "
        "}, {%20, %21, %22, %23}, db, p, 1, 1, 1;\n}\n"
        : "+f"(d[0]), "+f"(d[1]), "+f"(d[2]), "+f"(d[3]), "+f"(d[4]), "+f"(d[5]), "+f"(d[6]), "+f"(d[7]), "+f"(d[8]), "+f"(d[9]), "+f"(d[10]), "+f"(d[11]),
          "+f"(d[12]), "+f"(d[13]), "+f"(d[14]), "+f"(d[15]), "+f"(d[16]), "+f"(d[17]), "+f"(d[18]), "+f"(d[19])
        : "r"(a0), "r"(a1), "r"(a2), "r"(a3), "r"(blo), "r"(scale_d));
}
__device__ __forceinline__ void mma_qk0w(float (&d)[32], uint64_t da, uint64_t db) {
    asm volatile("{\n.reg .pred p;\n.reg .b64 da, db;\nsetp.ne.b32 p, 0, 0;\nmov.b64 da, %32;\nmov.b64 db, %33;\n"
        "wgmma.mma_async.sync.aligned.m64n64k16.f32.bf16.bf16 {"
        "%0, %1, %2, %3, %4, %5, %6, %7, %8, %9, %10, %11, %12, %13, %14, %15, %16, %17, %18, %19, %20, %21, %22, %23, %24, %25, %26, %27, %28, %29, %30, %31 "
        "}, da, db, p, 1, 1, 0, 0;\n}\n"
        : "=f"(d[0]), "=f"(d[1]), "=f"(d[2]), "=f"(d[3]), "=f"(d[4]), "=f"(d[5]), "=f"(d[6]), "=f"(d[7]), "=f"(d[8]), "=f"(d[9]), "=f"(d[10]), "=f"(d[11]),
          "=f"(d[12]), "=f"(d[13]), "=f"(d[14]), "=f"(d[15]), "=f"(d[16]), "=f"(d[17]), "=f"(d[18]), "=f"(d[19]), "=f"(d[20]), "=f"(d[21]), "=f"(d[22]),
          "=f"(d[23]), "=f"(d[24]), "=f"(d[25]), "=f"(d[26]), "=f"(d[27]), "=f"(d[28]), "=f"(d[29]), "=f"(d[30]), "=f"(d[31])
        : "l"(da), "l"(db));
}
__device__ __forceinline__ void mma_qk1w(float (&d)[32], uint64_t da, uint64_t db, int scale_d) {
    asm volatile("{\n.reg .pred p;\n.reg .b64 da, db;\nsetp.ne.b32 p, %34, 0;\nmov.b64 da, %32;\nmov.b64 db, %33;\n"
        "wgmma.mma_async.sync.aligned.m64n64k16.f32.bf16.bf16 {"
        "%0, %1, %2, %3, %4, %5, %6, %7, %8, %9, %10, %11, %12, %13, %14, %15, %16, %17, %18, %19, %20, %21, %22, %23, %24, %25, %26, %27, %28, %29, %30, %31 "
        "}, da, db, p, 1, 1, 0, 0;\n}\n"
        : "+f"(d[0]), "+f"(d[1]), "+f"(d[2]), "+f"(d[3]), "+f"(d[4]), "+f"(d[5]), "+f"(d[6]), "+f"(d[7]), "+f"(d[8]), "+f"(d[9]), "+f"(d[10]), "+f"(d[11]),
          "+f"(d[12]), "+f"(d[13]), "+f"(d[14]), "+f"(d[15]), "+f"(d[16]), "+f"(d[17]), "+f"(d[18]), "+f"(d[19]), "+f"(d[20]), "+f"(d[21]), "+f"(d[22]),
          "+f"(d[23]), "+f"(d[24]), "+f"(d[25]), "+f"(d[26]), "+f"(d[27]), "+f"(d[28]), "+f"(d[29]), "+f"(d[30]), "+f"(d[31])
        : "l"(da), "l"(db), "r"(scale_d));
}
__device__ __forceinline__ void mma_pvw(float (&d)[20], uint32_t a0, uint32_t a1, uint32_t a2, uint32_t a3, uint64_t db, int scale_d) {
    asm volatile("{\n.reg .pred p;\n.reg .b64 da, db;\nsetp.ne.b32 p, %25, 0;\nmov.b64 db, %24;\n"
        "wgmma.mma_async.sync.aligned.m64n40k16.f32.bf16.bf16 {"
        "%0, %1, %2, %3, %4, %5, %6, %7, %8, %9, %10, %11, %12, %13, %14, %15, %16, %17, %18, %19 "
        "}, {%20, %21, %22, %23}, db, p, 1, 1, 1;\n}\n"
        : "+f"(d[0]), "+f"(d[1]), "+f"(d[2]), "+f"(d[3]), "+f"(d[4]), "+f"(d[5]), "+f"(d[6]), "+f"(d[7]), "+f"(d[8]), "+f"(d[9]), "+f"(d[10]), "+f"(d[11]),
          "+f"(d[12]), "+f"(d[13]), "+f"(d[14]), "+f"(d[15]), "+f"(d[16]), "+f"(d[17]), "+f"(d[18]), "+f"(d[19])
        : "r"(a0), "r"(a1), "r"(a2), "r"(a3), "l"(db), "r"(scale_d));
}

struct GemmSmem { uint32_t base, full0, empty0, aux; };

struct NoEarly { __device__ __forceinline__ void operator()(const GemmSmem&) const {} };
template <class C, class E = NoEarly>
__device__ __forceinline__ GemmSmem gemm_setup(uint8_t* smem_raw, E early = E()) {
    GemmSmem s;
    s.base = smem_u32(smem_raw);
    s.full0 = s.base + C::BAR_OFF; s.empty0 = s.full0 + 8 * C::STAGES; s.aux = s.empty0 + 8 * C::STAGES;
    if (threadIdx.x == 0) {
        if (s.base & 1023) __trap();
        for (int i = 0; i < C::STAGES; i++) { mbar_init(s.full0 + 8 * i, 1); mbar_init(s.empty0 + 8 * i, C::MC ? 16 : 8); }
        mbar_init(s.aux, C::AUX_COUNT);
        fence_barrier_init();
        early(s);
    }
    __syncthreads();
    if (C::MC) { cluster_arrive(); cluster_wait(); }
    return s;
}

#define TK(slot)
#define TKC(slot)
#define TKW(slot)
template <class C, class P>
__device__ __forceinline__ void gemm_producer(const GemmSmem& s, const P& p, int tm, int tn) {
    TK(8);
    C::load_aux(p, s, tm, tn);
#pragma unroll 1
    for (int k = 0; k < C::PRE; k++) {
        mbar_expect_tx(s.full0 + 8 * k, C::STAGE_BYTES);
        C::load_w(p, s.base + k * C::STAGE_BYTES, s.full0 + 8 * k, k, tm, tn);
    }
    TK(9);
    pdl_wait();
    TK(10);
#pragma unroll 1
    for (int k = 0; k < C::STAGES; k++) {
        if (k >= C::PRE) mbar_expect_tx(s.full0 + 8 * k, C::STAGE_BYTES);
        C::load_x(p, s.base + k * C::STAGE_BYTES, s.full0 + 8 * k, k, tm, tn);
        if (k >= C::PRE) C::load_w(p, s.base + k * C::STAGE_BYTES, s.full0 + 8 * k, k, tm, tn);
    }
    TK(11);
    int st = 0; uint32_t ph = 0;
#pragma unroll 1
    for (int k = C::STAGES; k < C::KSTEPS; k++) {
        mbar_wait(s.empty0 + 8 * st, ph);
        if (k < C::STAGES + C::FOLLOW) mbar_wait(s.aux + 16 + 8 * st, ph);
        C::after_release(p, s, k, tm, tn);
        mbar_expect_tx(s.full0 + 8 * st, C::STAGE_BYTES);
        C::load_x(p, s.base + st * C::STAGE_BYTES, s.full0 + 8 * st, k, tm, tn);
        C::load_w(p, s.base + st * C::STAGE_BYTES, s.full0 + 8 * st, k, tm, tn);
        if (++st == C::STAGES) { st = 0; ph ^= 1; }
    }
    C::producer_done(s);
}

template <class C, int KEND = C::KSTEPS, int SK = 0, bool DONE_BAR = false>
__device__ __forceinline__ void gemm_mainloop(const GemmSmem& s, int wg, float (&acc)[C::MB][C::BN / 2], int tlk = 0) {
    const int lane = threadIdx.x & 31;
    int st = 0; uint32_t ph = 0;
    int prev = 0;
    const uint32_t rel0 = C::MC ? mapa(s.empty0, lane & 1) : s.empty0;
#pragma unroll
    for (int m = 0; m < C::MB; m++) fence_regs(acc[m]);
#pragma unroll 1
    for (int k = 0; k < KEND; k++) {
        if (SK > 0 && k == KEND - SK && wg == 1) {
            if (DONE_BAR) { wg_wait<0>(); named_arrive(10, 256); }
            named_bar(11, 256);
        }
        mbar_wait(s.full0 + 8 * st, ph);
        const uint32_t sb = s.base + st * C::STAGE_BYTES;
        wg_fence();
#pragma unroll
        for (int kk = 0; kk < 4; kk++) {
#pragma unroll
            for (int m = 0; m < C::MB; m++) C::mma(acc[m], C::desc_a(sb, wg, m, kk), C::desc_b(sb, kk), C::ACC_INIT || (k | kk) != 0);
        }
        wg_commit();
        if (SK > 0 && k == KEND - 1 && wg == 0) named_arrive(11, 256);
        if (k > 0) {
            wg_wait<1>();
            if (k <= C::KSTEPS - C::STAGES) {
                if (C::MC) { if (lane < 2) mbar_arrive_cluster(rel0 + 8 * prev); }
                else if (lane == 0) mbar_arrive(rel0 + 8 * prev);
            }
        }
        prev = st;
        if (++st == C::STAGES) { st = 0; ph ^= 1; }
    }
    if (KEND == C::KSTEPS) {
        wg_wait<0>();
#pragma unroll
        for (int m = 0; m < C::MB; m++) fence_regs(acc[m]);
    }
}

struct QkvParams { CUtensorMap x, w, out; const bf16* xp; const bf16* wp; };
struct QkvCfg {
    static constexpr int MB = 1, BN = 192, KSTEPS = 32, STAGES = 4, A_BYTES = 16384, B_BYTES = 24576;
    static constexpr int STAGE_BYTES = A_BYTES + B_BYTES, STG_OFF = STAGES * STAGE_BYTES, BAR_OFF = STG_OFF + 65536, AUX_OFF = BAR_OFF + 128, SMEM = AUX_OFF + 2816;
    static constexpr int AUX_COUNT = 3, PRE = 0;
    static constexpr int TLK = 1;
    static constexpr bool MC = true, ACC_INIT = false;
    static constexpr int FOLLOW = 16;
    static __device__ __forceinline__ void after_release(const QkvParams& p, const GemmSmem& s, int k, int tm, int tn) {
        const int g2 = k - (21 + QKV2_E0);
        if (g2 == 0 || g2 == 2 || g2 == 4) {
            fence_proxy_async();
#pragma unroll
            for (int i = 0; i < 4; i++)
                tma_st2(&p.out, s.base + STG_OFF + (i >> 1) * 24576 + (g2 + (i & 1)) * 4096, 0, (g2 >> 1) * (NH * SEQ) + (tn * 2 + (i & 1)) * SEQ + tm * 256 + (i >> 1) * 64);
        }
    }
    static __device__ __forceinline__ void producer_done(const GemmSmem& s) {
        tma_st_commit(); tma_st_wait(); mbar_arrive(s.aux + 48);
    }
    static __device__ __forceinline__ void load_w(const QkvParams& p, uint32_t sb, uint32_t bar, int k, int tm, int tn) {
        tma_ld4_mc(sb + A_BYTES + (tm & 1) * (B_BYTES / 2), &p.w, bar, 0, (k & 15) * 64 + (tm & 1) * 32, 0, tn);
    }
    static __device__ __forceinline__ void load_x(const QkvParams& p, uint32_t sb, uint32_t bar, int k, int tm, int tn) { tma_ld2(sb, &p.x, bar, (k & 15) * 64, tm * 256 + (k >> 4) * 128); }
    static __device__ __forceinline__ void load_aux(const QkvParams&, const GemmSmem&, int, int) {}
    static __device__ __forceinline__ uint32_t desc_a(uint32_t sb, int wg, int m, int kk) { return desc_lo(sb + wg * 8192 + kk * 32, 16); }
    static __device__ __forceinline__ uint32_t desc_b(uint32_t sb, int kk) { return desc_lo(sb + A_BYTES + (kk >> 1) * (B_BYTES / 2) + (kk & 1) * 2048, 4096); }
    static __device__ __forceinline__ void mma(float (&d)[96], uint32_t a, uint32_t b, int sc) { mma_qkv(d, a, b, sc); }
};

__device__ __forceinline__ void cp16(uint32_t dst, const void* src) { asm volatile("cp.async.cg.shared.global [%0], [%1], 16;" :: "r"(dst), "l"(src) : "memory"); }
__device__ __forceinline__ uint4 lds16(uint32_t a) { uint4 t; asm volatile("ld.shared.v4.u32 {%0, %1, %2, %3}, [%4];" : "=r"(t.x), "=r"(t.y), "=r"(t.z), "=r"(t.w) : "r"(a) : "memory"); return t; }
__device__ __forceinline__ void qkv_rows_load(const QkvParams& p, uint32_t reg, int row0, int w, int lane) {
    const uint4* xsrc = reinterpret_cast<const uint4*>(p.xp + (size_t)(row0 + w) * DM) + lane;
#pragma unroll 1
    for (int r = 0; w + 3 * r < 8; r++) {
#pragma unroll
        for (int i = 0; i < 4; i++) cp16(reg + r * 6144 + i * 512, xsrc + r * (3 * DM / 8) + i * 32);
    }
    asm volatile("cp.async.commit_group;" ::: "memory");
}
__device__ __forceinline__ void qkv_rows_gather(float2* sst, int row0, int t) {
    unsigned long long u[2];
    int it = 0;
    bool ok;
    do {
#pragma unroll
        for (int i = 0; i < 2; i++) asm volatile("ld.relaxed.gpu.global.u64 %0, [%1];" : "=l"(u[i]) : "l"(g_rowstat2 + row0 + min(t + 96 * i, 127)) : "memory");
        ok = (long long)(u[0] & u[1]) < 0;
        if (++it > (1 << 20)) __trap();
    } while (!ok);
#pragma unroll
    for (int i = 0; i < 2; i++)
        if (t + 96 * i < 128) sst[t + 96 * i] = make_float2(__uint_as_float((uint32_t)u[i]), __uint_as_float((uint32_t)(u[i] >> 32) & 0x7FFFFFFFu));
}
struct Moments {
    float sd0, sd1, sq0, sq1, x0;
    __device__ __forceinline__ void add(const uint4 x) {
        const float d0 = bf_lo(x.x) - x0, d1 = bf_hi(x.x) - x0, d2 = bf_lo(x.y) - x0, d3 = bf_hi(x.y) - x0;
        const float d4 = bf_lo(x.z) - x0, d5 = bf_hi(x.z) - x0, d6 = bf_lo(x.w) - x0, d7 = bf_hi(x.w) - x0;
        sd0 += (d0 + d1) + (d2 + d3); sd1 += (d4 + d5) + (d6 + d7);
        sq0 = fmaf(d0, d0, fmaf(d1, d1, fmaf(d2, d2, fmaf(d3, d3, sq0))));
        sq1 = fmaf(d4, d4, fmaf(d5, d5, fmaf(d6, d6, fmaf(d7, d7, sq1))));
    }
    template <int L> __device__ __forceinline__ unsigned long long finish() {
        float sd = sd0 + sd1, sq = sq0 + sq1;
#pragma unroll
        for (int o = 1; o < L; o <<= 1) { sd += __shfl_xor_sync(0xffffffffu, sd, o); sq += __shfl_xor_sync(0xffffffffu, sq, o); }
        const float md = sd * (1.f / DM);
        const float rstd = rsqrtf(fmaxf(fmaf(-md, md, sq * (1.f / DM)), 0.f) + 1e-5f);
        return ((unsigned long long)(__float_as_uint(rstd) | 0x80000000u) << 32) | __float_as_uint(x0 + md);
    }
};
template <class C>
__device__ __forceinline__ void qkv_aux(const QkvParams& p, uint8_t* smem_raw, const GemmSmem& s, int tm, int tn, int w, int lane) {
    AX(0);
    const uint32_t rel0 = mapa(s.aux + 16, lane & 1);
    const int chunk = lane & 7, sub = lane >> 3;
    const int wr = tm * 8 + sub;
    const uint32_t woff = C::A_BYTES + (wr >> 5) * (C::B_BYTES / 2) + w * 4096 + (wr & 31) * 128;
    const uint32_t woff0 = woff + ((chunk ^ (wr & 7)) << 4), woff1 = woff + 512 + ((chunk ^ ((wr + 4) & 7)) << 4);
    const int xr = tn * 8 + (w & 1) * 4 + sub;
    const uint32_t xoff = xr * 128 + ((chunk ^ (xr & 7)) << 4);
    const uint32_t xreg = s.base + C::STG_OFF + 49152 + w * 2048 + lane * 16;
    const uint8_t* pf = lane < 24 ? reinterpret_cast<const uint8_t*>(p.wp + (size_t)(tm * 8 + lane / 3) * (3 * DM) + (lane % 3) * DM + tn * 64)
                                  : reinterpret_cast<const uint8_t*>(p.xp + (size_t)(tm * 256 + tn * 8 + lane - 24) * DM);
    const uint32_t pf_step = lane < 24 ? 64 * 3 * DM * 2 : 128;
    float* scs = reinterpret_cast<float*>(smem_raw + C::AUX_OFF);
    float2* sst = reinterpret_cast<float2*>(smem_raw + C::AUX_OFF + 768);
    const int t = w * 32 + lane;
    float a[8];
#pragma unroll
    for (int i = 0; i < 8; i++) a[i] = 0.f;
    Moments m0 = {0.f, 0.f, 0.f, 0.f, 0.f};
#pragma unroll 1
    for (int k = 0; k < 16; k++) {
        const int st = k & 3;
        mbar_wait(s.full0 + 8 * st, (k >> 2) & 1);
        const uint32_t sb = s.base + st * C::STAGE_BYTES;
        const uint4 u = lds16(sb + woff0), v = lds16(sb + woff1);
        if (w < 2) {
            const uint4 x = lds16(sb + xoff);
            if (k == 0) m0.x0 = __shfl_sync(0xffffffffu, bf_lo(x.x), lane & 24);
            m0.add(x);
        } else if (QKV3_PF) {
            if (k == 0) for (int j = C::STAGES; j < QKV3_PF; j++) prefetch_line(pf + (size_t)j * pf_step);
            if (k + QKV3_PF < 16) prefetch_line(pf + (size_t)(k + QKV3_PF) * pf_step);
        }
        a[0] += bf_lo(u.x) + bf_lo(v.x); a[1] += bf_hi(u.x) + bf_hi(v.x); a[2] += bf_lo(u.y) + bf_lo(v.y); a[3] += bf_hi(u.y) + bf_hi(v.y);
        a[4] += bf_lo(u.z) + bf_lo(v.z); a[5] += bf_hi(u.z) + bf_hi(v.z); a[6] += bf_lo(u.w) + bf_lo(v.w); a[7] += bf_hi(u.w) + bf_hi(v.w);
        __syncwarp();
        if (lane < 2) mbar_arrive_cluster(rel0 + 8 * st);
        if (k == QKV3_R1) qkv_rows_load(p, xreg, tm * 256 + 128 + tn * 8, w, lane);
    }
    AX(1);
    if (w < 2) {
        const unsigned long long w0 = m0.finish<8>();
        if (chunk == 0) asm volatile("st.relaxed.gpu.global.u64 [%0], %1;" :: "l"(g_rowstat2 + tm * 256 + xr), "l"(w0) : "memory");
    }
#pragma unroll
    for (int i = 0; i < 8; i++) { a[i] += __shfl_xor_sync(0xffffffffu, a[i], 8); a[i] += __shfl_xor_sync(0xffffffffu, a[i], 16); }
    if (lane < 16) {
        const bool up = lane & 8;
        uint32_t* dst = g_colsum2 + tm * (3 * DM) + tn * 192 + w * 64 + (lane & 7) * 8 + (up ? 4 : 0);
        asm volatile("st.relaxed.gpu.global.v4.u32 [%0], {%1, %2, %3, %4};" :: "l"(dst), "r"(__float_as_uint(up ? a[4] : a[0]) | 1u), "r"(__float_as_uint(up ? a[5] : a[1]) | 1u),
                     "r"(__float_as_uint(up ? a[6] : a[2]) | 1u), "r"(__float_as_uint(up ? a[7] : a[3]) | 1u) : "memory");
    }
    AX(2);
    auto row1 = [&](int r) {
        Moments m = {0.f, 0.f, 0.f, 0.f, 0.f};
        const uint4 x = lds16(xreg + r * 6144);
        m.x0 = __shfl_sync(0xffffffffu, bf_lo(x.x), 0);
        m.add(x);
#pragma unroll
        for (int i = 1; i < 4; i++) m.add(lds16(xreg + r * 6144 + i * 512));
        const unsigned long long word = m.finish<32>();
        if (lane == 0) asm volatile("st.relaxed.gpu.global.u64 [%0], %1;" :: "l"(g_rowstat2 + tm * 256 + 128 + tn * 8 + w + 3 * r), "l"(word) : "memory");
    };
    {
        uint32_t ux[8], uy[8];
        unsigned long long r0, r1;
        int it = 0;
        bool ok;
        do {
            asm volatile("ld.relaxed.gpu.global.u64 %0, [%1];" : "=l"(r0) : "l"(g_rowstat2 + tm * 256 + t) : "memory");
            asm volatile("ld.relaxed.gpu.global.u64 %0, [%1];" : "=l"(r1) : "l"(g_rowstat2 + tm * 256 + 96 + (t & 31)) : "memory");
            uint32_t all = 1;
#pragma unroll
            for (int i = 0; i < 8; i++) {
                asm volatile("ld.relaxed.gpu.global.v2.u32 {%0, %1}, [%2];" : "=r"(ux[i]), "=r"(uy[i]) : "l"(g_colsum2 + i * (3 * DM) + tn * 192 + 2 * t) : "memory");
                all &= ux[i] & uy[i];
            }
            ok = (all & 1) && (long long)(r0 & r1) < 0;
            if (++it > (1 << 20)) __trap();
        } while (!ok);
        AX(3);
        sst[t] = make_float2(__uint_as_float((uint32_t)r0), __uint_as_float((uint32_t)(r0 >> 32) & 0x7FFFFFFFu));
        if (w == 0) sst[96 + t] = make_float2(__uint_as_float((uint32_t)r1), __uint_as_float((uint32_t)(r1 >> 32) & 0x7FFFFFFFu));
        float2 c = make_float2(0.f, 0.f);
#pragma unroll
        for (int i = 0; i < 8; i++) { c.x += __uint_as_float(ux[i]); c.y += __uint_as_float(uy[i]); }
        reinterpret_cast<float2*>(scs)[t] = c;
    }
    __syncwarp();
    if (lane == 0) mbar_arrive(s.aux);
    AX(4);
    asm volatile("cp.async.wait_group 0;" ::: "memory");
#pragma unroll 1
    for (int r = 0; w + 3 * r < 8; r++) row1(r);
    AX(5);
    qkv_rows_gather(sst + 128, tm * 256 + 128, t);
    __syncwarp();
    if (lane == 0) mbar_arrive(s.aux + 8);
    AX(6);
    AX(7);
}

__global__ void __launch_bounds__(384, 1) qkv_kernel(const __grid_constant__ QkvParams p) {
    using C = QkvCfg;
    extern __shared__ __align__(1024) uint8_t smem_raw[];
    TL(1, 4);
    pdl_launch();
    const int tm = blockIdx.x & 7, tn = blockIdx.x >> 3;
    if (threadIdx.x == 0) { prefetch_map(&p.x); prefetch_map(&p.w); prefetch_map(&p.out); }
    const GemmSmem s = gemm_setup<C>(smem_raw, [](const GemmSmem& g) { mbar_init(g.aux + 8, 3); for (int i = 0; i < C::STAGES; i++) mbar_init(g.aux + 16 + 8 * i, 6); mbar_init(g.aux + 48, 1); fence_barrier_init(); });
    const int wgi = __shfl_sync(0xffffffffu, threadIdx.x >> 7, 0);
    if (wgi == 0) {
        reg_dealloc<56>();
        if (threadIdx.x == 0) gemm_producer<C>(s, p, tm, tn);
        else if (threadIdx.x >= 32) {
            qkv_aux<C>(p, smem_raw, s, tm, tn, (threadIdx.x >> 5) - 1, threadIdx.x & 31);
            TK(14);
            if (threadIdx.x < 96) {
                const int wg = (threadIdx.x >> 5) - 1;
                const bool leader = (threadIdx.x & 31) == 0;
#pragma unroll 1
                for (int g = 0; g < 3; g++) {
                    take_over(2 + wg * 3 + g);
                    if (leader) {
#pragma unroll
                        for (int h = 0; h < 2; h++)
                            tma_st2(&p.out, s.base + C::STG_OFF + wg * 24576 + (g * 2 + h) * 4096, 0, g * (NH * SEQ) + (tn * 2 + h) * SEQ + tm * 256 + 128 + wg * 64);
                    }
                }
                if (leader) { tma_st_commit(); tma_st_wait(); }
                if (leader) TL(1, 3);
            }
        }
    } else {
        reg_alloc<224>();
        const int wg = wgi - 1, warp = (threadIdx.x >> 5) & 3, lane = threadIdx.x & 31;
        float acc0[1][96], acc1[96];
        TL(1, 0);
        gemm_mainloop<C, 16>(s, wg, acc0, 1);
        const uint32_t rel0 = mapa(s.empty0, lane & 1);
        auto step = [&](int st, uint32_t ph, bool first) {
            mbar_wait(s.full0 + 8 * st, ph);
            const uint32_t sb = s.base + st * C::STAGE_BYTES;
            wg_fence();
#pragma unroll
            for (int kk = 0; kk < 4; kk++) C::mma(acc1, C::desc_a(sb, wg, 0, kk), C::desc_b(sb, kk), !first || kk != 0);
            wg_commit();
        };
        auto release = [&](int st) { wg_wait<1>(); __syncwarp(); if (lane < 2) mbar_arrive_cluster(rel0 + 8 * st); };
        const float qscale = 0.17677669529663687f * 1.4426950408889634f;
        const float2* scs = reinterpret_cast<const float2*>(smem_raw + C::AUX_OFF);
        const float2* sst = reinterpret_cast<const float2*>(smem_raw + C::AUX_OFF + 768);
        const int arow = warp * 16 + ((lane >> 3) & 1) * 8 + (lane & 7);
        auto piece = [&](const float (&acc)[96], int half, int sub, float mean0, float mean1, float r0, float r1) {
            float v[16];
#pragma unroll
            for (int j = 0; j < 4; j++) {
                const float2 cs = scs[(sub * 4 + j) * 4 + (lane & 3)];
                v[4 * j] = fmaf(mean0, cs.x, acc[sub * 16 + 4 * j]) * r0;
                v[4 * j + 1] = fmaf(mean0, cs.y, acc[sub * 16 + 4 * j + 1]) * r0;
                v[4 * j + 2] = fmaf(mean1, cs.x, acc[sub * 16 + 4 * j + 2]) * r1;
                v[4 * j + 3] = fmaf(mean1, cs.y, acc[sub * 16 + 4 * j + 3]) * r1;
            }
#pragma unroll
            for (int jp = 0; jp < 2; jp++) {
                const int chunk = jp * 2 + (lane >> 4);
                const uint32_t addr = s.base + C::STG_OFF + wg * 24576 + sub * 4096 + arow * 64 + ((chunk ^ ((arow >> 1) & 3)) << 4);
                stmatrix_x4(addr, pack_bf16(v[8 * jp], v[8 * jp + 1]), pack_bf16(v[8 * jp + 2], v[8 * jp + 3]),
                            pack_bf16(v[8 * jp + 4], v[8 * jp + 5]), pack_bf16(v[8 * jp + 6], v[8 * jp + 7]));
            }
            if ((sub & 1) && half == 1) hand_over(2 + wg * 3 + (sub >> 1));
            float n0 = 0.f, n1 = 0.f;
#pragma unroll
            for (int j = 0; j < 4; j++) {
                n0 = fmaf(v[4 * j], v[4 * j], fmaf(v[4 * j + 1], v[4 * j + 1], n0));
                n1 = fmaf(v[4 * j + 2], v[4 * j + 2], fmaf(v[4 * j + 3], v[4 * j + 3], n1));
            }
            const bool odd = lane & 1;
            float full = (odd ? n1 : n0) + __shfl_xor_sync(0xffffffffu, odd ? n0 : n1, 1);
            full += __shfl_xor_sync(0xffffffffu, full, 2);
            const uint32_t mx = __reduce_max_sync(0xffffffffu, __float_as_uint(full));
            if (lane == 0) g_norm[((sub >> 1) * NH + tn * 2 + (sub & 1)) * 128 + tm * 16 + half * 8 + wg * 4 + warp] = mx;
        };
        fence_regs(acc1);
        constexpr int E0 = QKV2_E0;
        step(0, 0, true);
        release(3);
        fence_regs(acc0[0]);
#pragma unroll 1
        for (int j = 1; j <= E0; j++) { step(j & 3, (j >> 2) & 1, false); release((j - 1) & 3); }
        {
            mbar_wait(s.aux, 0);
            TKC(12);
            const float2 t0 = sst[wg * 64 + warp * 16 + (lane >> 2)], t1 = sst[wg * 64 + warp * 16 + 8 + (lane >> 2)];
#pragma unroll
            for (int sub = 0; sub < 6; sub++) {
                if (sub > 0) { step((E0 + sub) & 3, ((E0 + sub) >> 2) & 1, false); release((E0 + sub - 1) & 3); }
                const float qs = sub < 2 ? qscale : 1.f;
                piece(acc0[0], 0, sub, -t0.x, -t1.x, t0.y * qs, t1.y * qs);
            }
            TKC(13);
        }
#pragma unroll 1
        for (int k = 22 + E0; k < 32; k++) {
            if (QKV2_SKEW && k == 29 && wg == 1) named_bar(11, 256);
            step(k & 3, (k >> 2) & 1, false);
            if (QKV2_SKEW && k == (QKV2_SKEW == 2 ? 30 : 31) && wg == 0) named_arrive(11, 256);
            if (k <= C::KSTEPS - C::STAGES) release((k - 1) & 3); else wg_wait<1>();
        }
        mbar_wait(s.aux + 8, 0);
        const float2 t2 = sst[128 + wg * 64 + warp * 16 + (lane >> 2)], t3 = sst[128 + wg * 64 + warp * 16 + 8 + (lane >> 2)];
        wg_wait<0>();
        fence_regs(acc1);
        TL(1, 1);
        mbar_wait(s.aux + 48, 0);
#pragma unroll
        for (int sub = 0; sub < 6; sub++) {
            const float qs = sub < 2 ? qscale : 1.f;
            piece(acc1, 1, sub, -t2.x, -t3.x, t2.y * qs, t3.y * qs);
        }
        TL(1, 5);
    }
}

struct AttnParams { CUtensorMap kv, kv2; unsigned long long dbase; bf16* optr; const uint8_t* pf_wo; const uint8_t* pf_w1; const uint8_t* pf_b1;
                    const uint32_t* norm; void* colsum2; void* rowstat2; void* hpart; };
constexpr int AT_STAGES = 8, AT_STAGE_BYTES = 16384, AT_Q_OFF = AT_STAGES * AT_STAGE_BYTES, AT_ONES_OFF = AT_Q_OFF + 32768, AT_BAR_OFF = AT_ONES_OFF + 1024, AT_SMEM = AT_BAR_OFF + 256;
constexpr uint32_t AT_BASE = 1024;
constexpr int AT_TILES = 32;

__device__ __forceinline__ uint32_t fma_bf16x2(uint32_t a, uint32_t b, uint32_t c) { uint32_t d; asm("fma.rn.bf16x2 %0, %1, %2, %3;" : "=r"(d) : "r"(a), "r"(b), "r"(c)); return d; }
constexpr uint32_t FX_LEAD = 0x3EAB3EABu;
__device__ __forceinline__ uint32_t ex2_pair_fx(float x0, float x1, uint32_t c3, uint32_t one2) {
    const float m = 65663.f;
    const uint32_t w = __byte_perm(__float_as_uint(x0 + m), __float_as_uint(x1 + m), 0x5410);
    uint32_t g, r;
    asm("lop3.b32 %0, %1, 0x007F007F, %2, 0xEA;" : "=r"(g) : "r"(w), "r"(one2));
    uint32_t p = fma_bf16x2(g, c3, 0xBC5DBC5Du);
    p = fma_bf16x2(p, g, 0x3F2F3F2Fu);
    asm("lop3.b32 %0, %1, %2, 0xFF80FF80, 0xE4;" : "=r"(r) : "r"(w), "r"(p));
    return r;
}
template <uint32_t MASK> __device__ __forceinline__ uint32_t attn_exp2(float x0, float x1, int i, uint32_t c3) {
    return ((MASK >> i) & 1) ? ex2_pair_fx(x0, x1, c3, c3 ^ (FX_LEAD ^ 0x3F803F80u)) : pack_bf16(ex2(x0), ex2(x1));
}
__device__ __forceinline__ void attn_issue_tile(const AttnParams& p, uint32_t base, uint32_t full0, int g, int head) {
    const int st = g % AT_STAGES, key0 = (g & 15) * 128;
    const uint32_t bar = full0 + 8 * st, dst = base + st * AT_STAGE_BYTES;
    mbar_expect_tx(bar, AT_STAGE_BYTES);
    tma_ld3(dst, &p.kv2, bar, 0, head * SEQ + key0, 1);
}
__device__ __forceinline__ void attn_qk(float (&sacc)[32], uint32_t q_lo, uint32_t k_lo) {
    mma_qk0(sacc, q_lo, k_lo);
    mma_qk1(sacc, q_lo + 2, k_lo + 2, 1);
}
constexpr uint32_t PV_STEP = 64u - (64u << 16);
constexpr long long PV_STEP64 = 64ll - (64ll << 16);
__device__ __forceinline__ void attn_pv(float (&o)[20], const uint32_t (&pr)[16], uint32_t v_lo, int first) {
#pragma unroll
    for (int kk = 0; kk < 4; kk++)
        mma_pv(o, pr[4 * kk], pr[4 * kk + 1], pr[4 * kk + 2], pr[4 * kk + 3], v_lo + kk * PV_STEP, (kk > 0) || !first);
}
__device__ __forceinline__ void attn_store_o(const float (&o)[20], const AttnParams& p, int head, int row0, int lane) {
    const float r0 = 1.f / o[16], r1 = 1.f / o[18];
    uint32_t a[4], b[4];
#pragma unroll
    for (int j = 0; j < 4; j++) { a[j] = pack_bf16(o[4 * j] * r0, o[4 * j + 1] * r0); b[j] = pack_bf16(o[4 * j + 2] * r1, o[4 * j + 3] * r1); }
    const bool odd = lane & 1, up = lane & 2;
#pragma unroll
    for (int h = 0; h < 2; h++) {
        uint32_t t = __shfl_xor_sync(0xffffffffu, odd ? a[2 * h] : a[2 * h + 1], 1); if (odd) a[2 * h] = t; else a[2 * h + 1] = t;
        t = __shfl_xor_sync(0xffffffffu, odd ? b[2 * h] : b[2 * h + 1], 1); if (odd) b[2 * h] = t; else b[2 * h + 1] = t;
    }
#pragma unroll
    for (int h = 0; h < 2; h++) {
        uint32_t t = __shfl_xor_sync(0xffffffffu, up ? a[h] : a[h + 2], 2); if (up) a[h] = t; else a[h + 2] = t;
        t = __shfl_xor_sync(0xffffffffu, up ? b[h] : b[h + 2], 2); if (up) b[h] = t; else b[h + 2] = t;
    }
    uint4* op = reinterpret_cast<uint4*>(p.optr + (size_t)(row0 + (lane >> 2)) * PITCH + head * HD) + (lane & 3);
    op[0] = make_uint4(a[0], a[1], a[2], a[3]);
    op[8 * (PITCH / 8)] = make_uint4(b[0], b[1], b[2], b[3]);
}
__device__ __forceinline__ void attn_refill(const AttnParams& p, uint32_t base, uint32_t full0, uint32_t empty0, int g, int head) {
    if (threadIdx.x == 0 && g >= 4 && g + 4 < AT_TILES) {
        const int gp = g - 4;
        mbar_wait(empty0 + 8 * (gp % AT_STAGES), (gp / AT_STAGES) & 1);
        attn_issue_tile(p, base, full0, g + 4, head);
    }
    __syncwarp();
}

__device__ __forceinline__ void attn_housekeeping(const AttnParams& p) {
    const int l = threadIdx.x;
    if (l < 128 + 140) prefetch_line(l < 128 ? p.pf_wo + ((size_t)blockIdx.x * 128 + l) * 128 : p.pf_w1 + ((size_t)blockIdx.x * 140 + (l - 128)) * 128);
    if (blockIdx.x == 0 && l >= 300 && l < 300 + 56) prefetch_line(p.pf_b1 + (l - 300) * 128);
    if (l >= 384 && l < 384 + 48) reinterpret_cast<uint4*>(p.colsum2)[blockIdx.x * 48 + l - 384] = make_uint4(0, 0, 0, 0);
    if (l >= 432 && l < 432 + 8) reinterpret_cast<uint4*>(p.rowstat2)[blockIdx.x * 8 + l - 432] = make_uint4(0, 0, 0, 0);
    if (l >= 448) reinterpret_cast<uint4*>(p.hpart)[blockIdx.x * 64 + l - 448] = make_uint4(0, 0, 0, 0);
}
template <uint32_t MASK>
__device__ __forceinline__ void attn_piece(float (&o)[20], const float* sc, uint32_t c3, uint64_t dv) {
    uint32_t pr[8];
#pragma unroll
    for (int i = 0; i < 8; i++) pr[i] = attn_exp2<MASK>(sc[2 * i], sc[2 * i + 1], i, c3);
    wg_fence();
    mma_pvw(o, pr[0], pr[1], pr[2], pr[3], dv, 1);
    mma_pvw(o, pr[4], pr[5], pr[6], pr[7], dv + PV_STEP64, 1);
    wg_commit();
}
__device__ __forceinline__ void attn_fast(const AttnParams& p, uint32_t base, uint32_t full0, uint32_t empty0, int head, int qchunk) {
    const int wg = __shfl_sync(0xffffffffu, threadIdx.x >> 7, 0), warp = (threadIdx.x >> 5) & 3, lane = threadIdx.x & 31;
    const int warp_id = __shfl_sync(0xffffffffu, threadIdx.x >> 5, 0);
    const uint32_t k_lo0 = desc_lo(AT_BASE, 16), v_lo0 = desc_lo(AT_BASE + 8192, AT_ONES_OFF - 8192);
    const uint32_t q_lo0 = desc_lo(AT_BASE + AT_Q_OFF, 16) + wg * (64 * 64 >> 4);
    uint32_t c3;
    asm volatile("ld.shared.u32 %0, [%1];" : "=r"(c3) : "r"(base + AT_ONES_OFF));
    c3 ^= 0x3F803F80u ^ FX_LEAD;
    float sa[32], sb[32];
    const uint64_t HI = p.dbase;
    const uint64_t dk0 = HI + k_lo0, dv0 = HI + v_lo0;
    mbar_wait(full0, 0);
    wg_fence();
    mma_qk0w(sa, HI + q_lo0, dk0);
    mma_qk1w(sa, HI + q_lo0 + 2, dk0 + 2, 1);
    wg_commit();
    wg_wait<0>();
    fence_regs(sa);
#pragma unroll 1
    for (int pass = 0; pass < 2; pass++) {
    const uint32_t q = q_lo0 + pass * (256 * 64 >> 4);
    float o[20];
#pragma unroll
    for (int i = 0; i < 20; i++) o[i] = 0.f;
#pragma unroll 1
    for (int hh = 0; hh < 4; hh++) {
        const uint32_t par = hh >> 1, half = hh & 1;
        const int g0 = pass * 16 + hh * 4;
        const uint32_t fb = full0 + half * 32, eb = empty0 + half * 32, eo = empty0 + (half ^ 1) * 32;
        const uint64_t dq = HI + q, dqw = HI + (hh == 3 ? q_lo0 + (256 * 64 >> 4) : q);
        const uint64_t dkh = dk0 + half * (4 * AT_STAGE_BYTES >> 4), dkn = dk0 + (half ^ 1) * (4 * AT_STAGE_BYTES >> 4), dvh = dv0 + (long long)half * (64 * PV_STEP64);
#pragma unroll
        for (int j = 0; j < 4; j++) {
            if (warp_id == j * 5) {
                if (lane == 0 && g0 + 4 < AT_TILES) {
                    if (g0 >= 4) mbar_wait(eo + 8 * j, half ? par : (par ^ 1));
                    const uint32_t bar = full0 + (half ^ 1) * 32 + 8 * j;
                    mbar_expect_tx(bar, AT_STAGE_BYTES);
                    tma_ld3(base + ((half ^ 1) * 4 + j) * AT_STAGE_BYTES, &p.kv2, bar, 0, head * SEQ + ((g0 + 4 + j) & 15) * 128, 1);
                }
                __syncwarp();
            }
            wg_fence();
            const uint64_t kb = dkh + j * (AT_STAGE_BYTES >> 4), vb = dvh + j * 16 * PV_STEP64;
            mma_qk0w(sb, dq, kb + 256);
            mma_qk1w(sb, dq + 2, kb + 258, 1);
            wg_commit();
            wg_wait<2>();
            fence_regs(sa);
            attn_piece<QMASK_0>(o, sa, c3, vb);
            wg_wait<2>();
            if (lane == 0 && (j > 0 || g0 > 0)) mbar_arrive(j > 0 ? eb + 8 * (j - 1) : eo + 24);
            attn_piece<QMASK_1>(o, sa + 16, c3, vb + 2 * PV_STEP64);
            if (j < 3) mbar_wait(fb + 8 * (j + 1), par);
            else {
                if (g0 < 28) mbar_wait(full0 + (half ^ 1) * 32, half ? par ^ 1 : par);
                if (g0 == 12) mbar_wait(empty0 + 8 * AT_STAGES + 8, 0);
            }
            wg_fence();
            { const uint64_t qq = j < 3 ? dq : dqw, kn = j < 3 ? dkh + (j + 1) * (AT_STAGE_BYTES >> 4) : dkn;
              mma_qk0w(sa, qq, kn);
              mma_qk1w(sa, qq + 2, kn + 2, 1); }
            wg_commit();
            wg_wait<2>();
            fence_regs(sb);
            attn_piece<QMASK_2>(o, sb, c3, vb + 4 * PV_STEP64);
            wg_wait<2>();
            attn_piece<QMASK_3>(o, sb + 16, c3, vb + 6 * PV_STEP64);
        }
        wg_wait<0>();
        fence_regs(sa);
        fence_regs(o);
    }
    attn_store_o(o, p, head, qchunk * 512 + pass * 256 + wg * 64 + warp * 16, lane);
    if (pass == 0) attn_housekeeping(p);
    }
}

__device__ __forceinline__ void attn_safe(const AttnParams& p, uint32_t base, uint32_t full0, uint32_t empty0, int head, int qchunk) {
    const int wg = __shfl_sync(0xffffffffu, threadIdx.x >> 7, 0), warp = (threadIdx.x >> 5) & 3, lane = threadIdx.x & 31;
    const uint32_t k_lo0 = desc_lo(base, 16), v_lo0 = desc_lo(base + 8192, AT_ONES_OFF - 8192);
#pragma unroll 1
    for (int pass = 0; pass < 2; pass++) {
        const uint32_t q = desc_lo(base + AT_Q_OFF + (pass * 256 + wg * 64) * 64, 16);
        float o[20];
#pragma unroll
        for (int i = 0; i < 20; i++) o[i] = 0.f;
        float m0 = -INFINITY, m1 = -INFINITY;
#pragma unroll 1
        for (int t = 0; t < 32; t++) {
            const int g = pass * 16 + (t >> 1), half = t & 1;
            const int st = g % AT_STAGES;
            const uint32_t kb = k_lo0 + st * (AT_STAGE_BYTES >> 4), vb = v_lo0 + st * 16 * PV_STEP;
            if (half == 0) { attn_refill(p, base, full0, empty0, g, head); mbar_wait(full0 + 8 * st, (g / AT_STAGES) & 1); }
            float cur[32];
            wg_fence();
            attn_qk(cur, q, kb + half * 256);
            wg_commit();
            wg_wait<0>();
            fence_regs(cur);
            float x0 = cur[0], x1 = cur[2];
#pragma unroll
            for (int i = 0; i < 8; i++) { x0 = fmaxf(x0, fmaxf(cur[4 * i], cur[4 * i + 1])); x1 = fmaxf(x1, fmaxf(cur[4 * i + 2], cur[4 * i + 3])); }
            x0 = fmaxf(x0, __shfl_xor_sync(0xffffffffu, x0, 1)); x1 = fmaxf(x1, __shfl_xor_sync(0xffffffffu, x1, 1));
            x0 = fmaxf(x0, __shfl_xor_sync(0xffffffffu, x0, 2)); x1 = fmaxf(x1, __shfl_xor_sync(0xffffffffu, x1, 2));
            const float n0 = fmaxf(m0, x0), n1 = fmaxf(m1, x1);
            const float a0 = ex2(m0 - n0), a1 = ex2(m1 - n1);
            m0 = n0; m1 = n1;
            uint32_t pr[16];
#pragma unroll
            for (int i = 0; i < 8; i++) {
                pr[2 * i] = pack_bf16(ex2(cur[4 * i] - n0), ex2(cur[4 * i + 1] - n0));
                pr[2 * i + 1] = pack_bf16(ex2(cur[4 * i + 2] - n1), ex2(cur[4 * i + 3] - n1));
            }
#pragma unroll
            for (int i = 0; i < 5; i++) { o[4 * i] *= a0; o[4 * i + 1] *= a0; o[4 * i + 2] *= a1; o[4 * i + 3] *= a1; }
            wg_fence();
            attn_pv(o, pr, vb + half * 4 * PV_STEP, 0);
            wg_commit();
            wg_wait<0>();
            fence_regs(o);
            if (half == 1 && lane == 0) mbar_arrive(empty0 + 8 * st);
        }
        attn_store_o(o, p, head, qchunk * 512 + pass * 256 + wg * 64 + warp * 16, lane);
        if (pass == 0) attn_housekeeping(p);
    }
}

__global__ void __launch_bounds__(512, 1) attn_kernel(const __grid_constant__ AttnParams p) {
    extern __shared__ __align__(1024) uint8_t smem_raw[];
    TL(2, 4);
    pdl_launch();
    const uint32_t base = smem_u32(smem_raw);
    const uint32_t full0 = base + AT_BAR_OFF, empty0 = full0 + 8 * AT_STAGES;
    const int head = blockIdx.x >> 2, qchunk = blockIdx.x & 3;
    if (threadIdx.x == 0) {
        if (base & 1023) __trap();
        prefetch_map(&p.kv); prefetch_map(&p.kv2);
        for (int i = 0; i < AT_STAGES; i++) { mbar_init(full0 + 8 * i, 1); mbar_init(empty0 + 8 * i, 16); }
        mbar_init(empty0 + 8 * AT_STAGES, 1); mbar_init(empty0 + 8 * AT_STAGES + 8, 1);
        fence_barrier_init();
    }
    if (threadIdx.x < 256) reinterpret_cast<uint32_t*>(smem_raw + AT_ONES_OFF)[threadIdx.x] = 0x3F803F80u;
    fence_proxy_async();
    const uint4* nrm = reinterpret_cast<const uint4*>(p.norm) + head * 32 + (threadIdx.x & 31);
    __syncthreads();
    pdl_wait();
    TL(2, 0);
    uint4 nq, nk, nv;
    asm volatile("ld.global.cg.v4.u32 {%0, %1, %2, %3}, [%4];" : "=r"(nq.x), "=r"(nq.y), "=r"(nq.z), "=r"(nq.w) : "l"(nrm) : "memory");
    asm volatile("ld.global.cg.v4.u32 {%0, %1, %2, %3}, [%4];" : "=r"(nk.x), "=r"(nk.y), "=r"(nk.z), "=r"(nk.w) : "l"(nrm + NH * 32) : "memory");
    asm volatile("ld.global.cg.v4.u32 {%0, %1, %2, %3}, [%4];" : "=r"(nv.x), "=r"(nv.y), "=r"(nv.z), "=r"(nv.w) : "l"(nrm + 2 * NH * 32) : "memory");
    if (threadIdx.x == 0) {
        const uint32_t qbar = empty0 + 8 * AT_STAGES;
        mbar_expect_tx(qbar, 16384);
        for (int i = 0; i < 2; i++) tma_ld2(base + AT_Q_OFF + i * 8192, &p.kv, qbar, 0, head * SEQ + qchunk * 512 + i * 128);
    }
    if (threadIdx.x == 128) {
        for (int g = 0; g < 4; g++) attn_issue_tile(p, base, full0, g, head);
        const uint32_t qbar = empty0 + 8 * AT_STAGES + 8;
        mbar_expect_tx(qbar, 16384);
        for (int i = 2; i < 4; i++) tma_ld2(base + AT_Q_OFF + i * 8192, &p.kv, qbar, 0, head * SEQ + qchunk * 512 + i * 128);
    }
    __syncwarp();
    const float qn = __uint_as_float(__reduce_max_sync(0xffffffffu, max(max(nq.x, nq.y), max(nq.z, nq.w))));
    const float kn = __uint_as_float(__reduce_max_sync(0xffffffffu, max(max(nk.x, nk.y), max(nk.z, nk.w))));
    const float vn = __uint_as_float(__reduce_max_sync(0xffffffffu, max(max(nv.x, nv.y), max(nv.z, nv.w))));
    const bool bounded = (qn * kn <= 1.0e4f) && (vn <= 1.0e9f) && (base & 0xFFFFFFu) == AT_BASE;
    mbar_wait(empty0 + 8 * AT_STAGES, 0);
    if (bounded) attn_fast(p, base, full0, empty0, head, qchunk);
    else {
        if (threadIdx.x == 0) for (int g = 4; g < AT_STAGES; g++) attn_issue_tile(p, base, full0, g, head);
        mbar_wait(empty0 + 8 * AT_STAGES + 8, 0);
        attn_safe(p, base, full0, empty0, head, qchunk);
    }
    TL(2, 3);
}

struct ResParams { CUtensorMap a, b, res, out; const bf16* bias; };
template <bool MIX2>
struct ResCfg {
    static constexpr int MB = 1, BN = 128, KSTEPS = MIX2 ? 56 : 16, STAGES = 6, A_BYTES = 16384, B_BYTES = 16384;
    static constexpr int STAGE_BYTES = A_BYTES + B_BYTES, STG_OFF = STAGES * STAGE_BYTES, BAR_OFF = STG_OFF + 32768, SMEM = BAR_OFF + 128;
    static constexpr int AUX_COUNT = 1, PRE = MIX2 ? MIX2_PRE : WO_PRE;
    static constexpr int TLK = MIX2 ? 6 : 3;
    static constexpr bool MC = false, ACC_INIT = true;
    static constexpr int FOLLOW = 0;
    static __device__ __forceinline__ void after_release(const ResParams&, const GemmSmem&, int, int, int) {}
    static __device__ __forceinline__ void producer_done(const GemmSmem&) {}
    static __device__ __forceinline__ void load_w(const ResParams& p, uint32_t sb, uint32_t bar, int k, int tm, int tn) {
        if (MIX2) tma_ld3(sb, &p.a, bar, 0, k * 64, tm * 2);
        else tma_ld3(sb + A_BYTES, &p.b, bar, 0, k * 64, tn * 2);
    }
    static __device__ __forceinline__ void load_x(const ResParams& p, uint32_t sb, uint32_t bar, int k, int tm, int tn) {
        if (MIX2) tma_ld2(sb + A_BYTES, &p.b, bar, k * 64, tn * 128);
        else tma_ld2(sb, &p.a, bar, k * 64, tm * 128);
    }
    static __device__ __forceinline__ void load_aux(const ResParams& p, const GemmSmem& s, int tm, int tn) {
        mbar_expect_tx(s.aux, 32768);
        tma_ld2(s.base + STG_OFF, &p.res, s.aux, tn * 128, tm * 128);
        tma_ld2(s.base + STG_OFF + 16384, &p.res, s.aux, tn * 128 + 64, tm * 128);
    }
    static __device__ __forceinline__ uint32_t desc_a(uint32_t sb, int wg, int m, int kk) {
        return MIX2 ? desc_lo(sb + wg * 8192 + kk * 2048, 8192) : desc_lo(sb + wg * 8192 + kk * 32, 16);
    }
    static __device__ __forceinline__ uint32_t desc_b(uint32_t sb, int kk) {
        return MIX2 ? desc_lo(sb + A_BYTES + kk * 32, 16) : desc_lo(sb + A_BYTES + kk * 2048, 8192);
    }
    static __device__ __forceinline__ void mma(float (&d)[64], uint32_t a, uint32_t b, int sc) {
        if (MIX2) mma_mix2(d, a, b, sc); else mma_wo(d, a, b, sc);
    }
};
template <bool MIX2>
__global__ void __launch_bounds__(384, 1) res_gemm_kernel(const __grid_constant__ ResParams p) {
    using C = ResCfg<MIX2>;
    extern __shared__ __align__(1024) uint8_t smem_raw[];
    TL(MIX2 ? 6 : 3, 4);
    if (!MIX2) pdl_launch();
    const int tm = blockIdx.x >> 3, tn = blockIdx.x & 7;
    if (threadIdx.x == 0) { prefetch_map(&p.a); prefetch_map(&p.b); prefetch_map(&p.res); prefetch_map(&p.out); }
    const GemmSmem s = gemm_setup<C>(smem_raw);
    const int wgi = __shfl_sync(0xffffffffu, threadIdx.x >> 7, 0);
    if (wgi == 0) {
        reg_dealloc<40>();
        if (threadIdx.x < 32) {
            if (threadIdx.x == 0) gemm_producer<C>(s, p, tm, tn);
            __syncwarp();
#pragma unroll 1
            for (int i = 0; i < 4; i++) {
                constexpr bool SKEWED = (MIX2 ? MIX2_SKEW : WO_SKEW) > 0;
                const int b = SKEWED ? i & 1 : i >> 1, wg = SKEWED ? i >> 1 : i & 1;
                take_over(2 + b * 2 + wg);
                if (threadIdx.x == 0) tma_st2(&p.out, s.base + C::STG_OFF + b * 16384 + wg * 8192, tn * 128 + b * 64, tm * 128 + wg * 64);
            }
            if (threadIdx.x == 0) { tma_st_commit(); tma_st_wait(); TL(MIX2 ? 6 : 3, 3); }
        }
    } else {
        reg_alloc<232>();
        const int wg = wgi - 1, warp = (threadIdx.x >> 5) & 3, lane = threadIdx.x & 31;
        const int r0 = wg * 64 + warp * 16 + (lane >> 2);
        const int arow = wg * 64 + warp * 16 + ((lane >> 3) & 1) * 8 + (lane & 7);
        const uint32_t stg = s.base + C::STG_OFF + arow * 128;
        float acc[1][64];
        {
            float a0 = 1.f, a1 = 1.f, c0 = 0.f, c1 = 0.f;
            if (MIX2) {
                const float2 t0 = __ldcg(&g_rowln[tm * 128 + r0]), t1 = __ldcg(&g_rowln[tm * 128 + r0 + 8]);
                a0 = t0.y; a1 = t1.y;
                c0 = t0.x + __bfloat162float(p.bias[tm * 128 + r0]); c1 = t1.x + __bfloat162float(p.bias[tm * 128 + r0 + 8]);
            }
            mbar_wait(s.aux, 0);
#pragma unroll
            for (int jp = 0; jp < 8; jp++) {
                const int chunk = jp * 2 + (lane >> 4);
                uint32_t r[4];
                ldmatrix_x4(stg + (chunk >> 3) * 16384 + (((chunk & 7) ^ (arow & 7)) << 4), r);
#pragma unroll
                for (int i = 0; i < 4; i++) {
                    const float a = (i & 1) ? a1 : a0, c = (i & 1) ? c1 : c0;
                    acc[0][jp * 8 + 2 * i] = MIX2 ? fmaf(bf_lo(r[i]), a, c) : bf_lo(r[i]);
                    acc[0][jp * 8 + 2 * i + 1] = MIX2 ? fmaf(bf_hi(r[i]), a, c) : bf_hi(r[i]);
                }
            }
        }
        pdl_wait();
        TL(MIX2 ? 6 : 3, 0);
        constexpr int SK = MIX2 ? MIX2_SKEW : WO_SKEW;
        gemm_mainloop<C, C::KSTEPS, SK>(s, wg, acc, MIX2 ? 6 : 3);
        TL(MIX2 ? 6 : 3, 1);
        float sc0 = 1.f, sc1 = 1.f, of0 = 0.f, of1 = 0.f;
        if (!MIX2) {
            float s0 = 0.f, s1 = 0.f;
#pragma unroll
            for (int j = 0; j < 16; j++) { s0 += acc[0][4 * j] + acc[0][4 * j + 1]; s1 += acc[0][4 * j + 2] + acc[0][4 * j + 3]; }
            s0 += __shfl_xor_sync(0xffffffffu, s0, 1); s1 += __shfl_xor_sync(0xffffffffu, s1, 1);
            s0 += __shfl_xor_sync(0xffffffffu, s0, 2); s1 += __shfl_xor_sync(0xffffffffu, s1, 2);
            const float m0 = s0 * (1.f / 128), m1 = s1 * (1.f / 128);
            float q0 = 0.f, q1 = 0.f;
#pragma unroll
            for (int j = 0; j < 16; j++) {
                const float a = acc[0][4 * j] - m0, b = acc[0][4 * j + 1] - m0, c = acc[0][4 * j + 2] - m1, d = acc[0][4 * j + 3] - m1;
                q0 = fmaf(a, a, fmaf(b, b, q0)); q1 = fmaf(c, c, fmaf(d, d, q1));
            }
            q0 += __shfl_xor_sync(0xffffffffu, q0, 1); q1 += __shfl_xor_sync(0xffffffffu, q1, 1);
            q0 += __shfl_xor_sync(0xffffffffu, q0, 2); q1 += __shfl_xor_sync(0xffffffffu, q1, 2);
            const int wrow = tm * 128 + wg * 64 + warp * 16;
            if ((lane & 3) < 2) {
                const float m = (lane & 1) ? m1 : m0, q = (lane & 1) ? q1 : q0;
                const unsigned long long w = ((unsigned long long)(__float_as_uint(q) | 0x80000000u) << 32) | __float_as_uint(m);
                asm volatile("st.relaxed.gpu.global.u64 [%0], %1;" :: "l"(g_hpart + tn * SEQ + wrow + (lane >> 2) + (lane & 1) * 8), "l"(w) : "memory");
            }
            TL(3, 5);
            TKC(13);
            const unsigned long long* part = g_hpart + (lane >> 2) * SEQ + wrow + (lane & 3) * 4;
            unsigned long long t[4];
            int it = 0;
            bool ok;
            do {
                asm volatile("ld.relaxed.gpu.global.v2.u64 {%0, %1}, [%2];" : "=l"(t[0]), "=l"(t[1]) : "l"(part) : "memory");
                asm volatile("ld.relaxed.gpu.global.v2.u64 {%0, %1}, [%2];" : "=l"(t[2]), "=l"(t[3]) : "l"(part + 2) : "memory");
                ok = (long long)(t[0] & t[1] & t[2] & t[3]) < 0;
                if (++it > (1 << 20)) __trap();
            } while (!__all_sync(0xffffffffu, ok));
            TKC(14);
            float mt[4], qt[4];
#pragma unroll
            for (int i = 0; i < 4; i++) {
                const float mi = __uint_as_float((uint32_t)t[i]), qi = __uint_as_float((uint32_t)(t[i] >> 32) & 0x7FFFFFFFu);
                float m = mi;
                m += __shfl_xor_sync(0xffffffffu, m, 4); m += __shfl_xor_sync(0xffffffffu, m, 8); m += __shfl_xor_sync(0xffffffffu, m, 16);
                m *= 0.125f;
                float q = fmaf(128.f * (mi - m), mi - m, qi);
                q += __shfl_xor_sync(0xffffffffu, q, 4); q += __shfl_xor_sync(0xffffffffu, q, 8); q += __shfl_xor_sync(0xffffffffu, q, 16);
                mt[i] = m; qt[i] = q;
            }
            const int sel = (lane >> 2) & 3;
            const float mean = sel == 0 ? mt[0] : sel == 1 ? mt[1] : sel == 2 ? mt[2] : mt[3];
            const float var = (sel == 0 ? qt[0] : sel == 1 ? qt[1] : sel == 2 ? qt[2] : qt[3]) * (1.f / DM);
            const float r1 = rsqrtf(var + 1e-5f);
            const float r2 = rsqrtf(var * r1 * r1 + 1e-5f);
            const float scale = 0.5f * r1 * r2, off = -mean * scale;
            if (tn == 0 && lane < 16) g_rowln[wrow + 4 * (lane & 3) + sel] = make_float2(mean, 1.f / scale);
            const int ra = lane >> 2, src0 = ((ra & 3) << 2) | (ra >> 2);
            sc0 = __shfl_sync(0xffffffffu, scale, src0); of0 = __shfl_sync(0xffffffffu, off, src0);
            sc1 = __shfl_sync(0xffffffffu, scale, src0 + 2); of1 = __shfl_sync(0xffffffffu, off, src0 + 2);
        }
#pragma unroll
        for (int jp = 0; jp < 8; jp++) {
            const int chunk = jp * 2 + (lane >> 4);
            uint32_t r[4];
#pragma unroll
            for (int i = 0; i < 4; i++) {
                const float sc = (i & 1) ? sc1 : sc0, of = (i & 1) ? of1 : of0;
                const float v0 = acc[0][jp * 8 + 2 * i], v1 = acc[0][jp * 8 + 2 * i + 1];
                r[i] = MIX2 ? pack_bf16(v0, v1) : pack_bf16(fmaf(v0, sc, of), fmaf(v1, sc, of));
            }
            stmatrix_x4(stg + (chunk >> 3) * 16384 + (((chunk & 7) ^ (arow & 7)) << 4), r[0], r[1], r[2], r[3]);
            if ((jp & 3) == 3) hand_over(2 + (jp >> 2) * 2 + wg);
        }
        if (MIX2) TL(6, 5);
        TKC(15);
    }
}

struct Mix1Params { CUtensorMap hn, w1, out; const bf16* bias; const uint8_t* pf; };
struct Mix1Cfg {
    static constexpr int MB = 1, BN = 224, KSTEPS = 32, STAGES = 5, A_BYTES = 16384, B_BYTES = 28672;
    static constexpr int STAGE_BYTES = A_BYTES + B_BYTES, BAR_OFF = STAGES * STAGE_BYTES, SMEM = BAR_OFF + 128;
    static constexpr int AUX_COUNT = 1, PRE = MIX1_PRE;
    static constexpr int TLK = 5;
    static constexpr bool MC = true, ACC_INIT = true;
    static constexpr int FOLLOW = 0;
    static __device__ __forceinline__ void after_release(const Mix1Params&, const GemmSmem&, int, int, int) {}
    static __device__ __forceinline__ void producer_done(const GemmSmem&) {}
    static __device__ __forceinline__ void load_w(const Mix1Params& p, uint32_t sb, uint32_t bar, int k, int tm, int tn) {
        tma_ld3_mc(sb + A_BYTES + (tm & 1) * (B_BYTES / 2), &p.w1, bar, 0, k * 64 + (tm & 1) * 32, tn * 7);
    }
    static __device__ __forceinline__ void load_x(const Mix1Params& p, uint32_t sb, uint32_t bar, int k, int tm, int tn) { tma_ld3(sb, &p.hn, bar, 0, k * 64, tm * 2); }
    static __device__ __forceinline__ void load_aux(const Mix1Params&, const GemmSmem&, int, int) {}
    static __device__ __forceinline__ uint32_t desc_a(uint32_t sb, int wg, int m, int kk) { return desc_lo(sb + wg * 8192 + kk * 2048, 8192); }
    static __device__ __forceinline__ uint32_t desc_b(uint32_t sb, int kk) { return desc_lo(sb + A_BYTES + (kk >> 1) * (B_BYTES / 2) + (kk & 1) * 1024, 2048); }
    static __device__ __forceinline__ void mma(float (&d)[112], uint32_t a, uint32_t b, int sc) { mma_mix1(d, a, b, sc); }
    static __device__ __forceinline__ uint32_t stage_off(int wg) { return (2 + wg) * STAGE_BYTES; }
};
__global__ void __launch_bounds__(384, 1) mix1_kernel(const __grid_constant__ Mix1Params p) {
    using C = Mix1Cfg;
    extern __shared__ __align__(1024) uint8_t smem_raw[];
    TL(5, 4);
    const int tm = blockIdx.x & 7, tn = blockIdx.x >> 3;
    if (threadIdx.x == 0) { prefetch_map(&p.hn); prefetch_map(&p.w1); prefetch_map(&p.out); }
    const GemmSmem s = gemm_setup<C>(smem_raw);
    const int wgi = __shfl_sync(0xffffffffu, threadIdx.x >> 7, 0);
    if (wgi == 0) {
        reg_dealloc<40>();
        if (threadIdx.x < 32) {
            if (threadIdx.x == 0) gemm_producer<C>(s, p, tm, tn);
            __syncwarp();
#pragma unroll 1
            for (int i = 0; i < 8; i++) {
                const int wg = i >> 2, b = (i & 3) * 2;
                take_over(2 + i);
                if (threadIdx.x == 0) {
                    tma_st3(&p.out, s.base + C::stage_off(wg) + b * 4096, 0, tm * 128 + wg * 64, tn * 7 + b);
                    if (b < 6) tma_st3(&p.out, s.base + C::stage_off(wg) + (b + 1) * 4096, 0, tm * 128 + wg * 64, tn * 7 + b + 1);
                }
            }
            if (threadIdx.x == 0) { tma_st_commit(); tma_st_wait(); TL(5, 3); }
        } else if (threadIdx.x < 64) {
            pdl_wait();
            __nanosleep(PF_W2_DELAY);
#pragma unroll 1
            for (int i = 0; i < 4; i++) prefetch_line(p.pf + ((size_t)blockIdx.x * 128 + i * 32 + (threadIdx.x & 31)) * 128);
        }
    } else {
        reg_alloc<232>();
        const int wg = wgi - 1, warp = (threadIdx.x >> 5) & 3, lane = threadIdx.x & 31;
        float acc[1][112];
        {
            const uint32_t* bp = reinterpret_cast<const uint32_t*>(p.bias + tn * 224) + (lane & 3);
#pragma unroll
            for (int j = 0; j < 28; j++) {
                const uint32_t b2 = __ldg(bp + j * 4);
                acc[0][4 * j] = acc[0][4 * j + 2] = 0.5f * bf_lo(b2);
                acc[0][4 * j + 1] = acc[0][4 * j + 3] = 0.5f * bf_hi(b2);
            }
        }
        pdl_wait();
        pdl_launch();
        TL(5, 0);
        gemm_mainloop<C, 32, 4, true>(s, wg, acc, 5);
        TKW(2);
        TL(5, 1);
        if (wg == 0) { named_arrive(12, 256); named_bar(10, 256); }
        else named_bar(12, 256);
        const int arow = warp * 16 + ((lane >> 3) & 1) * 8 + (lane & 7);
        const uint32_t stg = s.base + C::stage_off(wg);
#pragma unroll
        for (int jp = 0; jp < 14; jp++) {
            float v[8];
#pragma unroll
            for (int i = 0; i < 8; i++) {
                const float hx = acc[0][jp * 8 + i];
                v[i] = fmaf(hx, tanh_fast(hx * fmaf(hx * hx, 8.f * 0.0356774081363f, 2.f * 0.7978845608029f)), hx);
            }
            const int j = jp * 2 + (lane >> 4);
            const uint32_t addr = stg + (j >> 2) * 4096 + arow * 64 + (((j & 3) ^ ((arow >> 1) & 3)) << 4);
            stmatrix_x4(addr, pack_bf16(v[0], v[1]), pack_bf16(v[2], v[3]), pack_bf16(v[4], v[5]), pack_bf16(v[6], v[7]));
            if ((jp & 3) == 3 || jp == 13) hand_over(2 + wg * 4 + (jp >> 2));
        }
        TKW(3);
        TL(5, 5);
    }
}

typedef CUresult (*EncodeFn)(CUtensorMap*, CUtensorMapDataType, cuuint32_t, void*, const cuuint64_t*, const cuuint64_t*, const cuuint32_t*,
                             const cuuint32_t*, CUtensorMapInterleave, CUtensorMapSwizzle, CUtensorMapL2promotion, CUtensorMapFloatOOBfill);
EncodeFn g_encode;

void make_map(CUtensorMap* m, const void* ptr, int rank, const uint64_t* dims, const uint64_t* strides_bytes, const uint32_t* box, CUtensorMapSwizzle swz) {
    cuuint64_t d[5], st[5]; cuuint32_t b[5], es[5];
    for (int i = 0; i < rank; i++) { d[i] = dims[i]; b[i] = box[i]; es[i] = 1; }
    for (int i = 0; i + 1 < rank; i++) st[i] = strides_bytes[i];
    CUresult r = g_encode(m, CU_TENSOR_MAP_DATA_TYPE_BFLOAT16, rank, const_cast<void*>(ptr), d, st, b, es, CU_TENSOR_MAP_INTERLEAVE_NONE, swz,
                          CU_TENSOR_MAP_L2_PROMOTION_L2_128B, CU_TENSOR_MAP_FLOAT_OOB_FILL_NONE);
    if (r != CUDA_SUCCESS) fprintf(stderr, "cuTensorMapEncodeTiled failed: %d\n", (int)r);
}
void map2d(CUtensorMap* m, const void* ptr, uint64_t cols, uint64_t rows, uint32_t bc, uint32_t br, CUtensorMapSwizzle swz, uint64_t pitch = 0) {
    uint64_t dims[2] = {cols, rows}, st[1] = {(pitch ? pitch : cols) * 2}; uint32_t box[2] = {bc, br};
    make_map(m, ptr, 2, dims, st, box, swz);
}
void map3d(CUtensorMap* m, const void* ptr, uint64_t cols, uint64_t rows, uint32_t inner, uint32_t br, uint32_t nblk, CUtensorMapSwizzle swz, uint64_t pitch = 0) {
    uint64_t dims[3] = {inner, rows, cols / inner}, st[2] = {(pitch ? pitch : cols) * 2, (uint64_t)inner * 2}; uint32_t box[3] = {inner, br, nblk};
    make_map(m, ptr, 3, dims, st, box, swz);
}

template <class... KArgs, class... Args>
void launch(void (*kern)(KArgs...), int grid, int block, int smem, bool pdl, bool pair, Args&&... args) {
    cudaLaunchConfig_t cfg = {};
    cfg.gridDim = dim3(grid); cfg.blockDim = dim3(block); cfg.dynamicSmemBytes = smem; cfg.stream = 0;
    cudaLaunchAttribute at[2];
    int n = 0;
    if (pdl) { at[n].id = cudaLaunchAttributeProgrammaticStreamSerialization; at[n].val.programmaticStreamSerializationAllowed = 1; n++; }
    if (pair) { at[n].id = cudaLaunchAttributeClusterDimension; at[n].val.clusterDim.x = 2; at[n].val.clusterDim.y = 1; at[n].val.clusterDim.z = 1; n++; }
    cfg.attrs = at; cfg.numAttrs = n;
    cudaError_t e = cudaLaunchKernelEx(&cfg, kern, KArgs(args)...);
    if (e != cudaSuccess) fprintf(stderr, "launch failed: %s\n", cudaGetErrorString(e));
}

struct HostState {
    bool ready;
    const void* key[9];
    QkvParams qkv; AttnParams attn; ResParams wo, mix2; Mix1Params mix1;
    bf16 *qkvp, *o, *hn, *u;
};
HostState g_hs;

}

extern "C" void kernel_launch(void* const* d_in, const int* in_sizes, int n_in, void* d_out, int out_size) {
    const bf16* x = (const bf16*)d_in[0];
    const bf16* wqkv = (const bf16*)d_in[1];
    const bf16* wo = (const bf16*)d_in[2];
    const bf16* w1 = (const bf16*)d_in[4];
    const bf16* b1 = (const bf16*)d_in[5];
    const bf16* w2 = (const bf16*)d_in[6];
    const bf16* b2 = (const bf16*)d_in[7];
    HostState& hs = g_hs;
    bool same = hs.ready;
    for (int i = 0; i < 8 && same; i++) same = (hs.key[i] == d_in[i]);
    same = same && hs.key[8] == d_out;
    if (!same) {
        if (!g_encode) {
            void* fn = nullptr; cudaDriverEntryPointQueryResult qr;
            cudaGetDriverEntryPoint("cuTensorMapEncodeTiled", &fn, cudaEnableDefault, &qr);
            g_encode = (EncodeFn)fn;
            cudaFuncSetAttribute(qkv_kernel, cudaFuncAttributeMaxDynamicSharedMemorySize, QkvCfg::SMEM);
            cudaFuncSetAttribute(attn_kernel, cudaFuncAttributeMaxDynamicSharedMemorySize, AT_SMEM);
            cudaFuncSetAttribute(res_gemm_kernel<false>, cudaFuncAttributeMaxDynamicSharedMemorySize, ResCfg<false>::SMEM);
            cudaFuncSetAttribute(res_gemm_kernel<true>, cudaFuncAttributeMaxDynamicSharedMemorySize, ResCfg<true>::SMEM);
            cudaFuncSetAttribute(mix1_kernel, cudaFuncAttributeMaxDynamicSharedMemorySize, Mix1Cfg::SMEM);
        }
        cudaGetSymbolAddress((void**)&hs.qkvp, g_qkv); cudaGetSymbolAddress((void**)&hs.o, g_o);
        cudaGetSymbolAddress((void**)&hs.hn, g_hn); cudaGetSymbolAddress((void**)&hs.u, g_u);
        const CUtensorMapSwizzle S128 = CU_TENSOR_MAP_SWIZZLE_128B, S64 = CU_TENSOR_MAP_SWIZZLE_64B;
        map2d(&hs.qkv.x, x, DM, SEQ, 64, 128, S128);
        hs.qkv.xp = x; hs.qkv.wp = wqkv;
        {
            uint64_t dims[4] = {64, (uint64_t)DM, 3, 16}, st[3] = {3 * DM * 2, DM * 2, 128}; uint32_t box[4] = {64, 32, 3, 1};
            make_map(&hs.qkv.w, wqkv, 4, dims, st, box, S128);
        }
        map2d(&hs.qkv.out, hs.qkvp, HD, 3 * NH * SEQ, 32, 64, S64);
        map2d(&hs.attn.kv, hs.qkvp, HD, 3 * NH * SEQ, 32, 128, S64);
        hs.attn.optr = hs.o;
        {
            uint64_t dims[3] = {(uint64_t)HD, (uint64_t)NH * SEQ, 3}, st[2] = {HD * 2, (uint64_t)NH * SEQ * HD * 2}; uint32_t box[3] = {32, 128, 2};
            make_map(&hs.attn.kv2, hs.qkvp, 3, dims, st, box, S64);
        }
        map2d(&hs.wo.a, hs.o, DM, SEQ, 64, 128, S128, PITCH);
        map3d(&hs.wo.b, wo, DM, DM, 64, 64, 2, S128);
        map2d(&hs.wo.res, x, DM, SEQ, 64, 128, S128);
        map2d(&hs.wo.out, hs.hn, DM, SEQ, 64, 64, S128, PITCH);
        hs.wo.bias = nullptr;
        map3d(&hs.mix1.hn, hs.hn, DM, SEQ, 64, 64, 2, S128, PITCH);
        map3d(&hs.mix1.w1, w1, FF, SEQ, 32, 32, 7, S64);
        hs.mix1.pf = (const uint8_t*)w2;
        hs.attn.dbase = 0x8000002000000000ull;
        cudaGetSymbolAddress((void**)&hs.attn.norm, g_norm); cudaGetSymbolAddress(&hs.attn.colsum2, g_colsum2); cudaGetSymbolAddress(&hs.attn.rowstat2, g_rowstat2);
        cudaGetSymbolAddress(&hs.attn.hpart, g_hpart);
        hs.attn.pf_wo = (const uint8_t*)wo; hs.attn.pf_w1 = (const uint8_t*)w1; hs.attn.pf_b1 = (const uint8_t*)b1;
        map3d(&hs.mix1.out, hs.u, FF, DM, 32, 64, 1, S64);
        hs.mix1.bias = b1;
        map3d(&hs.mix2.a, w2, SEQ, FF, 64, 64, 2, S128);
        map2d(&hs.mix2.b, hs.u, FF, DM, 64, 128, S128);
        map2d(&hs.mix2.res, hs.hn, DM, SEQ, 64, 128, S128, PITCH);
        map2d(&hs.mix2.out, d_out, DM, SEQ, 64, 64, S128);
        hs.mix2.bias = b2;
        for (int i = 0; i < 8; i++) hs.key[i] = d_in[i];
        hs.key[8] = d_out;
        hs.ready = true;
    }
    launch(qkv_kernel, 128, 384, QkvCfg::SMEM, false, true, hs.qkv);
    launch(attn_kernel, 128, 512, AT_SMEM, true, false, hs.attn);
    launch(res_gemm_kernel<false>, 128, 384, ResCfg<false>::SMEM, true, true, hs.wo);
    launch(mix1_kernel, 128, 384, Mix1Cfg::SMEM, true, true, hs.mix1);
    launch(res_gemm_kernel<true>, 128, 384, ResCfg<true>::SMEM, true, true, hs.mix2);
}
```

```cpp
#include <cuda_runtime.h>
#include <cuda_bf16.h>
#include <cuda.h>
#include <stdint.h>
#include <stdio.h>

typedef __nv_bfloat16 bf16;

namespace {

#define MIX1_PRE 1
#define WO_PRE 1
#define MIX2_PRE 1
#define PF_W2_DELAY 10000
#define QMASK_0 0xF0
#define QMASK_1 0xF0
#define QMASK_2 0xF0
#define QMASK_3 0xF0
#define MIX1_SKEW 4
#define MIX1_PAT 1
#define MIX1_PIN 1
#define MIX1_TK 0
#define QKV3_R1 10
#define QKV2_E0 5
#define QKV_FIRST 1
#define QKV3_PF 7
#define MIX2_SKEW 4
#define WO_SKEW 4
#define QKV2_SKEW 1
#define PITCH_PAD 64
constexpr int PITCH = 1024 + PITCH_PAD;
constexpr int SEQ = 2048, DM = 1024, NH = 32, HD = 32, FF = 3584;

__device__ __align__(1024) bf16 g_qkv[3 * NH * SEQ * HD];
__device__ __align__(1024) bf16 g_o[SEQ * PITCH];
__device__ __align__(1024) bf16 g_hn[SEQ * PITCH];
__device__ __align__(1024) bf16 g_u[DM * FF];
__device__ __align__(16) uint32_t g_norm[3 * NH * 128];
__device__ float2 g_rowln[SEQ];
__device__ __align__(16) unsigned long long g_hpart[SEQ * 8];
__device__ __align__(16) unsigned long long g_rowstat2[SEQ];
__device__ __align__(16) uint32_t g_colsum2[8 * 3 * DM];

#define TL(kern, slot)
#define AX(slot)

__device__ __forceinline__ uint32_t smem_u32(const void* p) { return (uint32_t)__cvta_generic_to_shared(p); }
__device__ __forceinline__ void mbar_init(uint32_t bar, uint32_t cnt) { asm volatile("mbarrier.init.shared::cta.b64 [%0], %1;" :: "r"(bar), "r"(cnt) : "memory"); }
__device__ __forceinline__ void mbar_expect_tx(uint32_t bar, uint32_t bytes) { asm volatile("mbarrier.arrive.expect_tx.shared::cta.b64 _, [%0], %1;" :: "r"(bar), "r"(bytes) : "memory"); }
__device__ __forceinline__ void mbar_arrive(uint32_t bar) { asm volatile("mbarrier.arrive.shared::cta.b64 _, [%0];" :: "r"(bar) : "memory"); }
__device__ __forceinline__ void mbar_wait(uint32_t bar, uint32_t parity) {
    asm volatile("{\n.reg .pred p;\nWAIT_%=:\nmbarrier.try_wait.parity.shared::cta.b64 p, [%0], %1;\n@p bra DONE_%=;\nbra WAIT_%=;\nDONE_%=:\n}" :: "r"(bar), "r"(parity) : "memory");
}
__device__ __forceinline__ void fence_barrier_init() { asm volatile("fence.mbarrier_init.release.cluster;" ::: "memory"); }
__device__ __forceinline__ void fence_proxy_async() { asm volatile("fence.proxy.async.shared::cta;" ::: "memory"); }
__device__ __forceinline__ void pdl_launch() { asm volatile("griddepcontrol.launch_dependents;" ::: "memory"); }
__device__ __forceinline__ void pdl_wait() { asm volatile("griddepcontrol.wait;" ::: "memory"); }
__device__ __forceinline__ void named_bar(int id, int n) { asm volatile("bar.sync %0, %1;" :: "r"(id), "r"(n) : "memory"); }
__device__ __forceinline__ void named_arrive(int id, int n) { asm volatile("bar.arrive %0, %1;" :: "r"(id), "r"(n) : "memory"); }
__device__ __forceinline__ void hand_over(int id) { named_arrive(id, 160); }
__device__ __forceinline__ void take_over(int id) { named_bar(id, 160); fence_proxy_async(); }
__device__ __forceinline__ void prefetch_map(const CUtensorMap* m) { asm volatile("prefetch.tensormap [%0];" :: "l"(m) : "memory"); }

__device__ __forceinline__ void tma_ld2(uint32_t dst, const CUtensorMap* m, uint32_t bar, int c0, int c1) {
    asm volatile("cp.async.bulk.tensor.2d.shared::cluster.global.mbarrier::complete_tx::bytes [%0], [%1, {%3, %4}], [%2];"
                 :: "r"(dst), "l"(m), "r"(bar), "r"(c0), "r"(c1) : "memory");
}
__device__ __forceinline__ void tma_ld3(uint32_t dst, const CUtensorMap* m, uint32_t bar, int c0, int c1, int c2) {
    asm volatile("cp.async.bulk.tensor.3d.shared::cluster.global.mbarrier::complete_tx::bytes [%0], [%1, {%3, %4, %5}], [%2];"
                 :: "r"(dst), "l"(m), "r"(bar), "r"(c0), "r"(c1), "r"(c2) : "memory");
}
__device__ __forceinline__ void tma_ld3_mc(uint32_t dst, const CUtensorMap* m, uint32_t bar, int c0, int c1, int c2) {
    asm volatile("cp.async.bulk.tensor.3d.shared::cluster.global.mbarrier::complete_tx::bytes.multicast::cluster [%0], [%1, {%3, %4, %5}], [%2], %6;"
                 :: "r"(dst), "l"(m), "r"(bar), "r"(c0), "r"(c1), "r"(c2), "h"((uint16_t)3) : "memory");
}
__device__ __forceinline__ void tma_ld4_mc(uint32_t dst, const CUtensorMap* m, uint32_t bar, int c0, int c1, int c2, int c3) {
    asm volatile("cp.async.bulk.tensor.4d.shared::cluster.global.mbarrier::complete_tx::bytes.multicast::cluster [%0], [%1, {%3, %4, %5, %6}], [%2], %7;"
                 :: "r"(dst), "l"(m), "r"(bar), "r"(c0), "r"(c1), "r"(c2), "r"(c3), "h"((uint16_t)3) : "memory");
}
__device__ __forceinline__ void prefetch_line(const void* p) { asm volatile("prefetch.global.L2 [%0];" :: "l"(p)); }
__device__ __forceinline__ uint32_t mapa(uint32_t addr, uint32_t cta) { uint32_t r; asm("mapa.shared::cluster.u32 %0, %1, %2;" : "=r"(r) : "r"(addr), "r"(cta)); return r; }
__device__ __forceinline__ void mbar_arrive_cluster(uint32_t bar) { asm volatile("mbarrier.arrive.shared::cluster.b64 _, [%0];" :: "r"(bar) : "memory"); }
__device__ __forceinline__ void cluster_arrive() { asm volatile("barrier.cluster.arrive.relaxed.aligned;" ::: "memory"); }
__device__ __forceinline__ void cluster_wait() { asm volatile("barrier.cluster.wait.aligned;" ::: "memory"); }
__device__ __forceinline__ void tma_st2(const CUtensorMap* m, uint32_t src, int c0, int c1) {
    asm volatile("cp.async.bulk.tensor.2d.global.shared::cta.bulk_group [%0, {%2, %3}], [%1];" :: "l"(m), "r"(src), "r"(c0), "r"(c1) : "memory");
}
__device__ __forceinline__ void tma_st3(const CUtensorMap* m, uint32_t src, int c0, int c1, int c2) {
    asm volatile("cp.async.bulk.tensor.3d.global.shared::cta.bulk_group [%0, {%2, %3, %4}], [%1];" :: "l"(m), "r"(src), "r"(c0), "r"(c1), "r"(c2) : "memory");
}
__device__ __forceinline__ void tma_st_commit() { asm volatile("cp.async.bulk.commit_group;" ::: "memory"); }
__device__ __forceinline__ void tma_st_wait() { asm volatile("cp.async.bulk.wait_group.read 0;" ::: "memory"); }

__device__ __forceinline__ void wg_fence() { asm volatile("wgmma.fence.sync.aligned;" ::: "memory"); }
__device__ __forceinline__ void wg_commit() { asm volatile("wgmma.commit_group.sync.aligned;" ::: "memory"); }
template <int N> __device__ __forceinline__ void wg_wait() { asm volatile("wgmma.wait_group.sync.aligned %0;" :: "n"(N) : "memory"); }
template <int R> __device__ __forceinline__ void reg_alloc() { asm volatile("setmaxnreg.inc.sync.aligned.u32 %0;" :: "n"(R)); }
template <int R> __device__ __forceinline__ void reg_dealloc() { asm volatile("setmaxnreg.dec.sync.aligned.u32 %0;" :: "n"(R)); }
__device__ __forceinline__ float lds_f32(uint32_t a) { float v; asm volatile("ld.volatile.shared.f32 %0, [%1];" : "=f"(v) : "r"(a) : "memory"); return v; }
template <int N> __device__ __forceinline__ void fence_regs(float (&d)[N]) {
#pragma unroll
    for (int i = 0; i < N; i++) asm volatile("" : "+f"(d[i]) :: "memory");
}

__device__ __forceinline__ uint32_t desc_lo(uint32_t addr, uint32_t lbo) { return ((addr & 0x3FFFFu) >> 4) | ((lbo >> 4) << 16); }
__device__ __forceinline__ uint32_t pack_bf16(float lo, float hi) { uint32_t d; asm("cvt.rn.bf16x2.f32 %0, %1, %2;" : "=r"(d) : "f"(hi), "f"(lo)); return d; }
__device__ __forceinline__ float bf_lo(uint32_t v) { return __uint_as_float(v << 16); }
__device__ __forceinline__ float bf_hi(uint32_t v) { return __uint_as_float(v & 0xFFFF0000u); }
__device__ __forceinline__ void stmatrix_x4(uint32_t addr, uint32_t r0, uint32_t r1, uint32_t r2, uint32_t r3) {
    asm volatile("stmatrix.sync.aligned.m8n8.x4.shared.b16 [%0], {%1, %2, %3, %4};" :: "r"(addr), "r"(r0), "r"(r1), "r"(r2), "r"(r3));
}
__device__ __forceinline__ void ldmatrix_x4(uint32_t addr, uint32_t (&r)[4]) {
    asm volatile("ldmatrix.sync.aligned.m8n8.x4.shared.b16 {%0, %1, %2, %3}, [%4];" : "=r"(r[0]), "=r"(r[1]), "=r"(r[2]), "=r"(r[3]) : "r"(addr) : "memory");
}
__device__ __forceinline__ float ex2(float x) { float y; asm("ex2.approx.ftz.f32 %0, %1;" : "=f"(y) : "f"(x)); return y; }
__device__ __forceinline__ float tanh_fast(float x) { float y; asm("tanh.approx.f32 %0, %1;" : "=f"(y) : "f"(x)); return y; }

__device__ __forceinline__ void mma_qkv(float (&d)[96], uint32_t alo, uint32_t blo, int scale_d) {
    asm volatile("{\n.reg .pred p;\n.reg .b64 da, db;\nsetp.ne.b32 p, %98, 0;\nmov.b64 da, {%96, 0x40000040};\nmov.b64 db, {%97, 0x40000040};\n"
        "wgmma.mma_async.sync.aligned.m64n192k16.f32.bf16.bf16 {"
        "%0, %1, %2, %3, %4, %5, %6, %7, %8, %9, %10, %11, %12, %13, %14, %15, %16, %17, %18, %19, %20, %21, %22, %23, %24, %25, %26, %27, %28, %29, %30, %31,  "
        "%32, %33, %34, %35, %36, %37, %38, %39, %40, %41, %42, %43, %44, %45, %46, %47, %48, %49, %50, %51, %52, %53, %54, %55, %56, %57, %58, %59, %60, %61,  "
        "%62, %63, %64, %65, %66, %67, %68, %69, %70, %71, %72, %73, %74, %75, %76, %77, %78, %79, %80, %81, %82, %83, %84, %85, %86, %87, %88, %89, %90, %91,  "
        "%92, %93, %94, %95 "
        "}, da, db, p, 1, 1, 0, 1;\n}\n"
        : "+f"(d[0]), "+f"(d[1]), "+f"(d[2]), "+f"(d[3]), "+f"(d[4]), "+f"(d[5]), "+f"(d[6]), "+f"(d[7]), "+f"(d[8]), "+f"(d[9]), "+f"(d[10]), "+f"(d[11]),
          "+f"(d[12]), "+f"(d[13]), "+f"(d[14]), "+f"(d[15]), "+f"(d[16]), "+f"(d[17]), "+f"(d[18]), "+f"(d[19]), "+f"(d[20]), "+f"(d[21]), "+f"(d[22]),
          "+f"(d[23]), "+f"(d[24]), "+f"(d[25]), "+f"(d[26]), "+f"(d[27]), "+f"(d[28]), "+f"(d[29]), "+f"(d[30]), "+f"(d[31]), "+f"(d[32]), "+f"(d[33]),
          "+f"(d[34]), "+f"(d[35]), "+f"(d[36]), "+f"(d[37]), "+f"(d[38]), "+f"(d[39]), "+f"(d[40]), "+f"(d[41]), "+f"(d[42]), "+f"(d[43]), "+f"(d[44]),
          "+f"(d[45]), "+f"(d[46]), "+f"(d[47]), "+f"(d[48]), "+f"(d[49]), "+f"(d[50]), "+f"(d[51]), "+f"(d[52]), "+f"(d[53]), "+f"(d[54]), "+f"(d[55]),
          "+f"(d[56]), "+f"(d[57]), "+f"(d[58]), "+f"(d[59]), "+f"(d[60]), "+f"(d[61]), "+f"(d[62]), "+f"(d[63]), "+f"(d[64]), "+f"(d[65]), "+f"(d[66]),
          "+f"(d[67]), "+f"(d[68]), "+f"(d[69]), "+f"(d[70]), "+f"(d[71]), "+f"(d[72]), "+f"(d[73]), "+f"(d[74]), "+f"(d[75]), "+f"(d[76]), "+f"(d[77]),
          "+f"(d[78]), "+f"(d[79]), "+f"(d[80]), "+f"(d[81]), "+f"(d[82]), "+f"(d[83]), "+f"(d[84]), "+f"(d[85]), "+f"(d[86]), "+f"(d[87]), "+f"(d[88]),
          "+f"(d[89]), "+f"(d[90]), "+f"(d[91]), "+f"(d[92]), "+f"(d[93]), "+f"(d[94]), "+f"(d[95])
        : "r"(alo), "r"(blo), "r"(scale_d));
}
__device__ __forceinline__ void mma_wo(float (&d)[64], uint32_t alo, uint32_t blo, int scale_d) {
    asm volatile("{\n.reg .pred p;\n.reg .b64 da, db;\nsetp.ne.b32 p, %66, 0;\nmov.b64 da, {%64, 0x40000040};\nmov.b64 db, {%65, 0x40000040};\n"
        "wgmma.mma_async.sync.aligned.m64n128k16.f32.bf16.bf16 {"
        "%0, %1, %2, %3, %4, %5, %6, %7, %8, %9, %10, %11, %12, %13, %14, %15, %16, %17, %18, %19, %20, %21, %22, %23, %24, %25, %26, %27, %28, %29, %30, %31,  "
        "%32, %33, %34, %35, %36, %37, %38, %39, %40, %41, %42, %43, %44, %45, %46, %47, %48, %49, %50, %51, %52, %53, %54, %55, %56, %57, %58, %59, %60, %61,  "
        "%62, %63 "
        "}, da, db, p, 1, 1, 0, 1;\n}\n"
        : "+f"(d[0]), "+f"(d[1]), "+f"(d[2]), "+f"(d[3]), "+f"(d[4]), "+f"(d[5]), "+f"(d[6]), "+f"(d[7]), "+f"(d[8]), "+f"(d[9]), "+f"(d[10]), "+f"(d[11]),
          "+f"(d[12]), "+f"(d[13]), "+f"(d[14]), "+f"(d[15]), "+f"(d[16]), "+f"(d[17]), "+f"(d[18]), "+f"(d[19]), "+f"(d[20]), "+f"(d[21]), "+f"(d[22]),
          "+f"(d[23]), "+f"(d[24]), "+f"(d[25]), "+f"(d[26]), "+f"(d[27]), "+f"(d[28]), "+f"(d[29]), "+f"(d[30]), "+f"(d[31]), "+f"(d[32]), "+f"(d[33]),
          "+f"(d[34]), "+f"(d[35]), "+f"(d[36]), "+f"(d[37]), "+f"(d[38]), "+f"(d[39]), "+f"(d[40]), "+f"(d[41]), "+f"(d[42]), "+f"(d[43]), "+f"(d[44]),
          "+f"(d[45]), "+f"(d[46]), "+f"(d[47]), "+f"(d[48]), "+f"(d[49]), "+f"(d[50]), "+f"(d[51]), "+f"(d[52]), "+f"(d[53]), "+f"(d[54]), "+f"(d[55]),
          "+f"(d[56]), "+f"(d[57]), "+f"(d[58]), "+f"(d[59]), "+f"(d[60]), "+f"(d[61]), "+f"(d[62]), "+f"(d[63])
        : "r"(alo), "r"(blo), "r"(scale_d));
}
__device__ __forceinline__ void mma_mix2(float (&d)[64], uint32_t alo, uint32_t blo, int scale_d) {
    asm volatile("{\n.reg .pred p;\n.reg .b64 da, db;\nsetp.ne.b32 p, %66, 0;\nmov.b64 da, {%64, 0x40000040};\nmov.b64 db, {%65, 0x40000040};\n"
        "wgmma.mma_async.sync.aligned.m64n128k16.f32.bf16.bf16 {"
        "%0, %1, %2, %3, %4, %5, %6, %7, %8, %9, %10, %11, %12, %13, %14, %15, %16, %17, %18, %19, %20, %21, %22, %23, %24, %25, %26, %27, %28, %29, %30, %31,  "
        "%32, %33, %34, %35, %36, %37, %38, %39, %40, %41, %42, %43, %44, %45, %46, %47, %48, %49, %50, %51, %52, %53, %54, %55, %56, %57, %58, %59, %60, %61,  "
        "%62, %63 "
        "}, da, db, p, 1, 1, 1, 0;\n}\n"
        : "+f"(d[0]), "+f"(d[1]), "+f"(d[2]), "+f"(d[3]), "+f"(d[4]), "+f"(d[5]), "+f"(d[6]), "+f"(d[7]), "+f"(d[8]), "+f"(d[9]), "+f"(d[10]), "+f"(d[11]),
          "+f"(d[12]), "+f"(d[13]), "+f"(d[14]), "+f"(d[15]), "+f"(d[16]), "+f"(d[17]), "+f"(d[18]), "+f"(d[19]), "+f"(d[20]), "+f"(d[21]), "+f"(d[22]),
          "+f"(d[23]), "+f"(d[24]), "+f"(d[25]), "+f"(d[26]), "+f"(d[27]), "+f"(d[28]), "+f"(d[29]), "+f"(d[30]), "+f"(d[31]), "+f"(d[32]), "+f"(d[33]),
          "+f"(d[34]), "+f"(d[35]), "+f"(d[36]), "+f"(d[37]), "+f"(d[38]), "+f"(d[39]), "+f"(d[40]), "+f"(d[41]), "+f"(d[42]), "+f"(d[43]), "+f"(d[44]),
          "+f"(d[45]), "+f"(d[46]), "+f"(d[47]), "+f"(d[48]), "+f"(d[49]), "+f"(d[50]), "+f"(d[51]), "+f"(d[52]), "+f"(d[53]), "+f"(d[54]), "+f"(d[55]),
          "+f"(d[56]), "+f"(d[57]), "+f"(d[58]), "+f"(d[59]), "+f"(d[60]), "+f"(d[61]), "+f"(d[62]), "+f"(d[63])
        : "r"(alo), "r"(blo), "r"(scale_d));
}
__device__ __forceinline__ void mma_mix1(float (&d)[112], uint32_t alo, uint32_t blo, int scale_d) {
    asm volatile("{\n.reg .pred p;\n.reg .b64 da, db;\nsetp.ne.b32 p, %114, 0;\nmov.b64 da, {%112, 0x40000040};\nmov.b64 db, {%113, 0x80000020};\n"
        "wgmma.mma_async.sync.aligned.m64n224k16.f32.bf16.bf16 {"
        "%0, %1, %2, %3, %4, %5, %6, %7, %8, %9, %10, %11, %12, %13, %14, %15, %16, %17, %18, %19, %20, %21, %22, %23, %24, %25, %26, %27, %28, %29, %30, %31,  "
        "%32, %33, %34, %35, %36, %37, %38, %39, %40, %41, %42, %43, %44, %45, %46, %47, %48, %49, %50, %51, %52, %53, %54, %55, %56, %57, %58, %59, %60, %61,  "
        "%62, %63, %64, %65, %66, %67, %68, %69, %70, %71, %72, %73, %74, %75, %76, %77, %78, %79, %80, %81, %82, %83, %84, %85, %86, %87, %88, %89, %90, %91,  "
        "%92, %93, %94, %95, %96, %97, %98, %99, %100, %101, %102, %103, %104, %105, %106, %107, %108, %109, %110, %111 "
        "}, da, db, p, 1, 1, 1, 1;\n}\n"
        : "+f"(d[0]), "+f"(d[1]), "+f"(d[2]), "+f"(d[3]), "+f"(d[4]), "+f"(d[5]), "+f"(d[6]), "+f"(d[7]), "+f"(d[8]), "+f"(d[9]), "+f"(d[10]), "+f"(d[11]),
          "+f"(d[12]), "+f"(d[13]), "+f"(d[14]), "+f"(d[15]), "+f"(d[16]), "+f"(d[17]), "+f"(d[18]), "+f"(d[19]), "+f"(d[20]), "+f"(d[21]), "+f"(d[22]),
          "+f"(d[23]), "+f"(d[24]), "+f"(d[25]), "+f"(d[26]), "+f"(d[27]), "+f"(d[28]), "+f"(d[29]), "+f"(d[30]), "+f"(d[31]), "+f"(d[32]), "+f"(d[33]),
          "+f"(d[34]), "+f"(d[35]), "+f"(d[36]), "+f"(d[37]), "+f"(d[38]), "+f"(d[39]), "+f"(d[40]), "+f"(d[41]), "+f"(d[42]), "+f"(d[43]), "+f"(d[44]),
          "+f"(d[45]), "+f"(d[46]), "+f"(d[47]), "+f"(d[48]), "+f"(d[49]), "+f"(d[50]), "+f"(d[51]), "+f"(d[52]), "+f"(d[53]), "+f"(d[54]), "+f"(d[55]),
          "+f"(d[56]), "+f"(d[57]), "+f"(d[58]), "+f"(d[59]), "+f"(d[60]), "+f"(d[61]), "+f"(d[62]), "+f"(d[63]), "+f"(d[64]), "+f"(d[65]), "+f"(d[66]),
          "+f"(d[67]), "+f"(d[68]), "+f"(d[69]), "+f"(d[70]), "+f"(d[71]), "+f"(d[72]), "+f"(d[73]), "+f"(d[74]), "+f"(d[75]), "+f"(d[76]), "+f"(d[77]),
          "+f"(d[78]), "+f"(d[79]), "+f"(d[80]), "+f"(d[81]), "+f"(d[82]), "+f"(d[83]), "+f"(d[84]), "+f"(d[85]), "+f"(d[86]), "+f"(d[87]), "+f"(d[88]),
          "+f"(d[89]), "+f"(d[90]), "+f"(d[91]), "+f"(d[92]), "+f"(d[93]), "+f"(d[94]), "+f"(d[95]), "+f"(d[96]), "+f"(d[97]), "+f"(d[98]), "+f"(d[99]),
          "+f"(d[100]), "+f"(d[101]), "+f"(d[102]), "+f"(d[103]), "+f"(d[104]), "+f"(d[105]), "+f"(d[106]), "+f"(d[107]), "+f"(d[108]), "+f"(d[109]),
          "+f"(d[110]), "+f"(d[111])
        : "r"(alo), "r"(blo), "r"(scale_d));
}
__device__ __forceinline__ void mma_qk0(float (&d)[32], uint32_t alo, uint32_t blo) {
    asm volatile("{\n.reg .pred p;\n.reg .b64 da, db;\nsetp.ne.b32 p, 0, 0;\nmov.b64 da, {%32, 0x80000020};\nmov.b64 db, {%33, 0x80000020};\n"
        "wgmma.mma_async.sync.aligned.m64n64k16.f32.bf16.bf16 {"
        "%0, %1, %2, %3, %4, %5, %6, %7, %8, %9, %10, %11, %12, %13, %14, %15, %16, %17, %18, %19, %20, %21, %22, %23, %24, %25, %26, %27, %28, %29, %30, %31 "
        "}, da, db, p, 1, 1, 0, 0;\n}\n"
        : "=f"(d[0]), "=f"(d[1]), "=f"(d[2]), "=f"(d[3]), "=f"(d[4]), "=f"(d[5]), "=f"(d[6]), "=f"(d[7]), "=f"(d[8]), "=f"(d[9]), "=f"(d[10]), "=f"(d[11]),
          "=f"(d[12]), "=f"(d[13]), "=f"(d[14]), "=f"(d[15]), "=f"(d[16]), "=f"(d[17]), "=f"(d[18]), "=f"(d[19]), "=f"(d[20]), "=f"(d[21]), "=f"(d[22]),
          "=f"(d[23]), "=f"(d[24]), "=f"(d[25]), "=f"(d[26]), "=f"(d[27]), "=f"(d[28]), "=f"(d[29]), "=f"(d[30]), "=f"(d[31])
        : "r"(alo), "r"(blo));
}
__device__ __forceinline__ void mma_qk1(float (&d)[32], uint32_t alo, uint32_t blo, int scale_d) {
    asm volatile("{\n.reg .pred p;\n.reg .b64 da, db;\nsetp.ne.b32 p, %34, 0;\nmov.b64 da, {%32, 0x80000020};\nmov.b64 db, {%33, 0x80000020};\n"
        "wgmma.mma_async.sync.aligned.m64n64k16.f32.bf16.bf16 {"
        "%0, %1, %2, %3, %4, %5, %6, %7, %8, %9, %10, %11, %12, %13, %14, %15, %16, %17, %18, %19, %20, %21, %22, %23, %24, %25, %26, %27, %28, %29, %30, %31 "
        "}, da, db, p, 1, 1, 0, 0;\n}\n"
        : "+f"(d[0]), "+f"(d[1]), "+f"(d[2]), "+f"(d[3]), "+f"(d[4]), "+f"(d[5]), "+f"(d[6]), "+f"(d[7]), "+f"(d[8]), "+f"(d[9]), "+f"(d[10]), "+f"(d[11]),
          "+f"(d[12]), "+f"(d[13]), "+f"(d[14]), "+f"(d[15]), "+f"(d[16]), "+f"(d[17]), "+f"(d[18]), "+f"(d[19]), "+f"(d[20]), "+f"(d[21]), "+f"(d[22]),
          "+f"(d[23]), "+f"(d[24]), "+f"(d[25]), "+f"(d[26]), "+f"(d[27]), "+f"(d[28]), "+f"(d[29]), "+f"(d[30]), "+f"(d[31])
        : "r"(alo), "r"(blo), "r"(scale_d));
}
__device__ __forceinline__ void mma_pv(float (&d)[20], uint32_t a0, uint32_t a1, uint32_t a2, uint32_t a3, uint32_t blo, int scale_d) {
    asm volatile("{\n.reg .pred p;\n.reg .b64 da, db;\nsetp.ne.b32 p, %25, 0;\nmov.b64 db, {%24, 0x80000020};\n"
        "wgmma.mma_async.sync.aligned.m64n40k16.f32.bf16.bf16 {"
        "%0, %1, %2, %3, %4, %5, %6, %7, %8, %9, %10, %11, %12, %13, %14, %15, %16, %17, %18, %19 "
        "}, {%20, %21, %22, %23}, db, p, 1, 1, 1;\n}\n"
        : "+f"(d[0]), "+f"(d[1]), "+f"(d[2]), "+f"(d[3]), "+f"(d[4]), "+f"(d[5]), "+f"(d[6]), "+f"(d[7]), "+f"(d[8]), "+f"(d[9]), "+f"(d[10]), "+f"(d[11]),
          "+f"(d[12]), "+f"(d[13]), "+f"(d[14]), "+f"(d[15]), "+f"(d[16]), "+f"(d[17]), "+f"(d[18]), "+f"(d[19])
        : "r"(a0), "r"(a1), "r"(a2), "r"(a3), "r"(blo), "r"(scale_d));
}
__device__ __forceinline__ void mma_qk0w(float (&d)[32], uint64_t da, uint64_t db) {
    asm volatile("{\n.reg .pred p;\n.reg .b64 da, db;\nsetp.ne.b32 p, 0, 0;\nmov.b64 da, %32;\nmov.b64 db, %33;\n"
        "wgmma.mma_async.sync.aligned.m64n64k16.f32.bf16.bf16 {"
        "%0, %1, %2, %3, %4, %5, %6, %7, %8, %9, %10, %11, %12, %13, %14, %15, %16, %17, %18, %19, %20, %21, %22, %23, %24, %25, %26, %27, %28, %29, %30, %31 "
        "}, da, db, p, 1, 1, 0, 0;\n}\n"
        : "=f"(d[0]), "=f"(d[1]), "=f"(d[2]), "=f"(d[3]), "=f"(d[4]), "=f"(d[5]), "=f"(d[6]), "=f"(d[7]), "=f"(d[8]), "=f"(d[9]), "=f"(d[10]), "=f"(d[11]),
          "=f"(d[12]), "=f"(d[13]), "=f"(d[14]), "=f"(d[15]), "=f"(d[16]), "=f"(d[17]), "=f"(d[18]), "=f"(d[19]), "=f"(d[20]), "=f"(d[21]), "=f"(d[22]),
          "=f"(d[23]), "=f"(d[24]), "=f"(d[25]), "=f"(d[26]), "=f"(d[27]), "=f"(d[28]), "=f"(d[29]), "=f"(d[30]), "=f"(d[31])
        : "l"(da), "l"(db));
}
__device__ __forceinline__ void mma_qk1w(float (&d)[32], uint64_t da, uint64_t db, int scale_d) {
    asm volatile("{\n.reg .pred p;\n.reg .b64 da, db;\nsetp.ne.b32 p, %34, 0;\nmov.b64 da, %32;\nmov.b64 db, %33;\n"
        "wgmma.mma_async.sync.aligned.m64n64k16.f32.bf16.bf16 {"
        "%0, %1, %2, %3, %4, %5, %6, %7, %8, %9, %10, %11, %12, %13, %14, %15, %16, %17, %18, %19, %20, %21, %22, %23, %24, %25, %26, %27, %28, %29, %30, %31 "
        "}, da, db, p, 1, 1, 0, 0;\n}\n"
        : "+f"(d[0]), "+f"(d[1]), "+f"(d[2]), "+f"(d[3]), "+f"(d[4]), "+f"(d[5]), "+f"(d[6]), "+f"(d[7]), "+f"(d[8]), "+f"(d[9]), "+f"(d[10]), "+f"(d[11]),
          "+f"(d[12]), "+f"(d[13]), "+f"(d[14]), "+f"(d[15]), "+f"(d[16]), "+f"(d[17]), "+f"(d[18]), "+f"(d[19]), "+f"(d[20]), "+f"(d[21]), "+f"(d[22]),
          "+f"(d[23]), "+f"(d[24]), "+f"(d[25]), "+f"(d[26]), "+f"(d[27]), "+f"(d[28]), "+f"(d[29]), "+f"(d[30]), "+f"(d[31])
        : "l"(da), "l"(db), "r"(scale_d));
}
__device__ __forceinline__ void mma_pvw(float (&d)[20], uint32_t a0, uint32_t a1, uint32_t a2, uint32_t a3, uint64_t db, int scale_d) {
    asm volatile("{\n.reg .pred p;\n.reg .b64 da, db;\nsetp.ne.b32 p, %25, 0;\nmov.b64 db, %24;\n"
        "wgmma.mma_async.sync.aligned.m64n40k16.f32.bf16.bf16 {"
        "%0, %1, %2, %3, %4, %5, %6, %7, %8, %9, %10, %11, %12, %13, %14, %15, %16, %17, %18, %19 "
        "}, {%20, %21, %22, %23}, db, p, 1, 1, 1;\n}\n"
        : "+f"(d[0]), "+f"(d[1]), "+f"(d[2]), "+f"(d[3]), "+f"(d[4]), "+f"(d[5]), "+f"(d[6]), "+f"(d[7]), "+f"(d[8]), "+f"(d[9]), "+f"(d[10]), "+f"(d[11]),
          "+f"(d[12]), "+f"(d[13]), "+f"(d[14]), "+f"(d[15]), "+f"(d[16]), "+f"(d[17]), "+f"(d[18]), "+f"(d[19])
        : "r"(a0), "r"(a1), "r"(a2), "r"(a3), "l"(db), "r"(scale_d));
}

struct GemmSmem { uint32_t base, full0, empty0, aux; };

struct NoEarly { __device__ __forceinline__ void operator()(const GemmSmem&) const {} };
template <class C, class E = NoEarly>
__device__ __forceinline__ GemmSmem gemm_setup(uint8_t* smem_raw, E early = E()) {
    GemmSmem s;
    s.base = smem_u32(smem_raw);
    s.full0 = s.base + C::BAR_OFF; s.empty0 = s.full0 + 8 * C::STAGES; s.aux = s.empty0 + 8 * C::STAGES;
    if (threadIdx.x == 0) {
        if (s.base & 1023) __trap();
        for (int i = 0; i < C::STAGES; i++) { mbar_init(s.full0 + 8 * i, 1); mbar_init(s.empty0 + 8 * i, C::MC ? 16 : 8); }
        mbar_init(s.aux, C::AUX_COUNT);
        fence_barrier_init();
        early(s);
    }
    __syncthreads();
    if (C::MC) { cluster_arrive(); cluster_wait(); }
    return s;
}

#define TK(slot)
#define TKC(slot)
#define TKW(slot)
template <class C, class P>
__device__ __forceinline__ void gemm_producer(const GemmSmem& s, const P& p, int tm, int tn) {
    TK(8);
    C::load_aux(p, s, tm, tn);
#pragma unroll 1
    for (int k = 0; k < C::PRE; k++) {
        mbar_expect_tx(s.full0 + 8 * k, C::STAGE_BYTES);
        C::load_w(p, s.base + k * C::STAGE_BYTES, s.full0 + 8 * k, k, tm, tn);
    }
    TK(9);
    pdl_wait();
    TK(10);
#pragma unroll 1
    for (int k = 0; k < C::STAGES; k++) {
        if (C::FIRST_BY_THREADS && k == 0) { mbar_arrive(s.full0); continue; }
        if (k >= C::PRE) mbar_expect_tx(s.full0 + 8 * k, C::STAGE_BYTES);
        C::load_x(p, s.base + k * C::STAGE_BYTES, s.full0 + 8 * k, k, tm, tn);
        if (k >= C::PRE) C::load_w(p, s.base + k * C::STAGE_BYTES, s.full0 + 8 * k, k, tm, tn);
    }
    TK(11);
    int st = 0; uint32_t ph = 0;
#pragma unroll 1
    for (int k = C::STAGES; k < C::KSTEPS; k++) {
        mbar_wait(s.empty0 + 8 * st, ph);
        if (k < C::STAGES + C::FOLLOW) mbar_wait(s.aux + 16 + 8 * st, ph);
        C::after_release(p, s, k, tm, tn);
        mbar_expect_tx(s.full0 + 8 * st, C::STAGE_BYTES);
        C::load_x(p, s.base + st * C::STAGE_BYTES, s.full0 + 8 * st, k, tm, tn);
        C::load_w(p, s.base + st * C::STAGE_BYTES, s.full0 + 8 * st, k, tm, tn);
        if (++st == C::STAGES) { st = 0; ph ^= 1; }
    }
    C::producer_done(s);
}

template <class C, int KEND = C::KSTEPS, int SK = 0, bool DONE_BAR = false>
__device__ __forceinline__ void gemm_mainloop(const GemmSmem& s, int wg, float (&acc)[C::MB][C::BN / 2], int tlk = 0) {
    const int lane = threadIdx.x & 31;
    int st = 0; uint32_t ph = 0;
    int prev = 0;
    const uint32_t rel0 = C::MC ? mapa(s.empty0, lane & 1) : s.empty0;
#pragma unroll
    for (int m = 0; m < C::MB; m++) fence_regs(acc[m]);
#pragma unroll 1
    for (int k = 0; k < KEND; k++) {
        if (SK > 0 && k == KEND - SK && wg == 1) {
            if (DONE_BAR) { wg_wait<0>(); named_arrive(10, 256); }
            named_bar(11, 256);
        }
        mbar_wait(s.full0 + 8 * st, ph);
        const uint32_t sb = s.base + st * C::STAGE_BYTES;
        wg_fence();
#pragma unroll
        for (int kk = 0; kk < 4; kk++) {
#pragma unroll
            for (int m = 0; m < C::MB; m++) C::mma(acc[m], C::desc_a(sb, wg, m, kk), C::desc_b(sb, kk), C::ACC_INIT || (k | kk) != 0);
        }
        wg_commit();
        if (SK > 0 && k == KEND - 1 && wg == 0) named_arrive(11, 256);
        if (k > 0) {
            wg_wait<1>();
            if (k <= C::KSTEPS - C::STAGES) {
                if (C::MC) { if (lane < 2) mbar_arrive_cluster(rel0 + 8 * prev); }
                else if (lane == 0) mbar_arrive(rel0 + 8 * prev);
            }
        }
        prev = st;
        if (++st == C::STAGES) { st = 0; ph ^= 1; }
    }
    if (KEND == C::KSTEPS) {
        wg_wait<0>();
#pragma unroll
        for (int m = 0; m < C::MB; m++) fence_regs(acc[m]);
    }
}

struct QkvParams { CUtensorMap x, w, out; const bf16* xp; const bf16* wp; };
struct QkvCfg {
    static constexpr int MB = 1, BN = 192, KSTEPS = 32, STAGES = 4, A_BYTES = 16384, B_BYTES = 24576;
    static constexpr int STAGE_BYTES = A_BYTES + B_BYTES, STG_OFF = STAGES * STAGE_BYTES, BAR_OFF = STG_OFF + 65536, AUX_OFF = BAR_OFF + 128, SMEM = AUX_OFF + 2816;
    static constexpr int AUX_COUNT = 3, PRE = 0;
    static constexpr int TLK = 1;
    static constexpr bool MC = true, ACC_INIT = false, FIRST_BY_THREADS = QKV_FIRST;
    static constexpr int FOLLOW = 16;
    static __device__ __forceinline__ void after_release(const QkvParams& p, const GemmSmem& s, int k, int tm, int tn) {
        const int g2 = k - (21 + QKV2_E0);
        if (g2 == 0 || g2 == 2 || g2 == 4) {
            fence_proxy_async();
#pragma unroll
            for (int i = 0; i < 4; i++)
                tma_st2(&p.out, s.base + STG_OFF + (i >> 1) * 24576 + (g2 + (i & 1)) * 4096, 0, (g2 >> 1) * (NH * SEQ) + (tn * 2 + (i & 1)) * SEQ + tm * 256 + (i >> 1) * 64);
        }
    }
    static __device__ __forceinline__ void producer_done(const GemmSmem& s) {
        tma_st_commit(); tma_st_wait(); mbar_arrive(s.aux + 48);
    }
    static __device__ __forceinline__ void load_w(const QkvParams& p, uint32_t sb, uint32_t bar, int k, int tm, int tn) {
        tma_ld4_mc(sb + A_BYTES + (tm & 1) * (B_BYTES / 2), &p.w, bar, 0, (k & 15) * 64 + (tm & 1) * 32, 0, tn);
    }
    static __device__ __forceinline__ void load_x(const QkvParams& p, uint32_t sb, uint32_t bar, int k, int tm, int tn) { tma_ld2(sb, &p.x, bar, (k & 15) * 64, tm * 256 + (k >> 4) * 128); }
    static __device__ __forceinline__ void load_aux(const QkvParams&, const GemmSmem&, int, int) {}
    static __device__ __forceinline__ uint32_t desc_a(uint32_t sb, int wg, int m, int kk) { return desc_lo(sb + wg * 8192 + kk * 32, 16); }
    static __device__ __forceinline__ uint32_t desc_b(uint32_t sb, int kk) { return desc_lo(sb + A_BYTES + (kk >> 1) * (B_BYTES / 2) + (kk & 1) * 2048, 4096); }
    static __device__ __forceinline__ void mma(float (&d)[96], uint32_t a, uint32_t b, int sc) { mma_qkv(d, a, b, sc); }
};

__device__ __forceinline__ void cp16(uint32_t dst, const void* src) { asm volatile("cp.async.cg.shared.global [%0], [%1], 16;" :: "r"(dst), "l"(src) : "memory"); }
__device__ __forceinline__ uint4 lds16(uint32_t a) { uint4 t; asm volatile("ld.shared.v4.u32 {%0, %1, %2, %3}, [%4];" : "=r"(t.x), "=r"(t.y), "=r"(t.z), "=r"(t.w) : "r"(a) : "memory"); return t; }
__device__ __forceinline__ void qkv_rows_load(const QkvParams& p, uint32_t reg, int row0, int w, int lane) {
    const uint4* xsrc = reinterpret_cast<const uint4*>(p.xp + (size_t)(row0 + w) * DM) + lane;
#pragma unroll 1
    for (int r = 0; w + 3 * r < 8; r++) {
#pragma unroll
        for (int i = 0; i < 4; i++) cp16(reg + r * 6144 + i * 512, xsrc + r * (3 * DM / 8) + i * 32);
    }
    asm volatile("cp.async.commit_group;" ::: "memory");
}
__device__ __forceinline__ void qkv_rows_gather(float2* sst, int row0, int t) {
    unsigned long long u[2];
    int it = 0;
    bool ok;
    do {
#pragma unroll
        for (int i = 0; i < 2; i++) asm volatile("ld.relaxed.gpu.global.u64 %0, [%1];" : "=l"(u[i]) : "l"(g_rowstat2 + row0 + min(t + 96 * i, 127)) : "memory");
        ok = (long long)(u[0] & u[1]) < 0;
        if (++it > (1 << 20)) __trap();
    } while (!ok);
#pragma unroll
    for (int i = 0; i < 2; i++)
        if (t + 96 * i < 128) sst[t + 96 * i] = make_float2(__uint_as_float((uint32_t)u[i]), __uint_as_float((uint32_t)(u[i] >> 32) & 0x7FFFFFFFu));
}
struct Moments {
    float sd0, sd1, sq0, sq1, x0;
    __device__ __forceinline__ void add(const uint4 x) {
        const float d0 = bf_lo(x.x) - x0, d1 = bf_hi(x.x) - x0, d2 = bf_lo(x.y) - x0, d3 = bf_hi(x.y) - x0;
        const float d4 = bf_lo(x.z) - x0, d5 = bf_hi(x.z) - x0, d6 = bf_lo(x.w) - x0, d7 = bf_hi(x.w) - x0;
        sd0 += (d0 + d1) + (d2 + d3); sd1 += (d4 + d5) + (d6 + d7);
        sq0 = fmaf(d0, d0, fmaf(d1, d1, fmaf(d2, d2, fmaf(d3, d3, sq0))));
        sq1 = fmaf(d4, d4, fmaf(d5, d5, fmaf(d6, d6, fmaf(d7, d7, sq1))));
    }
    template <int L> __device__ __forceinline__ unsigned long long finish() {
        float sd = sd0 + sd1, sq = sq0 + sq1;
#pragma unroll
        for (int o = 1; o < L; o <<= 1) { sd += __shfl_xor_sync(0xffffffffu, sd, o); sq += __shfl_xor_sync(0xffffffffu, sq, o); }
        const float md = sd * (1.f / DM);
        const float rstd = rsqrtf(fmaxf(fmaf(-md, md, sq * (1.f / DM)), 0.f) + 1e-5f);
        return ((unsigned long long)(__float_as_uint(rstd) | 0x80000000u) << 32) | __float_as_uint(x0 + md);
    }
};
template <class C>
__device__ __forceinline__ void qkv_aux(const QkvParams& p, uint8_t* smem_raw, const GemmSmem& s, int tm, int tn, int w, int lane) {
    AX(0);
    const uint32_t rel0 = mapa(s.aux + 16, lane & 1);
    const int chunk = lane & 7, sub = lane >> 3;
    const int wr = tm * 8 + sub;
    const uint32_t woff = C::A_BYTES + (wr >> 5) * (C::B_BYTES / 2) + w * 4096 + (wr & 31) * 128;
    const uint32_t woff0 = woff + ((chunk ^ (wr & 7)) << 4), woff1 = woff + 512 + ((chunk ^ ((wr + 4) & 7)) << 4);
    const int xr = tn * 8 + (w & 1) * 4 + sub;
    const uint32_t xoff = xr * 128 + ((chunk ^ (xr & 7)) << 4);
    const uint32_t xreg = s.base + C::STG_OFF + 49152 + w * 2048 + lane * 16;
    const uint8_t* pf = lane < 24 ? reinterpret_cast<const uint8_t*>(p.wp + (size_t)(tm * 8 + lane / 3) * (3 * DM) + (lane % 3) * DM + tn * 64)
                                  : reinterpret_cast<const uint8_t*>(p.xp + (size_t)(tm * 256 + tn * 8 + lane - 24) * DM);
    const uint32_t pf_step = lane < 24 ? 64 * 3 * DM * 2 : 128;
    float* scs = reinterpret_cast<float*>(smem_raw + C::AUX_OFF);
    float2* sst = reinterpret_cast<float2*>(smem_raw + C::AUX_OFF + 768);
    const int t = w * 32 + lane;
    float a[8];
#pragma unroll
    for (int i = 0; i < 8; i++) a[i] = 0.f;
    Moments m0 = {0.f, 0.f, 0.f, 0.f, 0.f};
    if (QKV_FIRST) named_bar(13, 352);
#pragma unroll 1
    for (int k = 0; k < 16; k++) {
        const int st = k & 3;
        mbar_wait(s.full0 + 8 * st, (k >> 2) & 1);
        const uint32_t sb = s.base + st * C::STAGE_BYTES;
        const uint4 u = lds16(sb + woff0), v = lds16(sb + woff1);
        if (w < 2) {
            const uint4 x = lds16(sb + xoff);
            if (k == 0) m0.x0 = __shfl_sync(0xffffffffu, bf_lo(x.x), lane & 24);
            m0.add(x);
        } else if (QKV3_PF) {
            if (k == 0) for (int j = C::STAGES; j < QKV3_PF; j++) prefetch_line(pf + (size_t)j * pf_step);
            if (k + QKV3_PF < 16) prefetch_line(pf + (size_t)(k + QKV3_PF) * pf_step);
        }
        a[0] += bf_lo(u.x) + bf_lo(v.x); a[1] += bf_hi(u.x) + bf_hi(v.x); a[2] += bf_lo(u.y) + bf_lo(v.y); a[3] += bf_hi(u.y) + bf_hi(v.y);
        a[4] += bf_lo(u.z) + bf_lo(v.z); a[5] += bf_hi(u.z) + bf_hi(v.z); a[6] += bf_lo(u.w) + bf_lo(v.w); a[7] += bf_hi(u.w) + bf_hi(v.w);
        __syncwarp();
        if (lane < 2) mbar_arrive_cluster(rel0 + 8 * st);
        if (k == QKV3_R1) qkv_rows_load(p, xreg, tm * 256 + 128 + tn * 8, w, lane);
    }
    AX(1);
    if (w < 2) {
        const unsigned long long w0 = m0.finish<8>();
        if (chunk == 0) asm volatile("st.relaxed.gpu.global.u64 [%0], %1;" :: "l"(g_rowstat2 + tm * 256 + xr), "l"(w0) : "memory");
    }
#pragma unroll
    for (int i = 0; i < 8; i++) { a[i] += __shfl_xor_sync(0xffffffffu, a[i], 8); a[i] += __shfl_xor_sync(0xffffffffu, a[i], 16); }
    if (lane < 16) {
        const bool up = lane & 8;
        uint32_t* dst = g_colsum2 + tm * (3 * DM) + tn * 192 + w * 64 + (lane & 7) * 8 + (up ? 4 : 0);
        asm volatile("st.relaxed.gpu.global.v4.u32 [%0], {%1, %2, %3, %4};" :: "l"(dst), "r"(__float_as_uint(up ? a[4] : a[0]) | 1u), "r"(__float_as_uint(up ? a[5] : a[1]) | 1u),
                     "r"(__float_as_uint(up ? a[6] : a[2]) | 1u), "r"(__float_as_uint(up ? a[7] : a[3]) | 1u) : "memory");
    }
    AX(2);
    auto row1 = [&](int r) {
        Moments m = {0.f, 0.f, 0.f, 0.f, 0.f};
        const uint4 x = lds16(xreg + r * 6144);
        m.x0 = __shfl_sync(0xffffffffu, bf_lo(x.x), 0);
        m.add(x);
#pragma unroll
        for (int i = 1; i < 4; i++) m.add(lds16(xreg + r * 6144 + i * 512));
        const unsigned long long word = m.finish<32>();
        if (lane == 0) asm volatile("st.relaxed.gpu.global.u64 [%0], %1;" :: "l"(g_rowstat2 + tm * 256 + 128 + tn * 8 + w + 3 * r), "l"(word) : "memory");
    };
    {
        uint32_t ux[8], uy[8];
        unsigned long long r0, r1;
        int it = 0;
        bool ok;
        do {
            asm volatile("ld.relaxed.gpu.global.u64 %0, [%1];" : "=l"(r0) : "l"(g_rowstat2 + tm * 256 + t) : "memory");
            asm volatile("ld.relaxed.gpu.global.u64 %0, [%1];" : "=l"(r1) : "l"(g_rowstat2 + tm * 256 + 96 + (t & 31)) : "memory");
            uint32_t all = 1;
#pragma unroll
            for (int i = 0; i < 8; i++) {
                asm volatile("ld.relaxed.gpu.global.v2.u32 {%0, %1}, [%2];" : "=r"(ux[i]), "=r"(uy[i]) : "l"(g_colsum2 + i * (3 * DM) + tn * 192 + 2 * t) : "memory");
                all &= ux[i] & uy[i];
            }
            ok = (all & 1) && (long long)(r0 & r1) < 0;
            if (++it > (1 << 20)) __trap();
        } while (!ok);
        AX(3);
        sst[t] = make_float2(__uint_as_float((uint32_t)r0), __uint_as_float((uint32_t)(r0 >> 32) & 0x7FFFFFFFu));
        if (w == 0) sst[96 + t] = make_float2(__uint_as_float((uint32_t)r1), __uint_as_float((uint32_t)(r1 >> 32) & 0x7FFFFFFFu));
        float2 c = make_float2(0.f, 0.f);
#pragma unroll
        for (int i = 0; i < 8; i++) { c.x += __uint_as_float(ux[i]); c.y += __uint_as_float(uy[i]); }
        reinterpret_cast<float2*>(scs)[t] = c;
    }
    __syncwarp();
    if (lane == 0) mbar_arrive(s.aux);
    AX(4);
    asm volatile("cp.async.wait_group 0;" ::: "memory");
#pragma unroll 1
    for (int r = 0; w + 3 * r < 8; r++) row1(r);
    AX(5);
    qkv_rows_gather(sst + 128, tm * 256 + 128, t);
    __syncwarp();
    if (lane == 0) mbar_arrive(s.aux + 8);
    AX(6);
    AX(7);
}

__global__ void __launch_bounds__(384, 1) qkv_kernel(const __grid_constant__ QkvParams p) {
    using C = QkvCfg;
    extern __shared__ __align__(1024) uint8_t smem_raw[];
    TL(1, 4);
    const int tm = blockIdx.x & 7, tn = blockIdx.x >> 3;
    if (QKV_FIRST && threadIdx.x >= 128) {
        const int t = threadIdx.x - 128, r = t >> 3, c = t & 7;
        const uint32_t dst = smem_u32(smem_raw) + r * 128 + ((c ^ (r & 7)) << 4);
        const bf16* xs = p.xp + (size_t)(tm * 256 + r) * DM + c * 8;
        const bf16* ws = p.wp + (size_t)r * (3 * DM) + tn * 64 + c * 8;
#pragma unroll
        for (int i = 0; i < 6; i++) cp16(dst + C::A_BYTES + (i & 1) * (C::B_BYTES / 2) + (i >> 1) * 4096, ws + (i & 1) * (32 * 3 * DM) + (i >> 1) * DM);
#pragma unroll
        for (int i = 0; i < 4; i++) cp16(dst + i * 4096, xs + i * 32 * DM);
        asm volatile("cp.async.commit_group;" ::: "memory");
    }
    pdl_launch();
    if (threadIdx.x == 0) { prefetch_map(&p.x); prefetch_map(&p.w); prefetch_map(&p.out); }
    const GemmSmem s = gemm_setup<C>(smem_raw, [](const GemmSmem& g) { mbar_init(g.aux + 8, 3); for (int i = 0; i < C::STAGES; i++) mbar_init(g.aux + 16 + 8 * i, 6); mbar_init(g.aux + 48, 1); fence_barrier_init(); });
    const int wgi = __shfl_sync(0xffffffffu, threadIdx.x >> 7, 0);
    if (wgi == 0) {
        reg_dealloc<56>();
        if (threadIdx.x == 0) gemm_producer<C>(s, p, tm, tn);
        else if (threadIdx.x >= 32) {
            qkv_aux<C>(p, smem_raw, s, tm, tn, (threadIdx.x >> 5) - 1, threadIdx.x & 31);
            TK(14);
            if (threadIdx.x < 96) {
                const int wg = (threadIdx.x >> 5) - 1;
                const bool leader = (threadIdx.x & 31) == 0;
#pragma unroll 1
                for (int g = 0; g < 3; g++) {
                    take_over(2 + wg * 3 + g);
                    if (leader) {
#pragma unroll
                        for (int h = 0; h < 2; h++)
                            tma_st2(&p.out, s.base + C::STG_OFF + wg * 24576 + (g * 2 + h) * 4096, 0, g * (NH * SEQ) + (tn * 2 + h) * SEQ + tm * 256 + 128 + wg * 64);
                    }
                }
                if (leader) { tma_st_commit(); tma_st_wait(); }
                if (leader) TL(1, 3);
            }
        }
    } else {
        reg_alloc<224>();
        const int wg = wgi - 1, warp = (threadIdx.x >> 5) & 3, lane = threadIdx.x & 31;
        float acc0[1][96], acc1[96];
        TL(1, 0);
        if (QKV_FIRST) { asm volatile("cp.async.wait_group 0;" ::: "memory"); fence_proxy_async(); named_bar(13, 352); }
        gemm_mainloop<C, 16>(s, wg, acc0, 1);
        const uint32_t rel0 = mapa(s.empty0, lane & 1);
        auto step = [&](int st, uint32_t ph, bool first) {
            mbar_wait(s.full0 + 8 * st, ph);
            const uint32_t sb = s.base + st * C::STAGE_BYTES;
            wg_fence();
#pragma unroll
            for (int kk = 0; kk < 4; kk++) C::mma(acc1, C::desc_a(sb, wg, 0, kk), C::desc_b(sb, kk), !first || kk != 0);
            wg_commit();
        };
        auto release = [&](int st) { wg_wait<1>(); __syncwarp(); if (lane < 2) mbar_arrive_cluster(rel0 + 8 * st); };
        const float qscale = 0.17677669529663687f * 1.4426950408889634f;
        const float2* scs = reinterpret_cast<const float2*>(smem_raw + C::AUX_OFF);
        const float2* sst = reinterpret_cast<const float2*>(smem_raw + C::AUX_OFF + 768);
        const int arow = warp * 16 + ((lane >> 3) & 1) * 8 + (lane & 7);
        auto piece = [&](const float (&acc)[96], int half, int sub, float mean0, float mean1, float r0, float r1) {
            float v[16];
#pragma unroll
            for (int j = 0; j < 4; j++) {
                const float2 cs = scs[(sub * 4 + j) * 4 + (lane & 3)];
                v[4 * j] = fmaf(mean0, cs.x, acc[sub * 16 + 4 * j]) * r0;
                v[4 * j + 1] = fmaf(mean0, cs.y, acc[sub * 16 + 4 * j + 1]) * r0;
                v[4 * j + 2] = fmaf(mean1, cs.x, acc[sub * 16 + 4 * j + 2]) * r1;
                v[4 * j + 3] = fmaf(mean1, cs.y, acc[sub * 16 + 4 * j + 3]) * r1;
            }
#pragma unroll
            for (int jp = 0; jp < 2; jp++) {
                const int chunk = jp * 2 + (lane >> 4);
                const uint32_t addr = s.base + C::STG_OFF + wg * 24576 + sub * 4096 + arow * 64 + ((chunk ^ ((arow >> 1) & 3)) << 4);
                stmatrix_x4(addr, pack_bf16(v[8 * jp], v[8 * jp + 1]), pack_bf16(v[8 * jp + 2], v[8 * jp + 3]),
                            pack_bf16(v[8 * jp + 4], v[8 * jp + 5]), pack_bf16(v[8 * jp + 6], v[8 * jp + 7]));
            }
            if ((sub & 1) && half == 1) hand_over(2 + wg * 3 + (sub >> 1));
            float n0 = 0.f, n1 = 0.f;
#pragma unroll
            for (int j = 0; j < 4; j++) {
                n0 = fmaf(v[4 * j], v[4 * j], fmaf(v[4 * j + 1], v[4 * j + 1], n0));
                n1 = fmaf(v[4 * j + 2], v[4 * j + 2], fmaf(v[4 * j + 3], v[4 * j + 3], n1));
            }
            const bool odd = lane & 1;
            float full = (odd ? n1 : n0) + __shfl_xor_sync(0xffffffffu, odd ? n0 : n1, 1);
            full += __shfl_xor_sync(0xffffffffu, full, 2);
            const uint32_t mx = __reduce_max_sync(0xffffffffu, __float_as_uint(full));
            if (lane == 0) g_norm[((sub >> 1) * NH + tn * 2 + (sub & 1)) * 128 + tm * 16 + half * 8 + wg * 4 + warp] = mx;
        };
        fence_regs(acc1);
        constexpr int E0 = QKV2_E0;
        step(0, 0, true);
        release(3);
        fence_regs(acc0[0]);
#pragma unroll 1
        for (int j = 1; j <= E0; j++) { step(j & 3, (j >> 2) & 1, false); release((j - 1) & 3); }
        {
            mbar_wait(s.aux, 0);
            TKC(12);
            const float2 t0 = sst[wg * 64 + warp * 16 + (lane >> 2)], t1 = sst[wg * 64 + warp * 16 + 8 + (lane >> 2)];
#pragma unroll
            for (int sub = 0; sub < 6; sub++) {
                if (sub > 0) { step((E0 + sub) & 3, ((E0 + sub) >> 2) & 1, false); release((E0 + sub - 1) & 3); }
                const float qs = sub < 2 ? qscale : 1.f;
                piece(acc0[0], 0, sub, -t0.x, -t1.x, t0.y * qs, t1.y * qs);
            }
            TKC(13);
        }
#pragma unroll 1
        for (int k = 22 + E0; k < 32; k++) {
            if (QKV2_SKEW && k == 29 && wg == 1) named_bar(11, 256);
            step(k & 3, (k >> 2) & 1, false);
            if (QKV2_SKEW && k == (QKV2_SKEW == 2 ? 30 : 31) && wg == 0) named_arrive(11, 256);
            if (k <= C::KSTEPS - C::STAGES) release((k - 1) & 3); else wg_wait<1>();
        }
        mbar_wait(s.aux + 8, 0);
        const float2 t2 = sst[128 + wg * 64 + warp * 16 + (lane >> 2)], t3 = sst[128 + wg * 64 + warp * 16 + 8 + (lane >> 2)];
        wg_wait<0>();
        fence_regs(acc1);
        TL(1, 1);
        mbar_wait(s.aux + 48, 0);
#pragma unroll
        for (int sub = 0; sub < 6; sub++) {
            const float qs = sub < 2 ? qscale : 1.f;
            piece(acc1, 1, sub, -t2.x, -t3.x, t2.y * qs, t3.y * qs);
        }
        TL(1, 5);
    }
}

struct AttnParams { CUtensorMap kv, kv2; unsigned long long dbase; bf16* optr; const uint8_t* pf_wo; const uint8_t* pf_w1; const uint8_t* pf_b1;
                    const uint32_t* norm; void* colsum2; void* rowstat2; void* hpart; };
constexpr int AT_STAGES = 8, AT_STAGE_BYTES = 16384, AT_Q_OFF = AT_STAGES * AT_STAGE_BYTES, AT_ONES_OFF = AT_Q_OFF + 32768, AT_BAR_OFF = AT_ONES_OFF + 1024, AT_SMEM = AT_BAR_OFF + 256;
constexpr uint32_t AT_BASE = 1024;
constexpr int AT_TILES = 32;

__device__ __forceinline__ uint32_t fma_bf16x2(uint32_t a, uint32_t b, uint32_t c) { uint32_t d; asm("fma.rn.bf16x2 %0, %1, %2, %3;" : "=r"(d) : "r"(a), "r"(b), "r"(c)); return d; }
constexpr uint32_t FX_LEAD = 0x3EAB3EABu;
__device__ __forceinline__ uint32_t ex2_pair_fx(float x0, float x1, uint32_t c3, uint32_t one2) {
    const float m = 65663.f;
    const uint32_t w = __byte_perm(__float_as_uint(x0 + m), __float_as_uint(x1 + m), 0x5410);
    uint32_t g, r;
    asm("lop3.b32 %0, %1, 0x007F007F, %2, 0xEA;" : "=r"(g) : "r"(w), "r"(one2));
    uint32_t p = fma_bf16x2(g, c3, 0xBC5DBC5Du);
    p = fma_bf16x2(p, g, 0x3F2F3F2Fu);
    asm("lop3.b32 %0, %1, %2, 0xFF80FF80, 0xE4;" : "=r"(r) : "r"(w), "r"(p));
    return r;
}
template <uint32_t MASK> __device__ __forceinline__ uint32_t attn_exp2(float x0, float x1, int i, uint32_t c3) {
    return ((MASK >> i) & 1) ? ex2_pair_fx(x0, x1, c3, c3 ^ (FX_LEAD ^ 0x3F803F80u)) : pack_bf16(ex2(x0), ex2(x1));
}
__device__ __forceinline__ void attn_issue_tile(const AttnParams& p, uint32_t base, uint32_t full0, int g, int head) {
    const int st = g % AT_STAGES, key0 = (g & 15) * 128;
    const uint32_t bar = full0 + 8 * st, dst = base + st * AT_STAGE_BYTES;
    mbar_expect_tx(bar, AT_STAGE_BYTES);
    tma_ld3(dst, &p.kv2, bar, 0, head * SEQ + key0, 1);
}
__device__ __forceinline__ void attn_qk(float (&sacc)[32], uint32_t q_lo, uint32_t k_lo) {
    mma_qk0(sacc, q_lo, k_lo);
    mma_qk1(sacc, q_lo + 2, k_lo + 2, 1);
}
constexpr uint32_t PV_STEP = 64u - (64u << 16);
constexpr long long PV_STEP64 = 64ll - (64ll << 16);
__device__ __forceinline__ void attn_pv(float (&o)[20], const uint32_t (&pr)[16], uint32_t v_lo, int first) {
#pragma unroll
    for (int kk = 0; kk < 4; kk++)
        mma_pv(o, pr[4 * kk], pr[4 * kk + 1], pr[4 * kk + 2], pr[4 * kk + 3], v_lo + kk * PV_STEP, (kk > 0) || !first);
}
__device__ __forceinline__ void attn_store_o(const float (&o)[20], const AttnParams& p, int head, int row0, int lane) {
    const float r0 = 1.f / o[16], r1 = 1.f / o[18];
    uint32_t a[4], b[4];
#pragma unroll
    for (int j = 0; j < 4; j++) { a[j] = pack_bf16(o[4 * j] * r0, o[4 * j + 1] * r0); b[j] = pack_bf16(o[4 * j + 2] * r1, o[4 * j + 3] * r1); }
    const bool odd = lane & 1, up = lane & 2;
#pragma unroll
    for (int h = 0; h < 2; h++) {
        uint32_t t = __shfl_xor_sync(0xffffffffu, odd ? a[2 * h] : a[2 * h + 1], 1); if (odd) a[2 * h] = t; else a[2 * h + 1] = t;
        t = __shfl_xor_sync(0xffffffffu, odd ? b[2 * h] : b[2 * h + 1], 1); if (odd) b[2 * h] = t; else b[2 * h + 1] = t;
    }
#pragma unroll
    for (int h = 0; h < 2; h++) {
        uint32_t t = __shfl_xor_sync(0xffffffffu, up ? a[h] : a[h + 2], 2); if (up) a[h] = t; else a[h + 2] = t;
        t = __shfl_xor_sync(0xffffffffu, up ? b[h] : b[h + 2], 2); if (up) b[h] = t; else b[h + 2] = t;
    }
    uint4* op = reinterpret_cast<uint4*>(p.optr + (size_t)(row0 + (lane >> 2)) * PITCH + head * HD) + (lane & 3);
    op[0] = make_uint4(a[0], a[1], a[2], a[3]);
    op[8 * (PITCH / 8)] = make_uint4(b[0], b[1], b[2], b[3]);
}
__device__ __forceinline__ void attn_refill(const AttnParams& p, uint32_t base, uint32_t full0, uint32_t empty0, int g, int head) {
    if (threadIdx.x == 0 && g >= 4 && g + 4 < AT_TILES) {
        const int gp = g - 4;
        mbar_wait(empty0 + 8 * (gp % AT_STAGES), (gp / AT_STAGES) & 1);
        attn_issue_tile(p, base, full0, g + 4, head);
    }
    __syncwarp();
}

__device__ __forceinline__ void attn_housekeeping(const AttnParams& p) {
    const int l = threadIdx.x;
    if (l < 128 + 140) prefetch_line(l < 128 ? p.pf_wo + ((size_t)blockIdx.x * 128 + l) * 128 : p.pf_w1 + ((size_t)blockIdx.x * 140 + (l - 128)) * 128);
    if (blockIdx.x == 0 && l >= 300 && l < 300 + 56) prefetch_line(p.pf_b1 + (l - 300) * 128);
    if (l >= 384 && l < 384 + 48) reinterpret_cast<uint4*>(p.colsum2)[blockIdx.x * 48 + l - 384] = make_uint4(0, 0, 0, 0);
    if (l >= 432 && l < 432 + 8) reinterpret_cast<uint4*>(p.rowstat2)[blockIdx.x * 8 + l - 432] = make_uint4(0, 0, 0, 0);
    if (l >= 448) reinterpret_cast<uint4*>(p.hpart)[blockIdx.x * 64 + l - 448] = make_uint4(0, 0, 0, 0);
}
template <uint32_t MASK>
__device__ __forceinline__ void attn_piece(float (&o)[20], const float* sc, uint32_t c3, uint64_t dv) {
    uint32_t pr[8];
#pragma unroll
    for (int i = 0; i < 8; i++) pr[i] = attn_exp2<MASK>(sc[2 * i], sc[2 * i + 1], i, c3);
    wg_fence();
    mma_pvw(o, pr[0], pr[1], pr[2], pr[3], dv, 1);
    mma_pvw(o, pr[4], pr[5], pr[6], pr[7], dv + PV_STEP64, 1);
    wg_commit();
}
__device__ __forceinline__ void attn_fast(const AttnParams& p, uint32_t base, uint32_t full0, uint32_t empty0, int head, int qchunk) {
    const int wg = __shfl_sync(0xffffffffu, threadIdx.x >> 7, 0), warp = (threadIdx.x >> 5) & 3, lane = threadIdx.x & 31;
    const int warp_id = __shfl_sync(0xffffffffu, threadIdx.x >> 5, 0);
    const uint32_t k_lo0 = desc_lo(AT_BASE, 16), v_lo0 = desc_lo(AT_BASE + 8192, AT_ONES_OFF - 8192);
    const uint32_t q_lo0 = desc_lo(AT_BASE + AT_Q_OFF, 16) + wg * (64 * 64 >> 4);
    uint32_t c3;
    asm volatile("ld.shared.u32 %0, [%1];" : "=r"(c3) : "r"(base + AT_ONES_OFF));
    c3 ^= 0x3F803F80u ^ FX_LEAD;
    float sa[32], sb[32];
    const uint64_t HI = p.dbase;
    const uint64_t dk0 = HI + k_lo0, dv0 = HI + v_lo0;
    mbar_wait(full0, 0);
    wg_fence();
    mma_qk0w(sa, HI + q_lo0, dk0);
    mma_qk1w(sa, HI + q_lo0 + 2, dk0 + 2, 1);
    wg_commit();
    wg_wait<0>();
    fence_regs(sa);
#pragma unroll 1
    for (int pass = 0; pass < 2; pass++) {
    const uint32_t q = q_lo0 + pass * (256 * 64 >> 4);
    float o[20];
#pragma unroll
    for (int i = 0; i < 20; i++) o[i] = 0.f;
#pragma unroll 1
    for (int hh = 0; hh < 4; hh++) {
        const uint32_t par = hh >> 1, half = hh & 1;
        const int g0 = pass * 16 + hh * 4;
        const uint32_t fb = full0 + half * 32, eb = empty0 + half * 32, eo = empty0 + (half ^ 1) * 32;
        const uint64_t dq = HI + q, dqw = HI + (hh == 3 ? q_lo0 + (256 * 64 >> 4) : q);
        const uint64_t dkh = dk0 + half * (4 * AT_STAGE_BYTES >> 4), dkn = dk0 + (half ^ 1) * (4 * AT_STAGE_BYTES >> 4), dvh = dv0 + (long long)half * (64 * PV_STEP64);
#pragma unroll
        for (int j = 0; j < 4; j++) {
            if (warp_id == j * 5) {
                if (lane == 0 && g0 + 4 < AT_TILES) {
                    if (g0 >= 4) mbar_wait(eo + 8 * j, half ? par : (par ^ 1));
                    const uint32_t bar = full0 + (half ^ 1) * 32 + 8 * j;
                    mbar_expect_tx(bar, AT_STAGE_BYTES);
                    tma_ld3(base + ((half ^ 1) * 4 + j) * AT_STAGE_BYTES, &p.kv2, bar, 0, head * SEQ + ((g0 + 4 + j) & 15) * 128, 1);
                }
                __syncwarp();
            }
            wg_fence();
            const uint64_t kb = dkh + j * (AT_STAGE_BYTES >> 4), vb = dvh + j * 16 * PV_STEP64;
            mma_qk0w(sb, dq, kb + 256);
            mma_qk1w(sb, dq + 2, kb + 258, 1);
            wg_commit();
            wg_wait<2>();
            fence_regs(sa);
            attn_piece<QMASK_0>(o, sa, c3, vb);
            wg_wait<2>();
            if (lane == 0 && (j > 0 || g0 > 0)) mbar_arrive(j > 0 ? eb + 8 * (j - 1) : eo + 24);
            attn_piece<QMASK_1>(o, sa + 16, c3, vb + 2 * PV_STEP64);
            if (j < 3) mbar_wait(fb + 8 * (j + 1), par);
            else {
                if (g0 < 28) mbar_wait(full0 + (half ^ 1) * 32, half ? par ^ 1 : par);
                if (g0 == 12) mbar_wait(empty0 + 8 * AT_STAGES + 8, 0);
            }
            wg_fence();
            { const uint64_t qq = j < 3 ? dq : dqw, kn = j < 3 ? dkh + (j + 1) * (AT_STAGE_BYTES >> 4) : dkn;
              mma_qk0w(sa, qq, kn);
              mma_qk1w(sa, qq + 2, kn + 2, 1); }
            wg_commit();
            wg_wait<2>();
            fence_regs(sb);
            attn_piece<QMASK_2>(o, sb, c3, vb + 4 * PV_STEP64);
            wg_wait<2>();
            attn_piece<QMASK_3>(o, sb + 16, c3, vb + 6 * PV_STEP64);
        }
        wg_wait<0>();
        fence_regs(sa);
        fence_regs(o);
    }
    attn_store_o(o, p, head, qchunk * 512 + pass * 256 + wg * 64 + warp * 16, lane);
    if (pass == 0) attn_housekeeping(p);
    }
}

__device__ __forceinline__ void attn_safe(const AttnParams& p, uint32_t base, uint32_t full0, uint32_t empty0, int head, int qchunk) {
    const int wg = __shfl_sync(0xffffffffu, threadIdx.x >> 7, 0), warp = (threadIdx.x >> 5) & 3, lane = threadIdx.x & 31;
    const uint32_t k_lo0 = desc_lo(base, 16), v_lo0 = desc_lo(base + 8192, AT_ONES_OFF - 8192);
#pragma unroll 1
    for (int pass = 0; pass < 2; pass++) {
        const uint32_t q = desc_lo(base + AT_Q_OFF + (pass * 256 + wg * 64) * 64, 16);
        float o[20];
#pragma unroll
        for (int i = 0; i < 20; i++) o[i] = 0.f;
        float m0 = -INFINITY, m1 = -INFINITY;
#pragma unroll 1
        for (int t = 0; t < 32; t++) {
            const int g = pass * 16 + (t >> 1), half = t & 1;
            const int st = g % AT_STAGES;
            const uint32_t kb = k_lo0 + st * (AT_STAGE_BYTES >> 4), vb = v_lo0 + st * 16 * PV_STEP;
            if (half == 0) { attn_refill(p, base, full0, empty0, g, head); mbar_wait(full0 + 8 * st, (g / AT_STAGES) & 1); }
            float cur[32];
            wg_fence();
            attn_qk(cur, q, kb + half * 256);
            wg_commit();
            wg_wait<0>();
            fence_regs(cur);
            float x0 = cur[0], x1 = cur[2];
#pragma unroll
            for (int i = 0; i < 8; i++) { x0 = fmaxf(x0, fmaxf(cur[4 * i], cur[4 * i + 1])); x1 = fmaxf(x1, fmaxf(cur[4 * i + 2], cur[4 * i + 3])); }
            x0 = fmaxf(x0, __shfl_xor_sync(0xffffffffu, x0, 1)); x1 = fmaxf(x1, __shfl_xor_sync(0xffffffffu, x1, 1));
            x0 = fmaxf(x0, __shfl_xor_sync(0xffffffffu, x0, 2)); x1 = fmaxf(x1, __shfl_xor_sync(0xffffffffu, x1, 2));
            const float n0 = fmaxf(m0, x0), n1 = fmaxf(m1, x1);
            const float a0 = ex2(m0 - n0), a1 = ex2(m1 - n1);
            m0 = n0; m1 = n1;
            uint32_t pr[16];
#pragma unroll
            for (int i = 0; i < 8; i++) {
                pr[2 * i] = pack_bf16(ex2(cur[4 * i] - n0), ex2(cur[4 * i + 1] - n0));
                pr[2 * i + 1] = pack_bf16(ex2(cur[4 * i + 2] - n1), ex2(cur[4 * i + 3] - n1));
            }
#pragma unroll
            for (int i = 0; i < 5; i++) { o[4 * i] *= a0; o[4 * i + 1] *= a0; o[4 * i + 2] *= a1; o[4 * i + 3] *= a1; }
            wg_fence();
            attn_pv(o, pr, vb + half * 4 * PV_STEP, 0);
            wg_commit();
            wg_wait<0>();
            fence_regs(o);
            if (half == 1 && lane == 0) mbar_arrive(empty0 + 8 * st);
        }
        attn_store_o(o, p, head, qchunk * 512 + pass * 256 + wg * 64 + warp * 16, lane);
        if (pass == 0) attn_housekeeping(p);
    }
}

__global__ void __launch_bounds__(512, 1) attn_kernel(const __grid_constant__ AttnParams p) {
    extern __shared__ __align__(1024) uint8_t smem_raw[];
    TL(2, 4);
    pdl_launch();
    const uint32_t base = smem_u32(smem_raw);
    const uint32_t full0 = base + AT_BAR_OFF, empty0 = full0 + 8 * AT_STAGES;
    const int head = blockIdx.x >> 2, qchunk = blockIdx.x & 3;
    if (threadIdx.x == 0) {
        if (base & 1023) __trap();
        prefetch_map(&p.kv); prefetch_map(&p.kv2);
        for (int i = 0; i < AT_STAGES; i++) { mbar_init(full0 + 8 * i, 1); mbar_init(empty0 + 8 * i, 16); }
        mbar_init(empty0 + 8 * AT_STAGES, 1); mbar_init(empty0 + 8 * AT_STAGES + 8, 1);
        fence_barrier_init();
    }
    if (threadIdx.x < 256) reinterpret_cast<uint32_t*>(smem_raw + AT_ONES_OFF)[threadIdx.x] = 0x3F803F80u;
    fence_proxy_async();
    const uint4* nrm = reinterpret_cast<const uint4*>(p.norm) + head * 32 + (threadIdx.x & 31);
    __syncthreads();
    pdl_wait();
    TL(2, 0);
    uint4 nq, nk, nv;
    asm volatile("ld.global.cg.v4.u32 {%0, %1, %2, %3}, [%4];" : "=r"(nq.x), "=r"(nq.y), "=r"(nq.z), "=r"(nq.w) : "l"(nrm) : "memory");
    asm volatile("ld.global.cg.v4.u32 {%0, %1, %2, %3}, [%4];" : "=r"(nk.x), "=r"(nk.y), "=r"(nk.z), "=r"(nk.w) : "l"(nrm + NH * 32) : "memory");
    asm volatile("ld.global.cg.v4.u32 {%0, %1, %2, %3}, [%4];" : "=r"(nv.x), "=r"(nv.y), "=r"(nv.z), "=r"(nv.w) : "l"(nrm + 2 * NH * 32) : "memory");
    if (threadIdx.x == 0) {
        const uint32_t qbar = empty0 + 8 * AT_STAGES;
        mbar_expect_tx(qbar, 16384);
        for (int i = 0; i < 2; i++) tma_ld2(base + AT_Q_OFF + i * 8192, &p.kv, qbar, 0, head * SEQ + qchunk * 512 + i * 128);
    }
    if (threadIdx.x == 128) {
        for (int g = 0; g < 4; g++) attn_issue_tile(p, base, full0, g, head);
        const uint32_t qbar = empty0 + 8 * AT_STAGES + 8;
        mbar_expect_tx(qbar, 16384);
        for (int i = 2; i < 4; i++) tma_ld2(base + AT_Q_OFF + i * 8192, &p.kv, qbar, 0, head * SEQ + qchunk * 512 + i * 128);
    }
    __syncwarp();
    const float qn = __uint_as_float(__reduce_max_sync(0xffffffffu, max(max(nq.x, nq.y), max(nq.z, nq.w))));
    const float kn = __uint_as_float(__reduce_max_sync(0xffffffffu, max(max(nk.x, nk.y), max(nk.z, nk.w))));
    const float vn = __uint_as_float(__reduce_max_sync(0xffffffffu, max(max(nv.x, nv.y), max(nv.z, nv.w))));
    const bool bounded = (qn * kn <= 1.0e4f) && (vn <= 1.0e9f) && (base & 0xFFFFFFu) == AT_BASE;
    mbar_wait(empty0 + 8 * AT_STAGES, 0);
    if (bounded) attn_fast(p, base, full0, empty0, head, qchunk);
    else {
        if (threadIdx.x == 0) for (int g = 4; g < AT_STAGES; g++) attn_issue_tile(p, base, full0, g, head);
        mbar_wait(empty0 + 8 * AT_STAGES + 8, 0);
        attn_safe(p, base, full0, empty0, head, qchunk);
    }
    TL(2, 3);
}

struct ResParams { CUtensorMap a, b, res, out; const bf16* bias; };
template <bool MIX2>
struct ResCfg {
    static constexpr int MB = 1, BN = 128, KSTEPS = MIX2 ? 56 : 16, STAGES = 6, A_BYTES = 16384, B_BYTES = 16384;
    static constexpr int STAGE_BYTES = A_BYTES + B_BYTES, STG_OFF = STAGES * STAGE_BYTES, BAR_OFF = STG_OFF + 32768, SMEM = BAR_OFF + 128;
    static constexpr int AUX_COUNT = 1, PRE = MIX2 ? MIX2_PRE : WO_PRE;
    static constexpr int TLK = MIX2 ? 6 : 3;
    static constexpr bool FIRST_BY_THREADS = false;
    static constexpr bool MC = false, ACC_INIT = true;
    static constexpr int FOLLOW = 0;
    static __device__ __forceinline__ void after_release(const ResParams&, const GemmSmem&, int, int, int) {}
    static __device__ __forceinline__ void producer_done(const GemmSmem&) {}
    static __device__ __forceinline__ void load_w(const ResParams& p, uint32_t sb, uint32_t bar, int k, int tm, int tn) {
        if (MIX2) tma_ld3(sb, &p.a, bar, 0, k * 64, tm * 2);
        else tma_ld3(sb + A_BYTES, &p.b, bar, 0, k * 64, tn * 2);
    }
    static __device__ __forceinline__ void load_x(const ResParams& p, uint32_t sb, uint32_t bar, int k, int tm, int tn) {
        if (MIX2) tma_ld2(sb + A_BYTES, &p.b, bar, k * 64, tn * 128);
        else tma_ld2(sb, &p.a, bar, k * 64, tm * 128);
    }
    static __device__ __forceinline__ void load_aux(const ResParams& p, const GemmSmem& s, int tm, int tn) {
        mbar_expect_tx(s.aux, 32768);
        tma_ld2(s.base + STG_OFF, &p.res, s.aux, tn * 128, tm * 128);
        tma_ld2(s.base + STG_OFF + 16384, &p.res, s.aux, tn * 128 + 64, tm * 128);
    }
    static __device__ __forceinline__ uint32_t desc_a(uint32_t sb, int wg, int m, int kk) {
        return MIX2 ? desc_lo(sb + wg * 8192 + kk * 2048, 8192) : desc_lo(sb + wg * 8192 + kk * 32, 16);
    }
    static __device__ __forceinline__ uint32_t desc_b(uint32_t sb, int kk) {
        return MIX2 ? desc_lo(sb + A_BYTES + kk * 32, 16) : desc_lo(sb + A_BYTES + kk * 2048, 8192);
    }
    static __device__ __forceinline__ void mma(float (&d)[64], uint32_t a, uint32_t b, int sc) {
        if (MIX2) mma_mix2(d, a, b, sc); else mma_wo(d, a, b, sc);
    }
};
template <bool MIX2>
__global__ void __launch_bounds__(384, 1) res_gemm_kernel(const __grid_constant__ ResParams p) {
    using C = ResCfg<MIX2>;
    extern __shared__ __align__(1024) uint8_t smem_raw[];
    TL(MIX2 ? 6 : 3, 4);
    if (!MIX2) pdl_launch();
    const int tm = blockIdx.x >> 3, tn = blockIdx.x & 7;
    if (threadIdx.x == 0) { prefetch_map(&p.a); prefetch_map(&p.b); prefetch_map(&p.res); prefetch_map(&p.out); }
    const GemmSmem s = gemm_setup<C>(smem_raw);
    const int wgi = __shfl_sync(0xffffffffu, threadIdx.x >> 7, 0);
    if (wgi == 0) {
        reg_dealloc<40>();
        if (threadIdx.x < 32) {
            if (threadIdx.x == 0) gemm_producer<C>(s, p, tm, tn);
            __syncwarp();
#pragma unroll 1
            for (int i = 0; i < 4; i++) {
                constexpr bool SKEWED = (MIX2 ? MIX2_SKEW : WO_SKEW) > 0;
                const int b = SKEWED ? i & 1 : i >> 1, wg = SKEWED ? i >> 1 : i & 1;
                take_over(2 + b * 2 + wg);
                if (threadIdx.x == 0) tma_st2(&p.out, s.base + C::STG_OFF + b * 16384 + wg * 8192, tn * 128 + b * 64, tm * 128 + wg * 64);
            }
            if (threadIdx.x == 0) { tma_st_commit(); tma_st_wait(); TL(MIX2 ? 6 : 3, 3); }
        }
    } else {
        reg_alloc<232>();
        const int wg = wgi - 1, warp = (threadIdx.x >> 5) & 3, lane = threadIdx.x & 31;
        const int r0 = wg * 64 + warp * 16 + (lane >> 2);
        const int arow = wg * 64 + warp * 16 + ((lane >> 3) & 1) * 8 + (lane & 7);
        const uint32_t stg = s.base + C::STG_OFF + arow * 128;
        float acc[1][64];
        {
            float a0 = 1.f, a1 = 1.f, c0 = 0.f, c1 = 0.f;
            if (MIX2) {
                const float2 t0 = __ldcg(&g_rowln[tm * 128 + r0]), t1 = __ldcg(&g_rowln[tm * 128 + r0 + 8]);
                a0 = t0.y; a1 = t1.y;
                c0 = t0.x + __bfloat162float(p.bias[tm * 128 + r0]); c1 = t1.x + __bfloat162float(p.bias[tm * 128 + r0 + 8]);
            }
            mbar_wait(s.aux, 0);
#pragma unroll
            for (int jp = 0; jp < 8; jp++) {
                const int chunk = jp * 2 + (lane >> 4);
                uint32_t r[4];
                ldmatrix_x4(stg + (chunk >> 3) * 16384 + (((chunk & 7) ^ (arow & 7)) << 4), r);
#pragma unroll
                for (int i = 0; i < 4; i++) {
                    const float a = (i & 1) ? a1 : a0, c = (i & 1) ? c1 : c0;
                    acc[0][jp * 8 + 2 * i] = MIX2 ? fmaf(bf_lo(r[i]), a, c) : bf_lo(r[i]);
                    acc[0][jp * 8 + 2 * i + 1] = MIX2 ? fmaf(bf_hi(r[i]), a, c) : bf_hi(r[i]);
                }
            }
        }
        pdl_wait();
        TL(MIX2 ? 6 : 3, 0);
        constexpr int SK = MIX2 ? MIX2_SKEW : WO_SKEW;
        gemm_mainloop<C, C::KSTEPS, SK>(s, wg, acc, MIX2 ? 6 : 3);
        TL(MIX2 ? 6 : 3, 1);
        float sc0 = 1.f, sc1 = 1.f, of0 = 0.f, of1 = 0.f;
        if (!MIX2) {
            float s0 = 0.f, s1 = 0.f;
#pragma unroll
            for (int j = 0; j < 16; j++) { s0 += acc[0][4 * j] + acc[0][4 * j + 1]; s1 += acc[0][4 * j + 2] + acc[0][4 * j + 3]; }
            s0 += __shfl_xor_sync(0xffffffffu, s0, 1); s1 += __shfl_xor_sync(0xffffffffu, s1, 1);
            s0 += __shfl_xor_sync(0xffffffffu, s0, 2); s1 += __shfl_xor_sync(0xffffffffu, s1, 2);
            const float m0 = s0 * (1.f / 128), m1 = s1 * (1.f / 128);
            float q0 = 0.f, q1 = 0.f;
#pragma unroll
            for (int j = 0; j < 16; j++) {
                const float a = acc[0][4 * j] - m0, b = acc[0][4 * j + 1] - m0, c = acc[0][4 * j + 2] - m1, d = acc[0][4 * j + 3] - m1;
                q0 = fmaf(a, a, fmaf(b, b, q0)); q1 = fmaf(c, c, fmaf(d, d, q1));
            }
            q0 += __shfl_xor_sync(0xffffffffu, q0, 1); q1 += __shfl_xor_sync(0xffffffffu, q1, 1);
            q0 += __shfl_xor_sync(0xffffffffu, q0, 2); q1 += __shfl_xor_sync(0xffffffffu, q1, 2);
            const int wrow = tm * 128 + wg * 64 + warp * 16;
            if ((lane & 3) < 2) {
                const float m = (lane & 1) ? m1 : m0, q = (lane & 1) ? q1 : q0;
                const unsigned long long w = ((unsigned long long)(__float_as_uint(q) | 0x80000000u) << 32) | __float_as_uint(m);
                asm volatile("st.relaxed.gpu.global.u64 [%0], %1;" :: "l"(g_hpart + tn * SEQ + wrow + (lane >> 2) + (lane & 1) * 8), "l"(w) : "memory");
            }
            TL(3, 5);
            TKC(13);
            const unsigned long long* part = g_hpart + (lane >> 2) * SEQ + wrow + (lane & 3) * 4;
            unsigned long long t[4];
            int it = 0;
            bool ok;
            do {
                asm volatile("ld.relaxed.gpu.global.v2.u64 {%0, %1}, [%2];" : "=l"(t[0]), "=l"(t[1]) : "l"(part) : "memory");
                asm volatile("ld.relaxed.gpu.global.v2.u64 {%0, %1}, [%2];" : "=l"(t[2]), "=l"(t[3]) : "l"(part + 2) : "memory");
                ok = (long long)(t[0] & t[1] & t[2] & t[3]) < 0;
                if (++it > (1 << 20)) __trap();
            } while (!__all_sync(0xffffffffu, ok));
            TKC(14);
            float mt[4], qt[4];
#pragma unroll
            for (int i = 0; i < 4; i++) {
                const float mi = __uint_as_float((uint32_t)t[i]), qi = __uint_as_float((uint32_t)(t[i] >> 32) & 0x7FFFFFFFu);
                float m = mi;
                m += __shfl_xor_sync(0xffffffffu, m, 4); m += __shfl_xor_sync(0xffffffffu, m, 8); m += __shfl_xor_sync(0xffffffffu, m, 16);
                m *= 0.125f;
                float q = fmaf(128.f * (mi - m), mi - m, qi);
                q += __shfl_xor_sync(0xffffffffu, q, 4); q += __shfl_xor_sync(0xffffffffu, q, 8); q += __shfl_xor_sync(0xffffffffu, q, 16);
                mt[i] = m; qt[i] = q;
            }
            const int sel = (lane >> 2) & 3;
            const float mean = sel == 0 ? mt[0] : sel == 1 ? mt[1] : sel == 2 ? mt[2] : mt[3];
            const float var = (sel == 0 ? qt[0] : sel == 1 ? qt[1] : sel == 2 ? qt[2] : qt[3]) * (1.f / DM);
            const float r1 = rsqrtf(var + 1e-5f);
            const float r2 = rsqrtf(var * r1 * r1 + 1e-5f);
            const float scale = 0.5f * r1 * r2, off = -mean * scale;
            if (tn == 0 && lane < 16) g_rowln[wrow + 4 * (lane & 3) + sel] = make_float2(mean, 1.f / scale);
            const int ra = lane >> 2, src0 = ((ra & 3) << 2) | (ra >> 2);
            sc0 = __shfl_sync(0xffffffffu, scale, src0); of0 = __shfl_sync(0xffffffffu, off, src0);
            sc1 = __shfl_sync(0xffffffffu, scale, src0 + 2); of1 = __shfl_sync(0xffffffffu, off, src0 + 2);
        }
#pragma unroll
        for (int jp = 0; jp < 8; jp++) {
            const int chunk = jp * 2 + (lane >> 4);
            uint32_t r[4];
#pragma unroll
            for (int i = 0; i < 4; i++) {
                const float sc = (i & 1) ? sc1 : sc0, of = (i & 1) ? of1 : of0;
                const float v0 = acc[0][jp * 8 + 2 * i], v1 = acc[0][jp * 8 + 2 * i + 1];
                r[i] = MIX2 ? pack_bf16(v0, v1) : pack_bf16(fmaf(v0, sc, of), fmaf(v1, sc, of));
            }
            stmatrix_x4(stg + (chunk >> 3) * 16384 + (((chunk & 7) ^ (arow & 7)) << 4), r[0], r[1], r[2], r[3]);
            if ((jp & 3) == 3) hand_over(2 + (jp >> 2) * 2 + wg);
        }
        if (MIX2) TL(6, 5);
        TKC(15);
    }
}

struct Mix1Params { CUtensorMap hn, w1, out; const bf16* bias; const uint8_t* pf; };
struct Mix1Cfg {
    static constexpr int MB = 1, BN = 224, KSTEPS = 32, STAGES = 5, A_BYTES = 16384, B_BYTES = 28672;
    static constexpr int STAGE_BYTES = A_BYTES + B_BYTES, BAR_OFF = STAGES * STAGE_BYTES, SMEM = BAR_OFF + 128;
    static constexpr int AUX_COUNT = 1, PRE = MIX1_PRE;
    static constexpr int TLK = 5;
    static constexpr bool MC = true, ACC_INIT = true, FIRST_BY_THREADS = false;
    static constexpr int FOLLOW = 0;
    static __device__ __forceinline__ void after_release(const Mix1Params&, const GemmSmem&, int, int, int) {}
    static __device__ __forceinline__ void producer_done(const GemmSmem&) {}
    static __device__ __forceinline__ void load_w(const Mix1Params& p, uint32_t sb, uint32_t bar, int k, int tm, int tn) {
        tma_ld3_mc(sb + A_BYTES + (tm & 1) * (B_BYTES / 2), &p.w1, bar, 0, k * 64 + (tm & 1) * 32, tn * 7);
    }
    static __device__ __forceinline__ void load_x(const Mix1Params& p, uint32_t sb, uint32_t bar, int k, int tm, int tn) { tma_ld3(sb, &p.hn, bar, 0, k * 64, tm * 2); }
    static __device__ __forceinline__ void load_aux(const Mix1Params&, const GemmSmem&, int, int) {}
    static __device__ __forceinline__ uint32_t desc_a(uint32_t sb, int wg, int m, int kk) { return desc_lo(sb + wg * 8192 + kk * 2048, 8192); }
    static __device__ __forceinline__ uint32_t desc_b(uint32_t sb, int kk) { return desc_lo(sb + A_BYTES + (kk >> 1) * (B_BYTES / 2) + (kk & 1) * 1024, 2048); }
    static __device__ __forceinline__ void mma(float (&d)[112], uint32_t a, uint32_t b, int sc) { mma_mix1(d, a, b, sc); }
    static __device__ __forceinline__ uint32_t stage_off(int wg) { return (2 + wg) * STAGE_BYTES; }
};
__global__ void __launch_bounds__(384, 1) mix1_kernel(const __grid_constant__ Mix1Params p) {
    using C = Mix1Cfg;
    extern __shared__ __align__(1024) uint8_t smem_raw[];
    TL(5, 4);
    const int tm = blockIdx.x & 7, tn = blockIdx.x >> 3;
    if (threadIdx.x == 0) { prefetch_map(&p.hn); prefetch_map(&p.w1); prefetch_map(&p.out); }
    const GemmSmem s = gemm_setup<C>(smem_raw, [](const GemmSmem& g) { asm volatile("st.shared.f32 [%0], %1;" :: "r"(g.aux + 16), "f"(2.f * 0.7978845608029f) : "memory"); });
    const int wgi = __shfl_sync(0xffffffffu, threadIdx.x >> 7, 0);
    if (wgi == 0) {
        reg_dealloc<40>();
        if (threadIdx.x < 32) {
            if (threadIdx.x == 0) gemm_producer<C>(s, p, tm, tn);
            __syncwarp();
#pragma unroll 1
            for (int i = 0; i < 8; i++) {
                const int wg = i >> 2, b = MIX1_PAT ? max((i & 3) * 2 - 1, 0) : (i & 3) * 2;
                take_over(2 + i);
                if (threadIdx.x == 0) {
                    tma_st3(&p.out, s.base + C::stage_off(wg) + b * 4096, 0, tm * 128 + wg * 64, tn * 7 + b);
                    if (MIX1_PAT ? (i & 3) != 0 : b < 6) tma_st3(&p.out, s.base + C::stage_off(wg) + (b + 1) * 4096, 0, tm * 128 + wg * 64, tn * 7 + b + 1);
                }
            }
            if (threadIdx.x == 0) { tma_st_commit(); tma_st_wait(); TL(5, 3); }
        } else if (threadIdx.x < 64) {
            pdl_wait();
            __nanosleep(PF_W2_DELAY);
#pragma unroll 1
            for (int i = 0; i < 4; i++) prefetch_line(p.pf + ((size_t)blockIdx.x * 128 + i * 32 + (threadIdx.x & 31)) * 128);
        }
    } else {
        reg_alloc<232>();
        const int wg = wgi - 1, warp = (threadIdx.x >> 5) & 3, lane = threadIdx.x & 31;
        float acc[1][112];
        {
            const uint32_t* bp = reinterpret_cast<const uint32_t*>(p.bias + tn * 224) + (lane & 3);
#pragma unroll
            for (int j = 0; j < 28; j++) {
                const uint32_t b2 = __ldg(bp + j * 4);
                acc[0][4 * j] = acc[0][4 * j + 2] = 0.5f * bf_lo(b2);
                acc[0][4 * j + 1] = acc[0][4 * j + 3] = 0.5f * bf_hi(b2);
            }
        }
        pdl_wait();
        pdl_launch();
        TL(5, 0);
        const int arow = warp * 16 + ((lane >> 3) & 1) * 8 + (lane & 7);
        float c1 = 0.f;
        auto next_piece = [&]() { c1 = MIX1_PIN ? lds_f32(s.aux + 16) : 2.f * 0.7978845608029f; };
        auto out_pair = [&](int jp, uint32_t stg) {
            float v[8];
#pragma unroll
            for (int i = 0; i < 8; i++) {
                const float hx = acc[0][jp * 8 + i];
                v[i] = fmaf(hx, tanh_fast(hx * fmaf(hx * hx, 8.f * 0.0356774081363f, c1)), hx);
            }
            const int j = (jp & 1) * 2 + (lane >> 4);
            stmatrix_x4(stg + arow * 64 + ((j ^ ((arow >> 1) & 3)) << 4), pack_bf16(v[0], v[1]), pack_bf16(v[2], v[3]), pack_bf16(v[4], v[5]), pack_bf16(v[6], v[7]));
        };
        gemm_mainloop<C, 32, MIX1_SKEW, true>(s, wg, acc, 5);
        TKW(2);
        TL(5, 1);
        if (wg == 0) { named_arrive(12, 256); named_bar(10, 256); }
        else named_bar(12, 256);
#pragma unroll
        for (int jp = 0; jp < 14; jp++) {
            const int jq = jp + MIX1_PAT * 2;
            if (jp == 0 || (jq & 3) == 0) next_piece();
            out_pair(jp, s.base + C::stage_off(wg) + (jp >> 1) * 4096);
            if ((jq & 3) == 3 || jp == 13) hand_over(2 + wg * 4 + (jq >> 2));
        }
        TKW(3);
        TL(5, 5);
    }
}

typedef CUresult (*EncodeFn)(CUtensorMap*, CUtensorMapDataType, cuuint32_t, void*, const cuuint64_t*, const cuuint64_t*, const cuuint32_t*,
                             const cuuint32_t*, CUtensorMapInterleave, CUtensorMapSwizzle, CUtensorMapL2promotion, CUtensorMapFloatOOBfill);
EncodeFn g_encode;

void make_map(CUtensorMap* m, const void* ptr, int rank, const uint64_t* dims, const uint64_t* strides_bytes, const uint32_t* box, CUtensorMapSwizzle swz) {
    cuuint64_t d[5], st[5]; cuuint32_t b[5], es[5];
    for (int i = 0; i < rank; i++) { d[i] = dims[i]; b[i] = box[i]; es[i] = 1; }
    for (int i = 0; i + 1 < rank; i++) st[i] = strides_bytes[i];
    CUresult r = g_encode(m, CU_TENSOR_MAP_DATA_TYPE_BFLOAT16, rank, const_cast<void*>(ptr), d, st, b, es, CU_TENSOR_MAP_INTERLEAVE_NONE, swz,
                          CU_TENSOR_MAP_L2_PROMOTION_L2_128B, CU_TENSOR_MAP_FLOAT_OOB_FILL_NONE);
    if (r != CUDA_SUCCESS) fprintf(stderr, "cuTensorMapEncodeTiled failed: %d\n", (int)r);
}
void map2d(CUtensorMap* m, const void* ptr, uint64_t cols, uint64_t rows, uint32_t bc, uint32_t br, CUtensorMapSwizzle swz, uint64_t pitch = 0) {
    uint64_t dims[2] = {cols, rows}, st[1] = {(pitch ? pitch : cols) * 2}; uint32_t box[2] = {bc, br};
    make_map(m, ptr, 2, dims, st, box, swz);
}
void map3d(CUtensorMap* m, const void* ptr, uint64_t cols, uint64_t rows, uint32_t inner, uint32_t br, uint32_t nblk, CUtensorMapSwizzle swz, uint64_t pitch = 0) {
    uint64_t dims[3] = {inner, rows, cols / inner}, st[2] = {(pitch ? pitch : cols) * 2, (uint64_t)inner * 2}; uint32_t box[3] = {inner, br, nblk};
    make_map(m, ptr, 3, dims, st, box, swz);
}

template <class... KArgs, class... Args>
void launch(void (*kern)(KArgs...), int grid, int block, int smem, bool pdl, bool pair, Args&&... args) {
    cudaLaunchConfig_t cfg = {};
    cfg.gridDim = dim3(grid); cfg.blockDim = dim3(block); cfg.dynamicSmemBytes = smem; cfg.stream = 0;
    cudaLaunchAttribute at[2];
    int n = 0;
    if (pdl) { at[n].id = cudaLaunchAttributeProgrammaticStreamSerialization; at[n].val.programmaticStreamSerializationAllowed = 1; n++; }
    if (pair) { at[n].id = cudaLaunchAttributeClusterDimension; at[n].val.clusterDim.x = 2; at[n].val.clusterDim.y = 1; at[n].val.clusterDim.z = 1; n++; }
    cfg.attrs = at; cfg.numAttrs = n;
    cudaError_t e = cudaLaunchKernelEx(&cfg, kern, KArgs(args)...);
    if (e != cudaSuccess) fprintf(stderr, "launch failed: %s\n", cudaGetErrorString(e));
}

struct HostState {
    bool ready;
    const void* key[9];
    QkvParams qkv; AttnParams attn; ResParams wo, mix2; Mix1Params mix1;
    bf16 *qkvp, *o, *hn, *u;
};
HostState g_hs;

}

extern "C" void kernel_launch(void* const* d_in, const int* in_sizes, int n_in, void* d_out, int out_size) {
    const bf16* x = (const bf16*)d_in[0];
    const bf16* wqkv = (const bf16*)d_in[1];
    const bf16* wo = (const bf16*)d_in[2];
    const bf16* w1 = (const bf16*)d_in[4];
    const bf16* b1 = (const bf16*)d_in[5];
    const bf16* w2 = (const bf16*)d_in[6];
    const bf16* b2 = (const bf16*)d_in[7];
    HostState& hs = g_hs;
    bool same = hs.ready;
    for (int i = 0; i < 8 && same; i++) same = (hs.key[i] == d_in[i]);
    same = same && hs.key[8] == d_out;
    if (!same) {
        if (!g_encode) {
            void* fn = nullptr; cudaDriverEntryPointQueryResult qr;
            cudaGetDriverEntryPoint("cuTensorMapEncodeTiled", &fn, cudaEnableDefault, &qr);
            g_encode = (EncodeFn)fn;
            cudaFuncSetAttribute(qkv_kernel, cudaFuncAttributeMaxDynamicSharedMemorySize, QkvCfg::SMEM);
            cudaFuncSetAttribute(attn_kernel, cudaFuncAttributeMaxDynamicSharedMemorySize, AT_SMEM);
            cudaFuncSetAttribute(res_gemm_kernel<false>, cudaFuncAttributeMaxDynamicSharedMemorySize, ResCfg<false>::SMEM);
            cudaFuncSetAttribute(res_gemm_kernel<true>, cudaFuncAttributeMaxDynamicSharedMemorySize, ResCfg<true>::SMEM);
            cudaFuncSetAttribute(mix1_kernel, cudaFuncAttributeMaxDynamicSharedMemorySize, Mix1Cfg::SMEM);
        }
        cudaGetSymbolAddress((void**)&hs.qkvp, g_qkv); cudaGetSymbolAddress((void**)&hs.o, g_o);
        cudaGetSymbolAddress((void**)&hs.hn, g_hn); cudaGetSymbolAddress((void**)&hs.u, g_u);
        const CUtensorMapSwizzle S128 = CU_TENSOR_MAP_SWIZZLE_128B, S64 = CU_TENSOR_MAP_SWIZZLE_64B;
        map2d(&hs.qkv.x, x, DM, SEQ, 64, 128, S128);
        hs.qkv.xp = x; hs.qkv.wp = wqkv;
        {
            uint64_t dims[4] = {64, (uint64_t)DM, 3, 16}, st[3] = {3 * DM * 2, DM * 2, 128}; uint32_t box[4] = {64, 32, 3, 1};
            make_map(&hs.qkv.w, wqkv, 4, dims, st, box, S128);
        }
        map2d(&hs.qkv.out, hs.qkvp, HD, 3 * NH * SEQ, 32, 64, S64);
        map2d(&hs.attn.kv, hs.qkvp, HD, 3 * NH * SEQ, 32, 128, S64);
        hs.attn.optr = hs.o;
        {
            uint64_t dims[3] = {(uint64_t)HD, (uint64_t)NH * SEQ, 3}, st[2] = {HD * 2, (uint64_t)NH * SEQ * HD * 2}; uint32_t box[3] = {32, 128, 2};
            make_map(&hs.attn.kv2, hs.qkvp, 3, dims, st, box, S64);
        }
        map2d(&hs.wo.a, hs.o, DM, SEQ, 64, 128, S128, PITCH);
        map3d(&hs.wo.b, wo, DM, DM, 64, 64, 2, S128);
        map2d(&hs.wo.res, x, DM, SEQ, 64, 128, S128);
        map2d(&hs.wo.out, hs.hn, DM, SEQ, 64, 64, S128, PITCH);
        hs.wo.bias = nullptr;
        map3d(&hs.mix1.hn, hs.hn, DM, SEQ, 64, 64, 2, S128, PITCH);
        map3d(&hs.mix1.w1, w1, FF, SEQ, 32, 32, 7, S64);
        hs.mix1.pf = (const uint8_t*)w2;
        hs.attn.dbase = 0x8000002000000000ull;
        cudaGetSymbolAddress((void**)&hs.attn.norm, g_norm); cudaGetSymbolAddress(&hs.attn.colsum2, g_colsum2); cudaGetSymbolAddress(&hs.attn.rowstat2, g_rowstat2);
        cudaGetSymbolAddress(&hs.attn.hpart, g_hpart);
        hs.attn.pf_wo = (const uint8_t*)wo; hs.attn.pf_w1 = (const uint8_t*)w1; hs.attn.pf_b1 = (const uint8_t*)b1;
        map3d(&hs.mix1.out, hs.u, FF, DM, 32, 64, 1, S64);
        hs.mix1.bias = b1;
        map3d(&hs.mix2.a, w2, SEQ, FF, 64, 64, 2, S128);
        map2d(&hs.mix2.b, hs.u, FF, DM, 64, 128, S128);
        map2d(&hs.mix2.res, hs.hn, DM, SEQ, 64, 128, S128, PITCH);
        map2d(&hs.mix2.out, d_out, DM, SEQ, 64, 64, S128);
        hs.mix2.bias = b2;
        for (int i = 0; i < 8; i++) hs.key[i] = d_in[i];
        hs.key[8] = d_out;
        hs.ready = true;
    }
    launch(qkv_kernel, 128, 384, QkvCfg::SMEM, false, true, hs.qkv);
    launch(attn_kernel, 128, 512, AT_SMEM, true, false, hs.attn);
    launch(res_gemm_kernel<false>, 128, 384, ResCfg<false>::SMEM, true, true, hs.wo);
    launch(mix1_kernel, 128, 384, Mix1Cfg::SMEM, true, true, hs.mix1);
    launch(res_gemm_kernel<true>, 128, 384, ResCfg<true>::SMEM, true, true, hs.mix2);
}
```

```cpp
#include <cuda_runtime.h>
#include <cuda_bf16.h>
#include <cuda.h>
#include <stdint.h>
#include <stdio.h>

typedef __nv_bfloat16 bf16;

namespace {

#define MIX1_PRE 1
#define WO_PRE 1
#define MIX2_PRE 1
#define PF_W2_DELAY 10000
#define QMASK_0 0xF0
#define QMASK_1 0xF0
#define QMASK_2 0xF0
#define QMASK_3 0xF0
#define MIX1_SKEW 4
#define MIX1_PAT 1
#define MIX1_PIN 1
#define QKV3_R1 10
#define QKV2_E0 5
#define QKV_FIRST 1
#define ATTN_UNR 1
#define QKV3_PF 7
#define MIX2_SKEW 4
#define WO_SKEW 4
#define QKV2_SKEW 1
#define PITCH_PAD 64
constexpr int PITCH = 1024 + PITCH_PAD;
constexpr int SEQ = 2048, DM = 1024, NH = 32, HD = 32, FF = 3584;

__device__ __align__(1024) bf16 g_qkv[3 * NH * SEQ * HD];
__device__ __align__(1024) bf16 g_o[SEQ * PITCH];
__device__ __align__(1024) bf16 g_hn[SEQ * PITCH];
__device__ __align__(1024) bf16 g_u[DM * FF];
__device__ __align__(16) uint32_t g_norm[3 * NH * 128];
__device__ float2 g_rowln[SEQ];
__device__ __align__(16) unsigned long long g_hpart[SEQ * 8];
__device__ __align__(16) unsigned long long g_rowstat2[SEQ];
__device__ __align__(16) uint32_t g_colsum2[8 * 3 * DM];

__device__ __forceinline__ uint32_t smem_u32(const void* p) { return (uint32_t)__cvta_generic_to_shared(p); }
__device__ __forceinline__ void mbar_init(uint32_t bar, uint32_t cnt) { asm volatile("mbarrier.init.shared::cta.b64 [%0], %1;" :: "r"(bar), "r"(cnt) : "memory"); }
__device__ __forceinline__ void mbar_expect_tx(uint32_t bar, uint32_t bytes) { asm volatile("mbarrier.arrive.expect_tx.shared::cta.b64 _, [%0], %1;" :: "r"(bar), "r"(bytes) : "memory"); }
__device__ __forceinline__ void mbar_arrive(uint32_t bar) { asm volatile("mbarrier.arrive.shared::cta.b64 _, [%0];" :: "r"(bar) : "memory"); }
__device__ __forceinline__ void mbar_wait(uint32_t bar, uint32_t parity) {
    asm volatile("{\n.reg .pred p;\nWAIT_%=:\nmbarrier.try_wait.parity.shared::cta.b64 p, [%0], %1;\n@p bra DONE_%=;\nbra WAIT_%=;\nDONE_%=:\n}" :: "r"(bar), "r"(parity) : "memory");
}
__device__ __forceinline__ bool elect_one() { uint32_t p; asm volatile("{\n.reg .pred q;\nelect.sync _|q, 0xffffffff;\nselp.u32 %0, 1, 0, q;\n}" : "=r"(p)); return p != 0; }
__device__ __forceinline__ void fence_barrier_init() { asm volatile("fence.mbarrier_init.release.cluster;" ::: "memory"); }
__device__ __forceinline__ void fence_proxy_async() { asm volatile("fence.proxy.async.shared::cta;" ::: "memory"); }
__device__ __forceinline__ void pdl_launch() { asm volatile("griddepcontrol.launch_dependents;" ::: "memory"); }
__device__ __forceinline__ void pdl_wait() { asm volatile("griddepcontrol.wait;" ::: "memory"); }
__device__ __forceinline__ void named_bar(int id, int n) { asm volatile("bar.sync %0, %1;" :: "r"(id), "r"(n) : "memory"); }
__device__ __forceinline__ void named_arrive(int id, int n) { asm volatile("bar.arrive %0, %1;" :: "r"(id), "r"(n) : "memory"); }
__device__ __forceinline__ void hand_over(int id) { named_arrive(id, 160); }
__device__ __forceinline__ void take_over(int id) { named_bar(id, 160); fence_proxy_async(); }
__device__ __forceinline__ void prefetch_map(const CUtensorMap* m) { asm volatile("prefetch.tensormap [%0];" :: "l"(m) : "memory"); }

__device__ __forceinline__ void tma_ld2(uint32_t dst, const CUtensorMap* m, uint32_t bar, int c0, int c1) {
    asm volatile("cp.async.bulk.tensor.2d.shared::cluster.global.mbarrier::complete_tx::bytes [%0], [%1, {%3, %4}], [%2];"
                 :: "r"(dst), "l"(m), "r"(bar), "r"(c0), "r"(c1) : "memory");
}
__device__ __forceinline__ void tma_ld3(uint32_t dst, const CUtensorMap* m, uint32_t bar, int c0, int c1, int c2) {
    asm volatile("cp.async.bulk.tensor.3d.shared::cluster.global.mbarrier::complete_tx::bytes [%0], [%1, {%3, %4, %5}], [%2];"
                 :: "r"(dst), "l"(m), "r"(bar), "r"(c0), "r"(c1), "r"(c2) : "memory");
}
__device__ __forceinline__ void tma_ld3_mc(uint32_t dst, const CUtensorMap* m, uint32_t bar, int c0, int c1, int c2) {
    asm volatile("cp.async.bulk.tensor.3d.shared::cluster.global.mbarrier::complete_tx::bytes.multicast::cluster [%0], [%1, {%3, %4, %5}], [%2], %6;"
                 :: "r"(dst), "l"(m), "r"(bar), "r"(c0), "r"(c1), "r"(c2), "h"((uint16_t)3) : "memory");
}
__device__ __forceinline__ void tma_ld4_mc(uint32_t dst, const CUtensorMap* m, uint32_t bar, int c0, int c1, int c2, int c3) {
    asm volatile("cp.async.bulk.tensor.4d.shared::cluster.global.mbarrier::complete_tx::bytes.multicast::cluster [%0], [%1, {%3, %4, %5, %6}], [%2], %7;"
                 :: "r"(dst), "l"(m), "r"(bar), "r"(c0), "r"(c1), "r"(c2), "r"(c3), "h"((uint16_t)3) : "memory");
}
__device__ __forceinline__ void prefetch_line(const void* p) { asm volatile("prefetch.global.L2 [%0];" :: "l"(p)); }
__device__ __forceinline__ uint32_t mapa(uint32_t addr, uint32_t cta) { uint32_t r; asm("mapa.shared::cluster.u32 %0, %1, %2;" : "=r"(r) : "r"(addr), "r"(cta)); return r; }
__device__ __forceinline__ void mbar_arrive_cluster(uint32_t bar) { asm volatile("mbarrier.arrive.shared::cluster.b64 _, [%0];" :: "r"(bar) : "memory"); }
__device__ __forceinline__ void cluster_arrive() { asm volatile("barrier.cluster.arrive.relaxed.aligned;" ::: "memory"); }
__device__ __forceinline__ void cluster_wait() { asm volatile("barrier.cluster.wait.aligned;" ::: "memory"); }
__device__ __forceinline__ void tma_st2(const CUtensorMap* m, uint32_t src, int c0, int c1) {
    asm volatile("cp.async.bulk.tensor.2d.global.shared::cta.bulk_group [%0, {%2, %3}], [%1];" :: "l"(m), "r"(src), "r"(c0), "r"(c1) : "memory");
}
__device__ __forceinline__ void tma_st3(const CUtensorMap* m, uint32_t src, int c0, int c1, int c2) {
    asm volatile("cp.async.bulk.tensor.3d.global.shared::cta.bulk_group [%0, {%2, %3, %4}], [%1];" :: "l"(m), "r"(src), "r"(c0), "r"(c1), "r"(c2) : "memory");
}
__device__ __forceinline__ void tma_st_commit() { asm volatile("cp.async.bulk.commit_group;" ::: "memory"); }
__device__ __forceinline__ void tma_st_wait() { asm volatile("cp.async.bulk.wait_group.read 0;" ::: "memory"); }

__device__ __forceinline__ void wg_fence() { asm volatile("wgmma.fence.sync.aligned;" ::: "memory"); }
__device__ __forceinline__ void wg_commit() { asm volatile("wgmma.commit_group.sync.aligned;" ::: "memory"); }
template <int N> __device__ __forceinline__ void wg_wait() { asm volatile("wgmma.wait_group.sync.aligned %0;" :: "n"(N) : "memory"); }
template <int R> __device__ __forceinline__ void reg_alloc() { asm volatile("setmaxnreg.inc.sync.aligned.u32 %0;" :: "n"(R)); }
template <int R> __device__ __forceinline__ void reg_dealloc() { asm volatile("setmaxnreg.dec.sync.aligned.u32 %0;" :: "n"(R)); }
__device__ __forceinline__ float lds_f32(uint32_t a) { float v; asm volatile("ld.volatile.shared.f32 %0, [%1];" : "=f"(v) : "r"(a) : "memory"); return v; }
template <int N> __device__ __forceinline__ void fence_regs(float (&d)[N]) {
#pragma unroll
    for (int i = 0; i < N; i++) asm volatile("" : "+f"(d[i]) :: "memory");
}

__device__ __forceinline__ uint32_t desc_lo(uint32_t addr, uint32_t lbo) { return ((addr & 0x3FFFFu) >> 4) | ((lbo >> 4) << 16); }
__device__ __forceinline__ uint32_t pack_bf16(float lo, float hi) { uint32_t d; asm("cvt.rn.bf16x2.f32 %0, %1, %2;" : "=r"(d) : "f"(hi), "f"(lo)); return d; }
__device__ __forceinline__ float bf_lo(uint32_t v) { return __uint_as_float(v << 16); }
__device__ __forceinline__ float bf_hi(uint32_t v) { return __uint_as_float(v & 0xFFFF0000u); }
__device__ __forceinline__ void stmatrix_x4(uint32_t addr, uint32_t r0, uint32_t r1, uint32_t r2, uint32_t r3) {
    asm volatile("stmatrix.sync.aligned.m8n8.x4.shared.b16 [%0], {%1, %2, %3, %4};" :: "r"(addr), "r"(r0), "r"(r1), "r"(r2), "r"(r3));
}
__device__ __forceinline__ void ldmatrix_x4(uint32_t addr, uint32_t (&r)[4]) {
    asm volatile("ldmatrix.sync.aligned.m8n8.x4.shared.b16 {%0, %1, %2, %3}, [%4];" : "=r"(r[0]), "=r"(r[1]), "=r"(r[2]), "=r"(r[3]) : "r"(addr) : "memory");
}
__device__ __forceinline__ float ex2(float x) { float y; asm("ex2.approx.ftz.f32 %0, %1;" : "=f"(y) : "f"(x)); return y; }
__device__ __forceinline__ float tanh_fast(float x) { float y; asm("tanh.approx.f32 %0, %1;" : "=f"(y) : "f"(x)); return y; }

__device__ __forceinline__ void mma_qkv(float (&d)[96], uint32_t alo, uint32_t blo, int scale_d) {
    asm volatile("{\n.reg .pred p;\n.reg .b64 da, db;\nsetp.ne.b32 p, %98, 0;\nmov.b64 da, {%96, 0x40000040};\nmov.b64 db, {%97, 0x40000040};\n"
        "wgmma.mma_async.sync.aligned.m64n192k16.f32.bf16.bf16 {"
        "%0, %1, %2, %3, %4, %5, %6, %7, %8, %9, %10, %11, %12, %13, %14, %15, %16, %17, %18, %19, %20, %21, %22, %23, %24, %25, %26, %27, %28, %29, %30, %31,  "
        "%32, %33, %34, %35, %36, %37, %38, %39, %40, %41, %42, %43, %44, %45, %46, %47, %48, %49, %50, %51, %52, %53, %54, %55, %56, %57, %58, %59, %60, %61,  "
        "%62, %63, %64, %65, %66, %67, %68, %69, %70, %71, %72, %73, %74, %75, %76, %77, %78, %79, %80, %81, %82, %83, %84, %85, %86, %87, %88, %89, %90, %91,  "
        "%92, %93, %94, %95 "
        "}, da, db, p, 1, 1, 0, 1;\n}\n"
        : "+f"(d[0]), "+f"(d[1]), "+f"(d[2]), "+f"(d[3]), "+f"(d[4]), "+f"(d[5]), "+f"(d[6]), "+f"(d[7]), "+f"(d[8]), "+f"(d[9]), "+f"(d[10]), "+f"(d[11]),
          "+f"(d[12]), "+f"(d[13]), "+f"(d[14]), "+f"(d[15]), "+f"(d[16]), "+f"(d[17]), "+f"(d[18]), "+f"(d[19]), "+f"(d[20]), "+f"(d[21]), "+f"(d[22]),
          "+f"(d[23]), "+f"(d[24]), "+f"(d[25]), "+f"(d[26]), "+f"(d[27]), "+f"(d[28]), "+f"(d[29]), "+f"(d[30]), "+f"(d[31]), "+f"(d[32]), "+f"(d[33]),
          "+f"(d[34]), "+f"(d[35]), "+f"(d[36]), "+f"(d[37]), "+f"(d[38]), "+f"(d[39]), "+f"(d[40]), "+f"(d[41]), "+f"(d[42]), "+f"(d[43]), "+f"(d[44]),
          "+f"(d[45]), "+f"(d[46]), "+f"(d[47]), "+f"(d[48]), "+f"(d[49]), "+f"(d[50]), "+f"(d[51]), "+f"(d[52]), "+f"(d[53]), "+f"(d[54]), "+f"(d[55]),
          "+f"(d[56]), "+f"(d[57]), "+f"(d[58]), "+f"(d[59]), "+f"(d[60]), "+f"(d[61]), "+f"(d[62]), "+f"(d[63]), "+f"(d[64]), "+f"(d[65]), "+f"(d[66]),
          "+f"(d[67]), "+f"(d[68]), "+f"(d[69]), "+f"(d[70]), "+f"(d[71]), "+f"(d[72]), "+f"(d[73]), "+f"(d[74]), "+f"(d[75]), "+f"(d[76]), "+f"(d[77]),
          "+f"(d[78]), "+f"(d[79]), "+f"(d[80]), "+f"(d[81]), "+f"(d[82]), "+f"(d[83]), "+f"(d[84]), "+f"(d[85]), "+f"(d[86]), "+f"(d[87]), "+f"(d[88]),
          "+f"(d[89]), "+f"(d[90]), "+f"(d[91]), "+f"(d[92]), "+f"(d[93]), "+f"(d[94]), "+f"(d[95])
        : "r"(alo), "r"(blo), "r"(scale_d));
}
__device__ __forceinline__ void mma_wo(float (&d)[64], uint32_t alo, uint32_t blo, int scale_d) {
    asm volatile("{\n.reg .pred p;\n.reg .b64 da, db;\nsetp.ne.b32 p, %66, 0;\nmov.b64 da, {%64, 0x40000040};\nmov.b64 db, {%65, 0x40000040};\n"
        "wgmma.mma_async.sync.aligned.m64n128k16.f32.bf16.bf16 {"
        "%0, %1, %2, %3, %4, %5, %6, %7, %8, %9, %10, %11, %12, %13, %14, %15, %16, %17, %18, %19, %20, %21, %22, %23, %24, %25, %26, %27, %28, %29, %30, %31,  "
        "%32, %33, %34, %35, %36, %37, %38, %39, %40, %41, %42, %43, %44, %45, %46, %47, %48, %49, %50, %51, %52, %53, %54, %55, %56, %57, %58, %59, %60, %61,  "
        "%62, %63 "
        "}, da, db, p, 1, 1, 0, 1;\n}\n"
        : "+f"(d[0]), "+f"(d[1]), "+f"(d[2]), "+f"(d[3]), "+f"(d[4]), "+f"(d[5]), "+f"(d[6]), "+f"(d[7]), "+f"(d[8]), "+f"(d[9]), "+f"(d[10]), "+f"(d[11]),
          "+f"(d[12]), "+f"(d[13]), "+f"(d[14]), "+f"(d[15]), "+f"(d[16]), "+f"(d[17]), "+f"(d[18]), "+f"(d[19]), "+f"(d[20]), "+f"(d[21]), "+f"(d[22]),
          "+f"(d[23]), "+f"(d[24]), "+f"(d[25]), "+f"(d[26]), "+f"(d[27]), "+f"(d[28]), "+f"(d[29]), "+f"(d[30]), "+f"(d[31]), "+f"(d[32]), "+f"(d[33]),
          "+f"(d[34]), "+f"(d[35]), "+f"(d[36]), "+f"(d[37]), "+f"(d[38]), "+f"(d[39]), "+f"(d[40]), "+f"(d[41]), "+f"(d[42]), "+f"(d[43]), "+f"(d[44]),
          "+f"(d[45]), "+f"(d[46]), "+f"(d[47]), "+f"(d[48]), "+f"(d[49]), "+f"(d[50]), "+f"(d[51]), "+f"(d[52]), "+f"(d[53]), "+f"(d[54]), "+f"(d[55]),
          "+f"(d[56]), "+f"(d[57]), "+f"(d[58]), "+f"(d[59]), "+f"(d[60]), "+f"(d[61]), "+f"(d[62]), "+f"(d[63])
        : "r"(alo), "r"(blo), "r"(scale_d));
}
__device__ __forceinline__ void mma_mix2(float (&d)[64], uint32_t alo, uint32_t blo, int scale_d) {
    asm volatile("{\n.reg .pred p;\n.reg .b64 da, db;\nsetp.ne.b32 p, %66, 0;\nmov.b64 da, {%64, 0x40000040};\nmov.b64 db, {%65, 0x40000040};\n"
        "wgmma.mma_async.sync.aligned.m64n128k16.f32.bf16.bf16 {"
        "%0, %1, %2, %3, %4, %5, %6, %7, %8, %9, %10, %11, %12, %13, %14, %15, %16, %17, %18, %19, %20, %21, %22, %23, %24, %25, %26, %27, %28, %29, %30, %31,  "
        "%32, %33, %34, %35, %36, %37, %38, %39, %40, %41, %42, %43, %44, %45, %46, %47, %48, %49, %50, %51, %52, %53, %54, %55, %56, %57, %58, %59, %60, %61,  "
        "%62, %63 "
        "}, da, db, p, 1, 1, 1, 0;\n}\n"
        : "+f"(d[0]), "+f"(d[1]), "+f"(d[2]), "+f"(d[3]), "+f"(d[4]), "+f"(d[5]), "+f"(d[6]), "+f"(d[7]), "+f"(d[8]), "+f"(d[9]), "+f"(d[10]), "+f"(d[11]),
          "+f"(d[12]), "+f"(d[13]), "+f"(d[14]), "+f"(d[15]), "+f"(d[16]), "+f"(d[17]), "+f"(d[18]), "+f"(d[19]), "+f"(d[20]), "+f"(d[21]), "+f"(d[22]),
          "+f"(d[23]), "+f"(d[24]), "+f"(d[25]), "+f"(d[26]), "+f"(d[27]), "+f"(d[28]), "+f"(d[29]), "+f"(d[30]), "+f"(d[31]), "+f"(d[32]), "+f"(d[33]),
          "+f"(d[34]), "+f"(d[35]), "+f"(d[36]), "+f"(d[37]), "+f"(d[38]), "+f"(d[39]), "+f"(d[40]), "+f"(d[41]), "+f"(d[42]), "+f"(d[43]), "+f"(d[44]),
          "+f"(d[45]), "+f"(d[46]), "+f"(d[47]), "+f"(d[48]), "+f"(d[49]), "+f"(d[50]), "+f"(d[51]), "+f"(d[52]), "+f"(d[53]), "+f"(d[54]), "+f"(d[55]),
          "+f"(d[56]), "+f"(d[57]), "+f"(d[58]), "+f"(d[59]), "+f"(d[60]), "+f"(d[61]), "+f"(d[62]), "+f"(d[63])
        : "r"(alo), "r"(blo), "r"(scale_d));
}
__device__ __forceinline__ void mma_mix1(float (&d)[112], uint32_t alo, uint32_t blo, int scale_d) {
    asm volatile("{\n.reg .pred p;\n.reg .b64 da, db;\nsetp.ne.b32 p, %114, 0;\nmov.b64 da, {%112, 0x40000040};\nmov.b64 db, {%113, 0x80000020};\n"
        "wgmma.mma_async.sync.aligned.m64n224k16.f32.bf16.bf16 {"
        "%0, %1, %2, %3, %4, %5, %6, %7, %8, %9, %10, %11, %12, %13, %14, %15, %16, %17, %18, %19, %20, %21, %22, %23, %24, %25, %26, %27, %28, %29, %30, %31,  "
        "%32, %33, %34, %35, %36, %37, %38, %39, %40, %41, %42, %43, %44, %45, %46, %47, %48, %49, %50, %51, %52, %53, %54, %55, %56, %57, %58, %59, %60, %61,  "
        "%62, %63, %64, %65, %66, %67, %68, %69, %70, %71, %72, %73, %74, %75, %76, %77, %78, %79, %80, %81, %82, %83, %84, %85, %86, %87, %88, %89, %90, %91,  "
        "%92, %93, %94, %95, %96, %97, %98, %99, %100, %101, %102, %103, %104, %105, %106, %107, %108, %109, %110, %111 "
        "}, da, db, p, 1, 1, 1, 1;\n}\n"
        : "+f"(d[0]), "+f"(d[1]), "+f"(d[2]), "+f"(d[3]), "+f"(d[4]), "+f"(d[5]), "+f"(d[6]), "+f"(d[7]), "+f"(d[8]), "+f"(d[9]), "+f"(d[10]), "+f"(d[11]),
          "+f"(d[12]), "+f"(d[13]), "+f"(d[14]), "+f"(d[15]), "+f"(d[16]), "+f"(d[17]), "+f"(d[18]), "+f"(d[19]), "+f"(d[20]), "+f"(d[21]), "+f"(d[22]),
          "+f"(d[23]), "+f"(d[24]), "+f"(d[25]), "+f"(d[26]), "+f"(d[27]), "+f"(d[28]), "+f"(d[29]), "+f"(d[30]), "+f"(d[31]), "+f"(d[32]), "+f"(d[33]),
          "+f"(d[34]), "+f"(d[35]), "+f"(d[36]), "+f"(d[37]), "+f"(d[38]), "+f"(d[39]), "+f"(d[40]), "+f"(d[41]), "+f"(d[42]), "+f"(d[43]), "+f"(d[44]),
          "+f"(d[45]), "+f"(d[46]), "+f"(d[47]), "+f"(d[48]), "+f"(d[49]), "+f"(d[50]), "+f"(d[51]), "+f"(d[52]), "+f"(d[53]), "+f"(d[54]), "+f"(d[55]),
          "+f"(d[56]), "+f"(d[57]), "+f"(d[58]), "+f"(d[59]), "+f"(d[60]), "+f"(d[61]), "+f"(d[62]), "+f"(d[63]), "+f"(d[64]), "+f"(d[65]), "+f"(d[66]),
          "+f"(d[67]), "+f"(d[68]), "+f"(d[69]), "+f"(d[70]), "+f"(d[71]), "+f"(d[72]), "+f"(d[73]), "+f"(d[74]), "+f"(d[75]), "+f"(d[76]), "+f"(d[77]),
          "+f"(d[78]), "+f"(d[79]), "+f"(d[80]), "+f"(d[81]), "+f"(d[82]), "+f"(d[83]), "+f"(d[84]), "+f"(d[85]), "+f"(d[86]), "+f"(d[87]), "+f"(d[88]),
          "+f"(d[89]), "+f"(d[90]), "+f"(d[91]), "+f"(d[92]), "+f"(d[93]), "+f"(d[94]), "+f"(d[95]), "+f"(d[96]), "+f"(d[97]), "+f"(d[98]), "+f"(d[99]),
          "+f"(d[100]), "+f"(d[101]), "+f"(d[102]), "+f"(d[103]), "+f"(d[104]), "+f"(d[105]), "+f"(d[106]), "+f"(d[107]), "+f"(d[108]), "+f"(d[109]),
          "+f"(d[110]), "+f"(d[111])
        : "r"(alo), "r"(blo), "r"(scale_d));
}
__device__ __forceinline__ void mma_qk0(float (&d)[32], uint32_t alo, uint32_t blo) {
    asm volatile("{\n.reg .pred p;\n.reg .b64 da, db;\nsetp.ne.b32 p, 0, 0;\nmov.b64 da, {%32, 0x80000020};\nmov.b64 db, {%33, 0x80000020};\n"
        "wgmma.mma_async.sync.aligned.m64n64k16.f32.bf16.bf16 {"
        "%0, %1, %2, %3, %4, %5, %6, %7, %8, %9, %10, %11, %12, %13, %14, %15, %16, %17, %18, %19, %20, %21, %22, %23, %24, %25, %26, %27, %28, %29, %30, %31 "
        "}, da, db, p, 1, 1, 0, 0;\n}\n"
        : "=f"(d[0]), "=f"(d[1]), "=f"(d[2]), "=f"(d[3]), "=f"(d[4]), "=f"(d[5]), "=f"(d[6]), "=f"(d[7]), "=f"(d[8]), "=f"(d[9]), "=f"(d[10]), "=f"(d[11]),
          "=f"(d[12]), "=f"(d[13]), "=f"(d[14]), "=f"(d[15]), "=f"(d[16]), "=f"(d[17]), "=f"(d[18]), "=f"(d[19]), "=f"(d[20]), "=f"(d[21]), "=f"(d[22]),
          "=f"(d[23]), "=f"(d[24]), "=f"(d[25]), "=f"(d[26]), "=f"(d[27]), "=f"(d[28]), "=f"(d[29]), "=f"(d[30]), "=f"(d[31])
        : "r"(alo), "r"(blo));
}
__device__ __forceinline__ void mma_qk1(float (&d)[32], uint32_t alo, uint32_t blo, int scale_d) {
    asm volatile("{\n.reg .pred p;\n.reg .b64 da, db;\nsetp.ne.b32 p, %34, 0;\nmov.b64 da, {%32, 0x80000020};\nmov.b64 db, {%33, 0x80000020};\n"
        "wgmma.mma_async.sync.aligned.m64n64k16.f32.bf16.bf16 {"
        "%0, %1, %2, %3, %4, %5, %6, %7, %8, %9, %10, %11, %12, %13, %14, %15, %16, %17, %18, %19, %20, %21, %22, %23, %24, %25, %26, %27, %28, %29, %30, %31 "
        "}, da, db, p, 1, 1, 0, 0;\n}\n"
        : "+f"(d[0]), "+f"(d[1]), "+f"(d[2]), "+f"(d[3]), "+f"(d[4]), "+f"(d[5]), "+f"(d[6]), "+f"(d[7]), "+f"(d[8]), "+f"(d[9]), "+f"(d[10]), "+f"(d[11]),
          "+f"(d[12]), "+f"(d[13]), "+f"(d[14]), "+f"(d[15]), "+f"(d[16]), "+f"(d[17]), "+f"(d[18]), "+f"(d[19]), "+f"(d[20]), "+f"(d[21]), "+f"(d[22]),
          "+f"(d[23]), "+f"(d[24]), "+f"(d[25]), "+f"(d[26]), "+f"(d[27]), "+f"(d[28]), "+f"(d[29]), "+f"(d[30]), "+f"(d[31])
        : "r"(alo), "r"(blo), "r"(scale_d));
}
__device__ __forceinline__ void mma_pv(float (&d)[20], uint32_t a0, uint32_t a1, uint32_t a2, uint32_t a3, uint32_t blo, int scale_d) {
    asm volatile("{\n.reg .pred p;\n.reg .b64 da, db;\nsetp.ne.b32 p, %25, 0;\nmov.b64 db, {%24, 0x80000020};\n"
        "wgmma.mma_async.sync.aligned.m64n40k16.f32.bf16.bf16 {"
        "%0, %1, %2, %3, %4, %5, %6, %7, %8, %9, %10, %11, %12, %13, %14, %15, %16, %17, %18, %19 "
        "}, {%20, %21, %22, %23}, db, p, 1, 1, 1;\n}\n"
        : "+f"(d[0]), "+f"(d[1]), "+f"(d[2]), "+f"(d[3]), "+f"(d[4]), "+f"(d[5]), "+f"(d[6]), "+f"(d[7]), "+f"(d[8]), "+f"(d[9]), "+f"(d[10]), "+f"(d[11]),
          "+f"(d[12]), "+f"(d[13]), "+f"(d[14]), "+f"(d[15]), "+f"(d[16]), "+f"(d[17]), "+f"(d[18]), "+f"(d[19])
        : "r"(a0), "r"(a1), "r"(a2), "r"(a3), "r"(blo), "r"(scale_d));
}
__device__ __forceinline__ void mma_qk0w(float (&d)[32], uint64_t da, uint64_t db) {
    asm volatile("{\n.reg .pred p;\n.reg .b64 da, db;\nsetp.ne.b32 p, 0, 0;\nmov.b64 da, %32;\nmov.b64 db, %33;\n"
        "wgmma.mma_async.sync.aligned.m64n64k16.f32.bf16.bf16 {"
        "%0, %1, %2, %3, %4, %5, %6, %7, %8, %9, %10, %11, %12, %13, %14, %15, %16, %17, %18, %19, %20, %21, %22, %23, %24, %25, %26, %27, %28, %29, %30, %31 "
        "}, da, db, p, 1, 1, 0, 0;\n}\n"
        : "=f"(d[0]), "=f"(d[1]), "=f"(d[2]), "=f"(d[3]), "=f"(d[4]), "=f"(d[5]), "=f"(d[6]), "=f"(d[7]), "=f"(d[8]), "=f"(d[9]), "=f"(d[10]), "=f"(d[11]),
          "=f"(d[12]), "=f"(d[13]), "=f"(d[14]), "=f"(d[15]), "=f"(d[16]), "=f"(d[17]), "=f"(d[18]), "=f"(d[19]), "=f"(d[20]), "=f"(d[21]), "=f"(d[22]),
          "=f"(d[23]), "=f"(d[24]), "=f"(d[25]), "=f"(d[26]), "=f"(d[27]), "=f"(d[28]), "=f"(d[29]), "=f"(d[30]), "=f"(d[31])
        : "l"(da), "l"(db));
}
__device__ __forceinline__ void mma_qk1w(float (&d)[32], uint64_t da, uint64_t db, int scale_d) {
    asm volatile("{\n.reg .pred p;\n.reg .b64 da, db;\nsetp.ne.b32 p, %34, 0;\nmov.b64 da, %32;\nmov.b64 db, %33;\n"
        "wgmma.mma_async.sync.aligned.m64n64k16.f32.bf16.bf16 {"
        "%0, %1, %2, %3, %4, %5, %6, %7, %8, %9, %10, %11, %12, %13, %14, %15, %16, %17, %18, %19, %20, %21, %22, %23, %24, %25, %26, %27, %28, %29, %30, %31 "
        "}, da, db, p, 1, 1, 0, 0;\n}\n"
        : "+f"(d[0]), "+f"(d[1]), "+f"(d[2]), "+f"(d[3]), "+f"(d[4]), "+f"(d[5]), "+f"(d[6]), "+f"(d[7]), "+f"(d[8]), "+f"(d[9]), "+f"(d[10]), "+f"(d[11]),
          "+f"(d[12]), "+f"(d[13]), "+f"(d[14]), "+f"(d[15]), "+f"(d[16]), "+f"(d[17]), "+f"(d[18]), "+f"(d[19]), "+f"(d[20]), "+f"(d[21]), "+f"(d[22]),
          "+f"(d[23]), "+f"(d[24]), "+f"(d[25]), "+f"(d[26]), "+f"(d[27]), "+f"(d[28]), "+f"(d[29]), "+f"(d[30]), "+f"(d[31])
        : "l"(da), "l"(db), "r"(scale_d));
}
__device__ __forceinline__ void mma_pvw(float (&d)[20], uint32_t a0, uint32_t a1, uint32_t a2, uint32_t a3, uint64_t db, int scale_d) {
    asm volatile("{\n.reg .pred p;\n.reg .b64 da, db;\nsetp.ne.b32 p, %25, 0;\nmov.b64 db, %24;\n"
        "wgmma.mma_async.sync.aligned.m64n40k16.f32.bf16.bf16 {"
        "%0, %1, %2, %3, %4, %5, %6, %7, %8, %9, %10, %11, %12, %13, %14, %15, %16, %17, %18, %19 "
        "}, {%20, %21, %22, %23}, db, p, 1, 1, 1;\n}\n"
        : "+f"(d[0]), "+f"(d[1]), "+f"(d[2]), "+f"(d[3]), "+f"(d[4]), "+f"(d[5]), "+f"(d[6]), "+f"(d[7]), "+f"(d[8]), "+f"(d[9]), "+f"(d[10]), "+f"(d[11]),
          "+f"(d[12]), "+f"(d[13]), "+f"(d[14]), "+f"(d[15]), "+f"(d[16]), "+f"(d[17]), "+f"(d[18]), "+f"(d[19])
        : "r"(a0), "r"(a1), "r"(a2), "r"(a3), "l"(db), "r"(scale_d));
}

struct GemmSmem { uint32_t base, full0, empty0, aux; };

struct NoEarly { __device__ __forceinline__ void operator()(const GemmSmem&) const {} };
template <class C, class E = NoEarly>
__device__ __forceinline__ GemmSmem gemm_setup(uint8_t* smem_raw, E early = E()) {
    GemmSmem s;
    s.base = smem_u32(smem_raw);
    s.full0 = s.base + C::BAR_OFF; s.empty0 = s.full0 + 8 * C::STAGES; s.aux = s.empty0 + 8 * C::STAGES;
    if (threadIdx.x == 0) {
        if (s.base & 1023) __trap();
        for (int i = 0; i < C::STAGES; i++) { mbar_init(s.full0 + 8 * i, 1); mbar_init(s.empty0 + 8 * i, C::MC ? 16 : 8); }
        mbar_init(s.aux, C::AUX_COUNT);
        fence_barrier_init();
        early(s);
    }
    __syncthreads();
    if (C::MC) { cluster_arrive(); cluster_wait(); }
    return s;
}

template <class C, class P>
__device__ __forceinline__ void gemm_producer(const GemmSmem& s, const P& p, int tm, int tn) {
    C::load_aux(p, s, tm, tn);
#pragma unroll 1
    for (int k = 0; k < C::PRE; k++) {
        mbar_expect_tx(s.full0 + 8 * k, C::STAGE_BYTES);
        C::load_w(p, s.base + k * C::STAGE_BYTES, s.full0 + 8 * k, k, tm, tn);
    }
    pdl_wait();
#pragma unroll 1
    for (int k = 0; k < C::STAGES; k++) {
        if (C::FIRST_BY_THREADS && k == 0) { mbar_arrive(s.full0); continue; }
        if (k >= C::PRE) mbar_expect_tx(s.full0 + 8 * k, C::STAGE_BYTES);
        C::load_x(p, s.base + k * C::STAGE_BYTES, s.full0 + 8 * k, k, tm, tn);
        if (k >= C::PRE) C::load_w(p, s.base + k * C::STAGE_BYTES, s.full0 + 8 * k, k, tm, tn);
    }
    int st = 0; uint32_t ph = 0;
#pragma unroll 1
    for (int k = C::STAGES; k < C::KSTEPS; k++) {
        mbar_wait(s.empty0 + 8 * st, ph);
        if (k < C::STAGES + C::FOLLOW) mbar_wait(s.aux + 16 + 8 * st, ph);
        C::after_release(p, s, k, tm, tn);
        mbar_expect_tx(s.full0 + 8 * st, C::STAGE_BYTES);
        C::load_x(p, s.base + st * C::STAGE_BYTES, s.full0 + 8 * st, k, tm, tn);
        C::load_w(p, s.base + st * C::STAGE_BYTES, s.full0 + 8 * st, k, tm, tn);
        if (++st == C::STAGES) { st = 0; ph ^= 1; }
    }
    C::producer_done(s);
}

template <class C, int KEND = C::KSTEPS, int SK = 0, bool DONE_BAR = false>
__device__ __forceinline__ void gemm_mainloop(const GemmSmem& s, int wg, float (&acc)[C::MB][C::BN / 2]) {
    const int lane = threadIdx.x & 31;
    int st = 0; uint32_t ph = 0;
    int prev = 0;
    const uint32_t rel0 = C::MC ? mapa(s.empty0, lane & 1) : s.empty0;
#pragma unroll
    for (int m = 0; m < C::MB; m++) fence_regs(acc[m]);
#pragma unroll 1
    for (int k = 0; k < KEND; k++) {
        if (SK > 0 && k == KEND - SK && wg == 1) {
            if (DONE_BAR) { wg_wait<0>(); named_arrive(10, 256); }
            named_bar(11, 256);
        }
        mbar_wait(s.full0 + 8 * st, ph);
        const uint32_t sb = s.base + st * C::STAGE_BYTES;
        wg_fence();
#pragma unroll
        for (int kk = 0; kk < 4; kk++) {
#pragma unroll
            for (int m = 0; m < C::MB; m++) C::mma(acc[m], C::desc_a(sb, wg, m, kk), C::desc_b(sb, kk), C::ACC_INIT || (k | kk) != 0);
        }
        wg_commit();
        if (SK > 0 && k == KEND - 1 && wg == 0) named_arrive(11, 256);
        if (k > 0) {
            wg_wait<1>();
            if (k <= C::KSTEPS - C::STAGES) {
                if (C::MC) { if (lane < 2) mbar_arrive_cluster(rel0 + 8 * prev); }
                else if (lane == 0) mbar_arrive(rel0 + 8 * prev);
            }
        }
        prev = st;
        if (++st == C::STAGES) { st = 0; ph ^= 1; }
    }
    if (KEND == C::KSTEPS) {
        wg_wait<0>();
#pragma unroll
        for (int m = 0; m < C::MB; m++) fence_regs(acc[m]);
    }
}

struct QkvParams { CUtensorMap x, w, out; const bf16* xp; const bf16* wp; };
struct QkvCfg {
    static constexpr int MB = 1, BN = 192, KSTEPS = 32, STAGES = 4, A_BYTES = 16384, B_BYTES = 24576;
    static constexpr int STAGE_BYTES = A_BYTES + B_BYTES, STG_OFF = STAGES * STAGE_BYTES, BAR_OFF = STG_OFF + 65536, AUX_OFF = BAR_OFF + 128, SMEM = AUX_OFF + 2816;
    static constexpr int AUX_COUNT = 3, PRE = 0;
    static constexpr bool MC = true, ACC_INIT = false, FIRST_BY_THREADS = QKV_FIRST;
    static constexpr int FOLLOW = 16;
    static __device__ __forceinline__ void after_release(const QkvParams& p, const GemmSmem& s, int k, int tm, int tn) {
        const int g2 = k - (21 + QKV2_E0);
        if (g2 == 0 || g2 == 2 || g2 == 4) {
            fence_proxy_async();
#pragma unroll
            for (int i = 0; i < 4; i++)
                tma_st2(&p.out, s.base + STG_OFF + (i >> 1) * 24576 + (g2 + (i & 1)) * 4096, 0, (g2 >> 1) * (NH * SEQ) + (tn * 2 + (i & 1)) * SEQ + tm * 256 + (i >> 1) * 64);
        }
    }
    static __device__ __forceinline__ void producer_done(const GemmSmem& s) {
        tma_st_commit(); tma_st_wait(); mbar_arrive(s.aux + 48);
    }
    static __device__ __forceinline__ void load_w(const QkvParams& p, uint32_t sb, uint32_t bar, int k, int tm, int tn) {
        tma_ld4_mc(sb + A_BYTES + (tm & 1) * (B_BYTES / 2), &p.w, bar, 0, (k & 15) * 64 + (tm & 1) * 32, 0, tn);
    }
    static __device__ __forceinline__ void load_x(const QkvParams& p, uint32_t sb, uint32_t bar, int k, int tm, int tn) { tma_ld2(sb, &p.x, bar, (k & 15) * 64, tm * 256 + (k >> 4) * 128); }
    static __device__ __forceinline__ void load_aux(const QkvParams&, const GemmSmem&, int, int) {}
    static __device__ __forceinline__ uint32_t desc_a(uint32_t sb, int wg, int m, int kk) { return desc_lo(sb + wg * 8192 + kk * 32, 16); }
    static __device__ __forceinline__ uint32_t desc_b(uint32_t sb, int kk) { return desc_lo(sb + A_BYTES + (kk >> 1) * (B_BYTES / 2) + (kk & 1) * 2048, 4096); }
    static __device__ __forceinline__ void mma(float (&d)[96], uint32_t a, uint32_t b, int sc) { mma_qkv(d, a, b, sc); }
};

__device__ __forceinline__ void cp16(uint32_t dst, const void* src) { asm volatile("cp.async.cg.shared.global [%0], [%1], 16;" :: "r"(dst), "l"(src) : "memory"); }
__device__ __forceinline__ uint4 lds16(uint32_t a) { uint4 t; asm volatile("ld.shared.v4.u32 {%0, %1, %2, %3}, [%4];" : "=r"(t.x), "=r"(t.y), "=r"(t.z), "=r"(t.w) : "r"(a) : "memory"); return t; }
__device__ __forceinline__ void qkv_rows_load(const QkvParams& p, uint32_t reg, int row0, int w, int lane) {
    const uint4* xsrc = reinterpret_cast<const uint4*>(p.xp + (size_t)(row0 + w) * DM) + lane;
#pragma unroll 1
    for (int r = 0; w + 3 * r < 8; r++) {
#pragma unroll
        for (int i = 0; i < 4; i++) cp16(reg + r * 6144 + i * 512, xsrc + r * (3 * DM / 8) + i * 32);
    }
    asm volatile("cp.async.commit_group;" ::: "memory");
}
__device__ __forceinline__ void qkv_rows_gather(float2* sst, int row0, int t) {
    unsigned long long u[2];
    int it = 0;
    bool ok;
    do {
#pragma unroll
        for (int i = 0; i < 2; i++) asm volatile("ld.relaxed.gpu.global.u64 %0, [%1];" : "=l"(u[i]) : "l"(g_rowstat2 + row0 + min(t + 96 * i, 127)) : "memory");
        ok = (long long)(u[0] & u[1]) < 0;
        if (++it > (1 << 20)) __trap();
    } while (!ok);
#pragma unroll
    for (int i = 0; i < 2; i++)
        if (t + 96 * i < 128) sst[t + 96 * i] = make_float2(__uint_as_float((uint32_t)u[i]), __uint_as_float((uint32_t)(u[i] >> 32) & 0x7FFFFFFFu));
}
struct Moments {
    float sd0, sd1, sq0, sq1, x0;
    __device__ __forceinline__ void add(const uint4 x) {
        const float d0 = bf_lo(x.x) - x0, d1 = bf_hi(x.x) - x0, d2 = bf_lo(x.y) - x0, d3 = bf_hi(x.y) - x0;
        const float d4 = bf_lo(x.z) - x0, d5 = bf_hi(x.z) - x0, d6 = bf_lo(x.w) - x0, d7 = bf_hi(x.w) - x0;
        sd0 += (d0 + d1) + (d2 + d3); sd1 += (d4 + d5) + (d6 + d7);
        sq0 = fmaf(d0, d0, fmaf(d1, d1, fmaf(d2, d2, fmaf(d3, d3, sq0))));
        sq1 = fmaf(d4, d4, fmaf(d5, d5, fmaf(d6, d6, fmaf(d7, d7, sq1))));
    }
    template <int L> __device__ __forceinline__ unsigned long long finish() {
        float sd = sd0 + sd1, sq = sq0 + sq1;
#pragma unroll
        for (int o = 1; o < L; o <<= 1) { sd += __shfl_xor_sync(0xffffffffu, sd, o); sq += __shfl_xor_sync(0xffffffffu, sq, o); }
        const float md = sd * (1.f / DM);
        const float rstd = rsqrtf(fmaxf(fmaf(-md, md, sq * (1.f / DM)), 0.f) + 1e-5f);
        return ((unsigned long long)(__float_as_uint(rstd) | 0x80000000u) << 32) | __float_as_uint(x0 + md);
    }
};
template <class C>
__device__ __forceinline__ void qkv_aux(const QkvParams& p, uint8_t* smem_raw, const GemmSmem& s, int tm, int tn, int w, int lane) {
    const uint32_t rel0 = mapa(s.aux + 16, lane & 1);
    const int chunk = lane & 7, sub = lane >> 3;
    const int wr = tm * 8 + sub;
    const uint32_t woff = C::A_BYTES + (wr >> 5) * (C::B_BYTES / 2) + w * 4096 + (wr & 31) * 128;
    const uint32_t woff0 = woff + ((chunk ^ (wr & 7)) << 4), woff1 = woff + 512 + ((chunk ^ ((wr + 4) & 7)) << 4);
    const int xr = tn * 8 + (w & 1) * 4 + sub;
    const uint32_t xoff = xr * 128 + ((chunk ^ (xr & 7)) << 4);
    const uint32_t xreg = s.base + C::STG_OFF + 49152 + w * 2048 + lane * 16;
    const uint8_t* pf = lane < 24 ? reinterpret_cast<const uint8_t*>(p.wp + (size_t)(tm * 8 + lane / 3) * (3 * DM) + (lane % 3) * DM + tn * 64)
                                  : reinterpret_cast<const uint8_t*>(p.xp + (size_t)(tm * 256 + tn * 8 + lane - 24) * DM);
    const uint32_t pf_step = lane < 24 ? 64 * 3 * DM * 2 : 128;
    float* scs = reinterpret_cast<float*>(smem_raw + C::AUX_OFF);
    float2* sst = reinterpret_cast<float2*>(smem_raw + C::AUX_OFF + 768);
    const int t = w * 32 + lane;
    float a[8];
#pragma unroll
    for (int i = 0; i < 8; i++) a[i] = 0.f;
    Moments m0 = {0.f, 0.f, 0.f, 0.f, 0.f};
    if (QKV_FIRST) named_bar(13, 352);
#pragma unroll 1
    for (int k = 0; k < 16; k++) {
        const int st = k & 3;
        mbar_wait(s.full0 + 8 * st, (k >> 2) & 1);
        const uint32_t sb = s.base + st * C::STAGE_BYTES;
        const uint4 u = lds16(sb + woff0), v = lds16(sb + woff1);
        if (w < 2) {
            const uint4 x = lds16(sb + xoff);
            if (k == 0) m0.x0 = __shfl_sync(0xffffffffu, bf_lo(x.x), lane & 24);
            m0.add(x);
        } else if (QKV3_PF) {
            if (k == 0) for (int j = C::STAGES; j < QKV3_PF; j++) prefetch_line(pf + (size_t)j * pf_step);
            if (k + QKV3_PF < 16) prefetch_line(pf + (size_t)(k + QKV3_PF) * pf_step);
        }
        a[0] += bf_lo(u.x) + bf_lo(v.x); a[1] += bf_hi(u.x) + bf_hi(v.x); a[2] += bf_lo(u.y) + bf_lo(v.y); a[3] += bf_hi(u.y) + bf_hi(v.y);
        a[4] += bf_lo(u.z) + bf_lo(v.z); a[5] += bf_hi(u.z) + bf_hi(v.z); a[6] += bf_lo(u.w) + bf_lo(v.w); a[7] += bf_hi(u.w) + bf_hi(v.w);
        __syncwarp();
        if (lane < 2) mbar_arrive_cluster(rel0 + 8 * st);
        if (k == QKV3_R1) qkv_rows_load(p, xreg, tm * 256 + 128 + tn * 8, w, lane);
    }
    if (w < 2) {
        const unsigned long long w0 = m0.finish<8>();
        if (chunk == 0) asm volatile("st.relaxed.gpu.global.u64 [%0], %1;" :: "l"(g_rowstat2 + tm * 256 + xr), "l"(w0) : "memory");
    }
#pragma unroll
    for (int i = 0; i < 8; i++) { a[i] += __shfl_xor_sync(0xffffffffu, a[i], 8); a[i] += __shfl_xor_sync(0xffffffffu, a[i], 16); }
    if (lane < 16) {
        const bool up = lane & 8;
        uint32_t* dst = g_colsum2 + tm * (3 * DM) + tn * 192 + w * 64 + (lane & 7) * 8 + (up ? 4 : 0);
        asm volatile("st.relaxed.gpu.global.v4.u32 [%0], {%1, %2, %3, %4};" :: "l"(dst), "r"(__float_as_uint(up ? a[4] : a[0]) | 1u), "r"(__float_as_uint(up ? a[5] : a[1]) | 1u),
                     "r"(__float_as_uint(up ? a[6] : a[2]) | 1u), "r"(__float_as_uint(up ? a[7] : a[3]) | 1u) : "memory");
    }
    auto row1 = [&](int r) {
        Moments m = {0.f, 0.f, 0.f, 0.f, 0.f};
        const uint4 x = lds16(xreg + r * 6144);
        m.x0 = __shfl_sync(0xffffffffu, bf_lo(x.x), 0);
        m.add(x);
#pragma unroll 1
        for (int i = 1; i < 4; i++) m.add(lds16(xreg + r * 6144 + i * 512));
        const unsigned long long word = m.finish<32>();
        if (lane == 0) asm volatile("st.relaxed.gpu.global.u64 [%0], %1;" :: "l"(g_rowstat2 + tm * 256 + 128 + tn * 8 + w + 3 * r), "l"(word) : "memory");
    };
    {
        uint32_t ux[8], uy[8];
        unsigned long long r0, r1;
        int it = 0;
        bool ok;
        do {
            asm volatile("ld.relaxed.gpu.global.u64 %0, [%1];" : "=l"(r0) : "l"(g_rowstat2 + tm * 256 + t) : "memory");
            asm volatile("ld.relaxed.gpu.global.u64 %0, [%1];" : "=l"(r1) : "l"(g_rowstat2 + tm * 256 + 96 + (t & 31)) : "memory");
            uint32_t all = 1;
#pragma unroll
            for (int i = 0; i < 8; i++) {
                asm volatile("ld.relaxed.gpu.global.v2.u32 {%0, %1}, [%2];" : "=r"(ux[i]), "=r"(uy[i]) : "l"(g_colsum2 + i * (3 * DM) + tn * 192 + 2 * t) : "memory");
                all &= ux[i] & uy[i];
            }
            ok = (all & 1) && (long long)(r0 & r1) < 0;
            if (++it > (1 << 20)) __trap();
        } while (!ok);
        sst[t] = make_float2(__uint_as_float((uint32_t)r0), __uint_as_float((uint32_t)(r0 >> 32) & 0x7FFFFFFFu));
        if (w == 0) sst[96 + t] = make_float2(__uint_as_float((uint32_t)r1), __uint_as_float((uint32_t)(r1 >> 32) & 0x7FFFFFFFu));
        float2 c = make_float2(0.f, 0.f);
#pragma unroll
        for (int i = 0; i < 8; i++) { c.x += __uint_as_float(ux[i]); c.y += __uint_as_float(uy[i]); }
        reinterpret_cast<float2*>(scs)[t] = c;
    }
    __syncwarp();
    if (lane == 0) mbar_arrive(s.aux);
    asm volatile("cp.async.wait_group 0;" ::: "memory");
#pragma unroll 1
    for (int r = 0; w + 3 * r < 8; r++) row1(r);
    qkv_rows_gather(sst + 128, tm * 256 + 128, t);
    __syncwarp();
    if (lane == 0) mbar_arrive(s.aux + 8);
}

__global__ void __launch_bounds__(384, 1) qkv_kernel(const __grid_constant__ QkvParams p) {
    using C = QkvCfg;
    extern __shared__ __align__(1024) uint8_t smem_raw[];
    const int tm = blockIdx.x & 7, tn = blockIdx.x >> 3;
    if (QKV_FIRST && threadIdx.x >= 128) {
        const int t = threadIdx.x - 128, r = t >> 3, c = t & 7;
        const uint32_t dst = smem_u32(smem_raw) + r * 128 + ((c ^ (r & 7)) << 4);
        const bf16* xs = p.xp + (size_t)(tm * 256 + r) * DM + c * 8;
        const bf16* ws = p.wp + (size_t)r * (3 * DM) + tn * 64 + c * 8;
#pragma unroll
        for (int i = 0; i < 6; i++) cp16(dst + C::A_BYTES + (i & 1) * (C::B_BYTES / 2) + (i >> 1) * 4096, ws + (i & 1) * (32 * 3 * DM) + (i >> 1) * DM);
#pragma unroll
        for (int i = 0; i < 4; i++) cp16(dst + i * 4096, xs + i * 32 * DM);
        asm volatile("cp.async.commit_group;" ::: "memory");
    }
    pdl_launch();
    if (threadIdx.x == 0) { prefetch_map(&p.x); prefetch_map(&p.w); prefetch_map(&p.out); }
    const GemmSmem s = gemm_setup<C>(smem_raw, [](const GemmSmem& g) { mbar_init(g.aux + 8, 3); for (int i = 0; i < C::STAGES; i++) mbar_init(g.aux + 16 + 8 * i, 6); mbar_init(g.aux + 48, 1); fence_barrier_init(); });
    const int wgi = __shfl_sync(0xffffffffu, threadIdx.x >> 7, 0);
    if (wgi == 0) {
        reg_dealloc<56>();
        const int wid = __shfl_sync(0xffffffffu, threadIdx.x >> 5, 0);
        if (wid == 0) { if (elect_one()) gemm_producer<C>(s, p, tm, tn); }
        else {
            qkv_aux<C>(p, smem_raw, s, tm, tn, wid - 1, threadIdx.x & 31);
            if (wid < 3) {
                const int wg = wid - 1;
                const bool leader = elect_one();
#pragma unroll 1
                for (int g = 0; g < 3; g++) {
                    take_over(2 + wg * 3 + g);
                    if (leader) {
#pragma unroll
                        for (int h = 0; h < 2; h++)
                            tma_st2(&p.out, s.base + C::STG_OFF + wg * 24576 + (g * 2 + h) * 4096, 0, g * (NH * SEQ) + (tn * 2 + h) * SEQ + tm * 256 + 128 + wg * 64);
                    }
                }
                if (leader) { tma_st_commit(); tma_st_wait(); }

            }
        }
    } else {
        reg_alloc<224>();
        const int wg = wgi - 1, warp = (threadIdx.x >> 5) & 3, lane = threadIdx.x & 31;
        float acc0[1][96], acc1[96];
        if (QKV_FIRST) { asm volatile("cp.async.wait_group 0;" ::: "memory"); fence_proxy_async(); named_bar(13, 352); }
        gemm_mainloop<C, 16>(s, wg, acc0);
        const uint32_t rel0 = mapa(s.empty0, lane & 1);
        auto step = [&](int st, uint32_t ph, bool first) {
            mbar_wait(s.full0 + 8 * st, ph);
            const uint32_t sb = s.base + st * C::STAGE_BYTES;
            wg_fence();
#pragma unroll
            for (int kk = 0; kk < 4; kk++) C::mma(acc1, C::desc_a(sb, wg, 0, kk), C::desc_b(sb, kk), !first || kk != 0);
            wg_commit();
        };
        auto release = [&](int st) { wg_wait<1>(); __syncwarp(); if (lane < 2) mbar_arrive_cluster(rel0 + 8 * st); };
        const float qscale = 0.17677669529663687f * 1.4426950408889634f;
        const float2* scs = reinterpret_cast<const float2*>(smem_raw + C::AUX_OFF);
        const float2* sst = reinterpret_cast<const float2*>(smem_raw + C::AUX_OFF + 768);
        const int arow = warp * 16 + ((lane >> 3) & 1) * 8 + (lane & 7);
        auto piece = [&](const float (&acc)[96], int half, int sub, float mean0, float mean1, float r0, float r1) {
            float v[16];
#pragma unroll
            for (int j = 0; j < 4; j++) {
                const float2 cs = scs[(sub * 4 + j) * 4 + (lane & 3)];
                v[4 * j] = fmaf(mean0, cs.x, acc[sub * 16 + 4 * j]) * r0;
                v[4 * j + 1] = fmaf(mean0, cs.y, acc[sub * 16 + 4 * j + 1]) * r0;
                v[4 * j + 2] = fmaf(mean1, cs.x, acc[sub * 16 + 4 * j + 2]) * r1;
                v[4 * j + 3] = fmaf(mean1, cs.y, acc[sub * 16 + 4 * j + 3]) * r1;
            }
#pragma unroll
            for (int jp = 0; jp < 2; jp++) {
                const int chunk = jp * 2 + (lane >> 4);
                const uint32_t addr = s.base + C::STG_OFF + wg * 24576 + sub * 4096 + arow * 64 + ((chunk ^ ((arow >> 1) & 3)) << 4);
                stmatrix_x4(addr, pack_bf16(v[8 * jp], v[8 * jp + 1]), pack_bf16(v[8 * jp + 2], v[8 * jp + 3]),
                            pack_bf16(v[8 * jp + 4], v[8 * jp + 5]), pack_bf16(v[8 * jp + 6], v[8 * jp + 7]));
            }
            if ((sub & 1) && half == 1) hand_over(2 + wg * 3 + (sub >> 1));
            float n0 = 0.f, n1 = 0.f;
#pragma unroll
            for (int j = 0; j < 4; j++) {
                n0 = fmaf(v[4 * j], v[4 * j], fmaf(v[4 * j + 1], v[4 * j + 1], n0));
                n1 = fmaf(v[4 * j + 2], v[4 * j + 2], fmaf(v[4 * j + 3], v[4 * j + 3], n1));
            }
            const bool odd = lane & 1;
            float full = (odd ? n1 : n0) + __shfl_xor_sync(0xffffffffu, odd ? n0 : n1, 1);
            full += __shfl_xor_sync(0xffffffffu, full, 2);
            const uint32_t mx = __reduce_max_sync(0xffffffffu, __float_as_uint(full));
            if (lane == 0) g_norm[((sub >> 1) * NH + tn * 2 + (sub & 1)) * 128 + tm * 16 + half * 8 + wg * 4 + warp] = mx;
        };
        fence_regs(acc1);
        constexpr int E0 = QKV2_E0;
        step(0, 0, true);
        release(3);
        fence_regs(acc0[0]);
#pragma unroll 1
        for (int j = 1; j <= E0; j++) { step(j & 3, (j >> 2) & 1, false); release((j - 1) & 3); }
        {
            mbar_wait(s.aux, 0);
            const float2 t0 = sst[wg * 64 + warp * 16 + (lane >> 2)], t1 = sst[wg * 64 + warp * 16 + 8 + (lane >> 2)];
#pragma unroll
            for (int sub = 0; sub < 6; sub++) {
                if (sub > 0) { step((E0 + sub) & 3, ((E0 + sub) >> 2) & 1, false); release((E0 + sub - 1) & 3); }
                const float qs = sub < 2 ? qscale : 1.f;
                piece(acc0[0], 0, sub, -t0.x, -t1.x, t0.y * qs, t1.y * qs);
            }
        }
#pragma unroll 1
        for (int k = 22 + E0; k < 32; k++) {
            if (QKV2_SKEW && k == 29 && wg == 1) named_bar(11, 256);
            step(k & 3, (k >> 2) & 1, false);
            if (QKV2_SKEW && k == (QKV2_SKEW == 2 ? 30 : 31) && wg == 0) named_arrive(11, 256);
            if (k <= C::KSTEPS - C::STAGES) release((k - 1) & 3); else wg_wait<1>();
        }
        mbar_wait(s.aux + 8, 0);
        const float2 t2 = sst[128 + wg * 64 + warp * 16 + (lane >> 2)], t3 = sst[128 + wg * 64 + warp * 16 + 8 + (lane >> 2)];
        wg_wait<0>();
        fence_regs(acc1);
        mbar_wait(s.aux + 48, 0);
#pragma unroll
        for (int sub = 0; sub < 6; sub++) {
            const float qs = sub < 2 ? qscale : 1.f;
            piece(acc1, 1, sub, -t2.x, -t3.x, t2.y * qs, t3.y * qs);
        }
    }
}

struct AttnParams { CUtensorMap kv, kv2; unsigned long long dbase; bf16* optr; const uint8_t* pf_wo; const uint8_t* pf_w1; const uint8_t* pf_b1;
                    const uint32_t* norm; void* colsum2; void* rowstat2; void* hpart; };
constexpr int AT_STAGES = 8, AT_STAGE_BYTES = 16384, AT_Q_OFF = AT_STAGES * AT_STAGE_BYTES, AT_ONES_OFF = AT_Q_OFF + 32768, AT_BAR_OFF = AT_ONES_OFF + 1024, AT_SMEM = AT_BAR_OFF + 256;
constexpr uint32_t AT_BASE = 1024;
constexpr int AT_TILES = 32;

__device__ __forceinline__ uint32_t fma_bf16x2(uint32_t a, uint32_t b, uint32_t c) { uint32_t d; asm("fma.rn.bf16x2 %0, %1, %2, %3;" : "=r"(d) : "r"(a), "r"(b), "r"(c)); return d; }
constexpr uint32_t FX_LEAD = 0x3EAB3EABu;
__device__ __forceinline__ uint32_t ex2_pair_fx(float x0, float x1, uint32_t c3, uint32_t one2) {
    const float m = 65663.f;
    const uint32_t w = __byte_perm(__float_as_uint(x0 + m), __float_as_uint(x1 + m), 0x5410);
    uint32_t g, r;
    asm("lop3.b32 %0, %1, 0x007F007F, %2, 0xEA;" : "=r"(g) : "r"(w), "r"(one2));
    uint32_t p = fma_bf16x2(g, c3, 0xBC5DBC5Du);
    p = fma_bf16x2(p, g, 0x3F2F3F2Fu);
    asm("lop3.b32 %0, %1, %2, 0xFF80FF80, 0xE4;" : "=r"(r) : "r"(w), "r"(p));
    return r;
}
template <uint32_t MASK> __device__ __forceinline__ uint32_t attn_exp2(float x0, float x1, int i, uint32_t c3) {
    return ((MASK >> i) & 1) ? ex2_pair_fx(x0, x1, c3, c3 ^ (FX_LEAD ^ 0x3F803F80u)) : pack_bf16(ex2(x0), ex2(x1));
}
__device__ __forceinline__ void attn_issue_tile(const AttnParams& p, uint32_t base, uint32_t full0, int g, int head) {
    const int st = g % AT_STAGES, key0 = (g & 15) * 128;
    const uint32_t bar = full0 + 8 * st, dst = base + st * AT_STAGE_BYTES;
    mbar_expect_tx(bar, AT_STAGE_BYTES);
    tma_ld3(dst, &p.kv2, bar, 0, head * SEQ + key0, 1);
}
__device__ __forceinline__ void attn_qk(float (&sacc)[32], uint32_t q_lo, uint32_t k_lo) {
    mma_qk0(sacc, q_lo, k_lo);
    mma_qk1(sacc, q_lo + 2, k_lo + 2, 1);
}
constexpr uint32_t PV_STEP = 64u - (64u << 16);
constexpr long long PV_STEP64 = 64ll - (64ll << 16);
__device__ __forceinline__ void attn_pv(float (&o)[20], const uint32_t (&pr)[16], uint32_t v_lo, int first) {
#pragma unroll
    for (int kk = 0; kk < 4; kk++)
        mma_pv(o, pr[4 * kk], pr[4 * kk + 1], pr[4 * kk + 2], pr[4 * kk + 3], v_lo + kk * PV_STEP, (kk > 0) || !first);
}
__device__ __forceinline__ void attn_store_o(const float (&o)[20], const AttnParams& p, int head, int row0, int lane) {
    const float r0 = 1.f / o[16], r1 = 1.f / o[18];
    uint32_t a[4], b[4];
#pragma unroll
    for (int j = 0; j < 4; j++) { a[j] = pack_bf16(o[4 * j] * r0, o[4 * j + 1] * r0); b[j] = pack_bf16(o[4 * j + 2] * r1, o[4 * j + 3] * r1); }
    const bool odd = lane & 1, up = lane & 2;
#pragma unroll
    for (int h = 0; h < 2; h++) {
        uint32_t t = __shfl_xor_sync(0xffffffffu, odd ? a[2 * h] : a[2 * h + 1], 1); if (odd) a[2 * h] = t; else a[2 * h + 1] = t;
        t = __shfl_xor_sync(0xffffffffu, odd ? b[2 * h] : b[2 * h + 1], 1); if (odd) b[2 * h] = t; else b[2 * h + 1] = t;
    }
#pragma unroll
    for (int h = 0; h < 2; h++) {
        uint32_t t = __shfl_xor_sync(0xffffffffu, up ? a[h] : a[h + 2], 2); if (up) a[h] = t; else a[h + 2] = t;
        t = __shfl_xor_sync(0xffffffffu, up ? b[h] : b[h + 2], 2); if (up) b[h] = t; else b[h + 2] = t;
    }
    uint4* op = reinterpret_cast<uint4*>(p.optr + (size_t)(row0 + (lane >> 2)) * PITCH + head * HD) + (lane & 3);
    op[0] = make_uint4(a[0], a[1], a[2], a[3]);
    op[8 * (PITCH / 8)] = make_uint4(b[0], b[1], b[2], b[3]);
}
__device__ __forceinline__ void attn_refill(const AttnParams& p, uint32_t base, uint32_t full0, uint32_t empty0, int g, int head) {
    if (threadIdx.x == 0 && g >= 4 && g + 4 < AT_TILES) {
        const int gp = g - 4;
        mbar_wait(empty0 + 8 * (gp % AT_STAGES), (gp / AT_STAGES) & 1);
        attn_issue_tile(p, base, full0, g + 4, head);
    }
    __syncwarp();
}

__device__ __forceinline__ void attn_housekeeping(const AttnParams& p) {
    const int l = threadIdx.x;
    if (l < 128 + 140) prefetch_line(l < 128 ? p.pf_wo + ((size_t)blockIdx.x * 128 + l) * 128 : p.pf_w1 + ((size_t)blockIdx.x * 140 + (l - 128)) * 128);
    if (blockIdx.x == 0 && l >= 300 && l < 300 + 56) prefetch_line(p.pf_b1 + (l - 300) * 128);
    if (l >= 384 && l < 384 + 48) reinterpret_cast<uint4*>(p.colsum2)[blockIdx.x * 48 + l - 384] = make_uint4(0, 0, 0, 0);
    if (l >= 432 && l < 432 + 8) reinterpret_cast<uint4*>(p.rowstat2)[blockIdx.x * 8 + l - 432] = make_uint4(0, 0, 0, 0);
    if (l >= 448) reinterpret_cast<uint4*>(p.hpart)[blockIdx.x * 64 + l - 448] = make_uint4(0, 0, 0, 0);
}
template <uint32_t MASK>
__device__ __forceinline__ void attn_piece(float (&o)[20], const float* sc, uint32_t c3, uint64_t dv) {
    uint32_t pr[8];
#pragma unroll
    for (int i = 0; i < 8; i++) pr[i] = attn_exp2<MASK>(sc[2 * i], sc[2 * i + 1], i, c3);
    wg_fence();
    mma_pvw(o, pr[0], pr[1], pr[2], pr[3], dv, 1);
    mma_pvw(o, pr[4], pr[5], pr[6], pr[7], dv + PV_STEP64, 1);
    wg_commit();
}
__device__ __forceinline__ void attn_fast(const AttnParams& p, uint32_t base, uint32_t full0, uint32_t empty0, int head, int qchunk) {
    const int wg = __shfl_sync(0xffffffffu, threadIdx.x >> 7, 0), warp = (threadIdx.x >> 5) & 3, lane = threadIdx.x & 31;
    const int warp_id = __shfl_sync(0xffffffffu, threadIdx.x >> 5, 0);
    const uint32_t k_lo0 = desc_lo(AT_BASE, 16), v_lo0 = desc_lo(AT_BASE + 8192, AT_ONES_OFF - 8192);
    const uint32_t q_lo0 = desc_lo(AT_BASE + AT_Q_OFF, 16) + wg * (64 * 64 >> 4);
    uint32_t c3;
    asm volatile("ld.shared.u32 %0, [%1];" : "=r"(c3) : "r"(base + AT_ONES_OFF));
    c3 ^= 0x3F803F80u ^ FX_LEAD;
    float sa[32], sb[32];
    const uint64_t HI = p.dbase;
    const uint64_t dk0 = HI + k_lo0, dv0 = HI + v_lo0;
    mbar_wait(full0, 0);
    wg_fence();
    mma_qk0w(sa, HI + q_lo0, dk0);
    mma_qk1w(sa, HI + q_lo0 + 2, dk0 + 2, 1);
    wg_commit();
    wg_wait<0>();
    fence_regs(sa);
#pragma unroll 1
    for (int pass = 0; pass < 2; pass++) {
    const uint32_t q = q_lo0 + pass * (256 * 64 >> 4);
    float o[20];
#pragma unroll
    for (int i = 0; i < 20; i++) o[i] = 0.f;
#pragma unroll 1
    for (int h2 = 0; h2 < 4 / ATTN_UNR; h2++) {
#pragma unroll
    for (int hu = 0; hu < ATTN_UNR; hu++) {
        const int hh = h2 * ATTN_UNR + hu;
        const uint32_t par = hh >> 1, half = hh & 1;
        const int g0 = pass * 16 + hh * 4;
        const uint32_t fb = full0 + half * 32, eb = empty0 + half * 32, eo = empty0 + (half ^ 1) * 32;
        const uint64_t dq = HI + q, dqw = HI + (hh == 3 ? q_lo0 + (256 * 64 >> 4) : q);
        const uint64_t dkh = dk0 + half * (4 * AT_STAGE_BYTES >> 4), dkn = dk0 + (half ^ 1) * (4 * AT_STAGE_BYTES >> 4), dvh = dv0 + (long long)half * (64 * PV_STEP64);
#pragma unroll
        for (int j = 0; j < 4; j++) {
            if (warp_id == j * 5) {
                if (g0 + 4 < AT_TILES && elect_one()) {
                    if (g0 >= 4) mbar_wait(eo + 8 * j, half ? par : (par ^ 1));
                    const uint32_t bar = full0 + (half ^ 1) * 32 + 8 * j;
                    mbar_expect_tx(bar, AT_STAGE_BYTES);
                    tma_ld3(base + ((half ^ 1) * 4 + j) * AT_STAGE_BYTES, &p.kv2, bar, 0, head * SEQ + ((g0 + 4 + j) & 15) * 128, 1);
                }
                __syncwarp();
            }
            wg_fence();
            const uint64_t kb = dkh + j * (AT_STAGE_BYTES >> 4), vb = dvh + j * 16 * PV_STEP64;
            mma_qk0w(sb, dq, kb + 256);
            mma_qk1w(sb, dq + 2, kb + 258, 1);
            wg_commit();
            wg_wait<2>();
            fence_regs(sa);
            attn_piece<QMASK_0>(o, sa, c3, vb);
            wg_wait<2>();
            if (lane == 0 && (j > 0 || g0 > 0)) mbar_arrive(j > 0 ? eb + 8 * (j - 1) : eo + 24);
            attn_piece<QMASK_1>(o, sa + 16, c3, vb + 2 * PV_STEP64);
            if (j < 3) mbar_wait(fb + 8 * (j + 1), par);
            else {
                if (g0 < 28) mbar_wait(full0 + (half ^ 1) * 32, half ? par ^ 1 : par);
                if (g0 == 12) mbar_wait(empty0 + 8 * AT_STAGES + 8, 0);
            }
            wg_fence();
            { const uint64_t qq = j < 3 ? dq : dqw, kn = j < 3 ? dkh + (j + 1) * (AT_STAGE_BYTES >> 4) : dkn;
              mma_qk0w(sa, qq, kn);
              mma_qk1w(sa, qq + 2, kn + 2, 1); }
            wg_commit();
            wg_wait<2>();
            fence_regs(sb);
            attn_piece<QMASK_2>(o, sb, c3, vb + 4 * PV_STEP64);
            wg_wait<2>();
            attn_piece<QMASK_3>(o, sb + 16, c3, vb + 6 * PV_STEP64);
        }
        if (hu == ATTN_UNR - 1) {
            wg_wait<0>();
            fence_regs(sa);
            fence_regs(o);
        }
    }
    }
    attn_store_o(o, p, head, qchunk * 512 + pass * 256 + wg * 64 + warp * 16, lane);
    if (pass == 0) attn_housekeeping(p);
    }
}

__device__ __forceinline__ void attn_safe(const AttnParams& p, uint32_t base, uint32_t full0, uint32_t empty0, int head, int qchunk) {
    const int wg = __shfl_sync(0xffffffffu, threadIdx.x >> 7, 0), warp = (threadIdx.x >> 5) & 3, lane = threadIdx.x & 31;
    const uint32_t k_lo0 = desc_lo(base, 16), v_lo0 = desc_lo(base + 8192, AT_ONES_OFF - 8192);
#pragma unroll 1
    for (int pass = 0; pass < 2; pass++) {
        const uint32_t q = desc_lo(base + AT_Q_OFF + (pass * 256 + wg * 64) * 64, 16);
        float o[20];
#pragma unroll
        for (int i = 0; i < 20; i++) o[i] = 0.f;
        float m0 = -INFINITY, m1 = -INFINITY;
#pragma unroll 1
        for (int t = 0; t < 32; t++) {
            const int g = pass * 16 + (t >> 1), half = t & 1;
            const int st = g % AT_STAGES;
            const uint32_t kb = k_lo0 + st * (AT_STAGE_BYTES >> 4), vb = v_lo0 + st * 16 * PV_STEP;
            if (half == 0) { attn_refill(p, base, full0, empty0, g, head); mbar_wait(full0 + 8 * st, (g / AT_STAGES) & 1); }
            float cur[32];
            wg_fence();
            attn_qk(cur, q, kb + half * 256);
            wg_commit();
            wg_wait<0>();
            fence_regs(cur);
            float x0 = cur[0], x1 = cur[2];
#pragma unroll
            for (int i = 0; i < 8; i++) { x0 = fmaxf(x0, fmaxf(cur[4 * i], cur[4 * i + 1])); x1 = fmaxf(x1, fmaxf(cur[4 * i + 2], cur[4 * i + 3])); }
            x0 = fmaxf(x0, __shfl_xor_sync(0xffffffffu, x0, 1)); x1 = fmaxf(x1, __shfl_xor_sync(0xffffffffu, x1, 1));
            x0 = fmaxf(x0, __shfl_xor_sync(0xffffffffu, x0, 2)); x1 = fmaxf(x1, __shfl_xor_sync(0xffffffffu, x1, 2));
            const float n0 = fmaxf(m0, x0), n1 = fmaxf(m1, x1);
            const float a0 = ex2(m0 - n0), a1 = ex2(m1 - n1);
            m0 = n0; m1 = n1;
            uint32_t pr[16];
#pragma unroll
            for (int i = 0; i < 8; i++) {
                pr[2 * i] = pack_bf16(ex2(cur[4 * i] - n0), ex2(cur[4 * i + 1] - n0));
                pr[2 * i + 1] = pack_bf16(ex2(cur[4 * i + 2] - n1), ex2(cur[4 * i + 3] - n1));
            }
#pragma unroll
            for (int i = 0; i < 5; i++) { o[4 * i] *= a0; o[4 * i + 1] *= a0; o[4 * i + 2] *= a1; o[4 * i + 3] *= a1; }
            wg_fence();
            attn_pv(o, pr, vb + half * 4 * PV_STEP, 0);
            wg_commit();
            wg_wait<0>();
            fence_regs(o);
            if (half == 1 && lane == 0) mbar_arrive(empty0 + 8 * st);
        }
        attn_store_o(o, p, head, qchunk * 512 + pass * 256 + wg * 64 + warp * 16, lane);
        if (pass == 0) attn_housekeeping(p);
    }
}

__global__ void __launch_bounds__(512, 1) attn_kernel(const __grid_constant__ AttnParams p) {
    extern __shared__ __align__(1024) uint8_t smem_raw[];
    pdl_launch();
    const uint32_t base = smem_u32(smem_raw);
    const uint32_t full0 = base + AT_BAR_OFF, empty0 = full0 + 8 * AT_STAGES;
    const int head = blockIdx.x >> 2, qchunk = blockIdx.x & 3;
    if (threadIdx.x == 0) {
        if (base & 1023) __trap();
        prefetch_map(&p.kv); prefetch_map(&p.kv2);
        for (int i = 0; i < AT_STAGES; i++) { mbar_init(full0 + 8 * i, 1); mbar_init(empty0 + 8 * i, 16); }
        mbar_init(empty0 + 8 * AT_STAGES, 1); mbar_init(empty0 + 8 * AT_STAGES + 8, 1);
        fence_barrier_init();
    }
    if (threadIdx.x < 256) reinterpret_cast<uint32_t*>(smem_raw + AT_ONES_OFF)[threadIdx.x] = 0x3F803F80u;
    fence_proxy_async();
    const uint4* nrm = reinterpret_cast<const uint4*>(p.norm) + head * 32 + (threadIdx.x & 31);
    __syncthreads();
    pdl_wait();
    uint4 nq, nk, nv;
    asm volatile("ld.global.cg.v4.u32 {%0, %1, %2, %3}, [%4];" : "=r"(nq.x), "=r"(nq.y), "=r"(nq.z), "=r"(nq.w) : "l"(nrm) : "memory");
    asm volatile("ld.global.cg.v4.u32 {%0, %1, %2, %3}, [%4];" : "=r"(nk.x), "=r"(nk.y), "=r"(nk.z), "=r"(nk.w) : "l"(nrm + NH * 32) : "memory");
    asm volatile("ld.global.cg.v4.u32 {%0, %1, %2, %3}, [%4];" : "=r"(nv.x), "=r"(nv.y), "=r"(nv.z), "=r"(nv.w) : "l"(nrm + 2 * NH * 32) : "memory");
    const int wid = __shfl_sync(0xffffffffu, threadIdx.x >> 5, 0);
    if (wid == 0 && elect_one()) {
        const uint32_t qbar = empty0 + 8 * AT_STAGES;
        mbar_expect_tx(qbar, 16384);
        tma_ld2(base + AT_Q_OFF, &p.kv, qbar, 0, head * SEQ + qchunk * 512);
    }
    if (wid == 4 && elect_one()) {
        for (int g = 0; g < 4; g++) attn_issue_tile(p, base, full0, g, head);
        const uint32_t qbar = empty0 + 8 * AT_STAGES + 8;
        mbar_expect_tx(qbar, 16384);
        tma_ld2(base + AT_Q_OFF + 16384, &p.kv, qbar, 0, head * SEQ + qchunk * 512 + 256);
    }
    __syncwarp();
    const float qn = __uint_as_float(__reduce_max_sync(0xffffffffu, max(max(nq.x, nq.y), max(nq.z, nq.w))));
    const float kn = __uint_as_float(__reduce_max_sync(0xffffffffu, max(max(nk.x, nk.y), max(nk.z, nk.w))));
    const float vn = __uint_as_float(__reduce_max_sync(0xffffffffu, max(max(nv.x, nv.y), max(nv.z, nv.w))));
    const bool bounded = (qn * kn <= 1.0e4f) && (vn <= 1.0e9f) && (base & 0xFFFFFFu) == AT_BASE;
    mbar_wait(empty0 + 8 * AT_STAGES, 0);
    if (bounded) attn_fast(p, base, full0, empty0, head, qchunk);
    else {
        if (threadIdx.x == 0) for (int g = 4; g < AT_STAGES; g++) attn_issue_tile(p, base, full0, g, head);
        mbar_wait(empty0 + 8 * AT_STAGES + 8, 0);
        attn_safe(p, base, full0, empty0, head, qchunk);
    }
}

struct ResParams { CUtensorMap a, b, res, out; const bf16* bias; };
template <bool MIX2>
struct ResCfg {
    static constexpr int MB = 1, BN = 128, KSTEPS = MIX2 ? 56 : 16, STAGES = 6, A_BYTES = 16384, B_BYTES = 16384;
    static constexpr int STAGE_BYTES = A_BYTES + B_BYTES, STG_OFF = STAGES * STAGE_BYTES, BAR_OFF = STG_OFF + 32768, SMEM = BAR_OFF + 128;
    static constexpr int AUX_COUNT = 1, PRE = MIX2 ? MIX2_PRE : WO_PRE;
    static constexpr bool FIRST_BY_THREADS = false;
    static constexpr bool MC = false, ACC_INIT = true;
    static constexpr int FOLLOW = 0;
    static __device__ __forceinline__ void after_release(const ResParams&, const GemmSmem&, int, int, int) {}
    static __device__ __forceinline__ void producer_done(const GemmSmem&) {}
    static __device__ __forceinline__ void load_w(const ResParams& p, uint32_t sb, uint32_t bar, int k, int tm, int tn) {
        if (MIX2) tma_ld3(sb, &p.a, bar, 0, k * 64, tm * 2);
        else tma_ld3(sb + A_BYTES, &p.b, bar, 0, k * 64, tn * 2);
    }
    static __device__ __forceinline__ void load_x(const ResParams& p, uint32_t sb, uint32_t bar, int k, int tm, int tn) {
        if (MIX2) tma_ld2(sb + A_BYTES, &p.b, bar, k * 64, tn * 128);
        else tma_ld2(sb, &p.a, bar, k * 64, tm * 128);
    }
    static __device__ __forceinline__ void load_aux(const ResParams& p, const GemmSmem& s, int tm, int tn) {
        mbar_expect_tx(s.aux, 32768);
        tma_ld2(s.base + STG_OFF, &p.res, s.aux, tn * 128, tm * 128);
        tma_ld2(s.base + STG_OFF + 16384, &p.res, s.aux, tn * 128 + 64, tm * 128);
    }
    static __device__ __forceinline__ uint32_t desc_a(uint32_t sb, int wg, int m, int kk) {
        return MIX2 ? desc_lo(sb + wg * 8192 + kk * 2048, 8192) : desc_lo(sb + wg * 8192 + kk * 32, 16);
    }
    static __device__ __forceinline__ uint32_t desc_b(uint32_t sb, int kk) {
        return MIX2 ? desc_lo(sb + A_BYTES + kk * 32, 16) : desc_lo(sb + A_BYTES + kk * 2048, 8192);
    }
    static __device__ __forceinline__ void mma(float (&d)[64], uint32_t a, uint32_t b, int sc) {
        if (MIX2) mma_mix2(d, a, b, sc); else mma_wo(d, a, b, sc);
    }
};
template <bool MIX2>
__global__ void __launch_bounds__(384, 1) res_gemm_kernel(const __grid_constant__ ResParams p) {
    using C = ResCfg<MIX2>;
    extern __shared__ __align__(1024) uint8_t smem_raw[];
    if (!MIX2) pdl_launch();
    const int tm = blockIdx.x >> 3, tn = blockIdx.x & 7;
    if (threadIdx.x == 0) { prefetch_map(&p.a); prefetch_map(&p.b); prefetch_map(&p.res); prefetch_map(&p.out); }
    const GemmSmem s = gemm_setup<C>(smem_raw);
    const int wgi = __shfl_sync(0xffffffffu, threadIdx.x >> 7, 0);
    if (wgi == 0) {
        reg_dealloc<40>();
        if (__shfl_sync(0xffffffffu, threadIdx.x >> 5, 0) == 0) {
            const bool leader = elect_one();
            if (leader) gemm_producer<C>(s, p, tm, tn);
            __syncwarp();
#pragma unroll 1
            for (int i = 0; i < 4; i++) {
                constexpr bool SKEWED = (MIX2 ? MIX2_SKEW : WO_SKEW) > 0;
                const int b = SKEWED ? i & 1 : i >> 1, wg = SKEWED ? i >> 1 : i & 1;
                take_over(2 + b * 2 + wg);
                if (leader) tma_st2(&p.out, s.base + C::STG_OFF + b * 16384 + wg * 8192, tn * 128 + b * 64, tm * 128 + wg * 64);
            }
            if (leader) { tma_st_commit(); tma_st_wait(); }
        }
    } else {
        reg_alloc<232>();
        const int wg = wgi - 1, warp = (threadIdx.x >> 5) & 3, lane = threadIdx.x & 31;
        const int r0 = wg * 64 + warp * 16 + (lane >> 2);
        const int arow = wg * 64 + warp * 16 + ((lane >> 3) & 1) * 8 + (lane & 7);
        const uint32_t stg = s.base + C::STG_OFF + arow * 128;
        float acc[1][64];
        {
            float a0 = 1.f, a1 = 1.f, c0 = 0.f, c1 = 0.f;
            if (MIX2) {
                const float2 t0 = __ldcg(&g_rowln[tm * 128 + r0]), t1 = __ldcg(&g_rowln[tm * 128 + r0 + 8]);
                a0 = t0.y; a1 = t1.y;
                c0 = t0.x + __bfloat162float(p.bias[tm * 128 + r0]); c1 = t1.x + __bfloat162float(p.bias[tm * 128 + r0 + 8]);
            }
            mbar_wait(s.aux, 0);
#pragma unroll
            for (int jp = 0; jp < 8; jp++) {
                const int chunk = jp * 2 + (lane >> 4);
                uint32_t r[4];
                ldmatrix_x4(stg + (chunk >> 3) * 16384 + (((chunk & 7) ^ (arow & 7)) << 4), r);
#pragma unroll
                for (int i = 0; i < 4; i++) {
                    const float a = (i & 1) ? a1 : a0, c = (i & 1) ? c1 : c0;
                    acc[0][jp * 8 + 2 * i] = MIX2 ? fmaf(bf_lo(r[i]), a, c) : bf_lo(r[i]);
                    acc[0][jp * 8 + 2 * i + 1] = MIX2 ? fmaf(bf_hi(r[i]), a, c) : bf_hi(r[i]);
                }
            }
        }
        pdl_wait();
        constexpr int SK = MIX2 ? MIX2_SKEW : WO_SKEW;
        gemm_mainloop<C, C::KSTEPS, SK>(s, wg, acc);
        float sc0 = 1.f, sc1 = 1.f, of0 = 0.f, of1 = 0.f;
        if (!MIX2) {
            float s0 = 0.f, s1 = 0.f;
#pragma unroll
            for (int j = 0; j < 16; j++) { s0 += acc[0][4 * j] + acc[0][4 * j + 1]; s1 += acc[0][4 * j + 2] + acc[0][4 * j + 3]; }
            s0 += __shfl_xor_sync(0xffffffffu, s0, 1); s1 += __shfl_xor_sync(0xffffffffu, s1, 1);
            s0 += __shfl_xor_sync(0xffffffffu, s0, 2); s1 += __shfl_xor_sync(0xffffffffu, s1, 2);
            const float m0 = s0 * (1.f / 128), m1 = s1 * (1.f / 128);
            float q0 = 0.f, q1 = 0.f;
#pragma unroll
            for (int j = 0; j < 16; j++) {
                const float a = acc[0][4 * j] - m0, b = acc[0][4 * j + 1] - m0, c = acc[0][4 * j + 2] - m1, d = acc[0][4 * j + 3] - m1;
                q0 = fmaf(a, a, fmaf(b, b, q0)); q1 = fmaf(c, c, fmaf(d, d, q1));
            }
            q0 += __shfl_xor_sync(0xffffffffu, q0, 1); q1 += __shfl_xor_sync(0xffffffffu, q1, 1);
            q0 += __shfl_xor_sync(0xffffffffu, q0, 2); q1 += __shfl_xor_sync(0xffffffffu, q1, 2);
            const int wrow = tm * 128 + wg * 64 + warp * 16;
            if ((lane & 3) < 2) {
                const float m = (lane & 1) ? m1 : m0, q = (lane & 1) ? q1 : q0;
                const unsigned long long w = ((unsigned long long)(__float_as_uint(q) | 0x80000000u) << 32) | __float_as_uint(m);
                asm volatile("st.relaxed.gpu.global.u64 [%0], %1;" :: "l"(g_hpart + tn * SEQ + wrow + (lane >> 2) + (lane & 1) * 8), "l"(w) : "memory");
            }
            const unsigned long long* part = g_hpart + (lane >> 2) * SEQ + wrow + (lane & 3) * 4;
            unsigned long long t[4];
            int it = 0;
            bool ok;
            do {
                asm volatile("ld.relaxed.gpu.global.v2.u64 {%0, %1}, [%2];" : "=l"(t[0]), "=l"(t[1]) : "l"(part) : "memory");
                asm volatile("ld.relaxed.gpu.global.v2.u64 {%0, %1}, [%2];" : "=l"(t[2]), "=l"(t[3]) : "l"(part + 2) : "memory");
                ok = (long long)(t[0] & t[1] & t[2] & t[3]) < 0;
                if (++it > (1 << 20)) __trap();
            } while (!__all_sync(0xffffffffu, ok));
            float mt[4], qt[4];
#pragma unroll
            for (int i = 0; i < 4; i++) {
                const float mi = __uint_as_float((uint32_t)t[i]), qi = __uint_as_float((uint32_t)(t[i] >> 32) & 0x7FFFFFFFu);
                float m = mi;
                m += __shfl_xor_sync(0xffffffffu, m, 4); m += __shfl_xor_sync(0xffffffffu, m, 8); m += __shfl_xor_sync(0xffffffffu, m, 16);
                m *= 0.125f;
                float q = fmaf(128.f * (mi - m), mi - m, qi);
                q += __shfl_xor_sync(0xffffffffu, q, 4); q += __shfl_xor_sync(0xffffffffu, q, 8); q += __shfl_xor_sync(0xffffffffu, q, 16);
                mt[i] = m; qt[i] = q;
            }
            const int sel = (lane >> 2) & 3;
            const float mean = sel == 0 ? mt[0] : sel == 1 ? mt[1] : sel == 2 ? mt[2] : mt[3];
            const float var = (sel == 0 ? qt[0] : sel == 1 ? qt[1] : sel == 2 ? qt[2] : qt[3]) * (1.f / DM);
            const float r1 = rsqrtf(var + 1e-5f);
            const float r2 = rsqrtf(var * r1 * r1 + 1e-5f);
            const float scale = 0.5f * r1 * r2, off = -mean * scale;
            if (tn == 0 && lane < 16) g_rowln[wrow + 4 * (lane & 3) + sel] = make_float2(mean, 1.f / scale);
            const int ra = lane >> 2, src0 = ((ra & 3) << 2) | (ra >> 2);
            sc0 = __shfl_sync(0xffffffffu, scale, src0); of0 = __shfl_sync(0xffffffffu, off, src0);
            sc1 = __shfl_sync(0xffffffffu, scale, src0 + 2); of1 = __shfl_sync(0xffffffffu, off, src0 + 2);
        }
#pragma unroll
        for (int jp = 0; jp < 8; jp++) {
            const int chunk = jp * 2 + (lane >> 4);
            uint32_t r[4];
#pragma unroll
            for (int i = 0; i < 4; i++) {
                const float sc = (i & 1) ? sc1 : sc0, of = (i & 1) ? of1 : of0;
                const float v0 = acc[0][jp * 8 + 2 * i], v1 = acc[0][jp * 8 + 2 * i + 1];
                r[i] = MIX2 ? pack_bf16(v0, v1) : pack_bf16(fmaf(v0, sc, of), fmaf(v1, sc, of));
            }
            stmatrix_x4(stg + (chunk >> 3) * 16384 + (((chunk & 7) ^ (arow & 7)) << 4), r[0], r[1], r[2], r[3]);
            if ((jp & 3) == 3) hand_over(2 + (jp >> 2) * 2 + wg);
        }
    }
}

struct Mix1Params { CUtensorMap hn, w1, out; const bf16* bias; const uint8_t* pf; };
struct Mix1Cfg {
    static constexpr int MB = 1, BN = 224, KSTEPS = 32, STAGES = 5, A_BYTES = 16384, B_BYTES = 28672;
    static constexpr int STAGE_BYTES = A_BYTES + B_BYTES, BAR_OFF = STAGES * STAGE_BYTES, SMEM = BAR_OFF + 128;
    static constexpr int AUX_COUNT = 1, PRE = MIX1_PRE;
    static constexpr bool MC = true, ACC_INIT = true, FIRST_BY_THREADS = false;
    static constexpr int FOLLOW = 0;
    static __device__ __forceinline__ void after_release(const Mix1Params&, const GemmSmem&, int, int, int) {}
    static __device__ __forceinline__ void producer_done(const GemmSmem&) {}
    static __device__ __forceinline__ void load_w(const Mix1Params& p, uint32_t sb, uint32_t bar, int k, int tm, int tn) {
        tma_ld3_mc(sb + A_BYTES + (tm & 1) * (B_BYTES / 2), &p.w1, bar, 0, k * 64 + (tm & 1) * 32, tn * 7);
    }
    static __device__ __forceinline__ void load_x(const Mix1Params& p, uint32_t sb, uint32_t bar, int k, int tm, int tn) { tma_ld3(sb, &p.hn, bar, 0, k * 64, tm * 2); }
    static __device__ __forceinline__ void load_aux(const Mix1Params&, const GemmSmem&, int, int) {}
    static __device__ __forceinline__ uint32_t desc_a(uint32_t sb, int wg, int m, int kk) { return desc_lo(sb + wg * 8192 + kk * 2048, 8192); }
    static __device__ __forceinline__ uint32_t desc_b(uint32_t sb, int kk) { return desc_lo(sb + A_BYTES + (kk >> 1) * (B_BYTES / 2) + (kk & 1) * 1024, 2048); }
    static __device__ __forceinline__ void mma(float (&d)[112], uint32_t a, uint32_t b, int sc) { mma_mix1(d, a, b, sc); }
    static __device__ __forceinline__ uint32_t stage_off(int wg) { return (2 + wg) * STAGE_BYTES; }
};
__global__ void __launch_bounds__(384, 1) mix1_kernel(const __grid_constant__ Mix1Params p) {
    using C = Mix1Cfg;
    extern __shared__ __align__(1024) uint8_t smem_raw[];
    const int tm = blockIdx.x & 7, tn = blockIdx.x >> 3;
    if (threadIdx.x == 0) { prefetch_map(&p.hn); prefetch_map(&p.w1); prefetch_map(&p.out); }
    const GemmSmem s = gemm_setup<C>(smem_raw, [](const GemmSmem& g) { asm volatile("st.shared.f32 [%0], %1;" :: "r"(g.aux + 16), "f"(2.f * 0.7978845608029f) : "memory"); });
    const int wgi = __shfl_sync(0xffffffffu, threadIdx.x >> 7, 0);
    if (wgi == 0) {
        reg_dealloc<40>();
        const int wid = __shfl_sync(0xffffffffu, threadIdx.x >> 5, 0);
        if (wid == 0) {
            const bool leader = elect_one();
            if (leader) gemm_producer<C>(s, p, tm, tn);
            __syncwarp();
#pragma unroll 1
            for (int i = 0; i < 8; i++) {
                const int wg = i >> 2, b = MIX1_PAT ? max((i & 3) * 2 - 1, 0) : (i & 3) * 2;
                take_over(2 + i);
                if (leader) {
                    tma_st3(&p.out, s.base + C::stage_off(wg) + b * 4096, 0, tm * 128 + wg * 64, tn * 7 + b);
                    if (MIX1_PAT ? (i & 3) != 0 : b < 6) tma_st3(&p.out, s.base + C::stage_off(wg) + (b + 1) * 4096, 0, tm * 128 + wg * 64, tn * 7 + b + 1);
                }
            }
            if (leader) { tma_st_commit(); tma_st_wait(); }
        } else if (wid == 1) {
            pdl_wait();
            __nanosleep(PF_W2_DELAY);
#pragma unroll 1
            for (int i = 0; i < 4; i++) prefetch_line(p.pf + ((size_t)blockIdx.x * 128 + i * 32 + (threadIdx.x & 31)) * 128);
        }
    } else {
        reg_alloc<232>();
        const int wg = wgi - 1, warp = (threadIdx.x >> 5) & 3, lane = threadIdx.x & 31;
        float acc[1][112];
        {
            const uint32_t* bp = reinterpret_cast<const uint32_t*>(p.bias + tn * 224) + (lane & 3);
#pragma unroll
            for (int j = 0; j < 28; j++) {
                const uint32_t b2 = __ldg(bp + j * 4);
                acc[0][4 * j] = acc[0][4 * j + 2] = 0.5f * bf_lo(b2);
                acc[0][4 * j + 1] = acc[0][4 * j + 3] = 0.5f * bf_hi(b2);
            }
        }
        pdl_wait();
        pdl_launch();
        const int arow = warp * 16 + ((lane >> 3) & 1) * 8 + (lane & 7);
        float c1 = 0.f;
        auto next_piece = [&]() { c1 = MIX1_PIN ? lds_f32(s.aux + 16) : 2.f * 0.7978845608029f; };
        auto out_pair = [&](int jp, uint32_t stg) {
            float v[8];
#pragma unroll
            for (int i = 0; i < 8; i++) {
                const float hx = acc[0][jp * 8 + i];
                v[i] = fmaf(hx, tanh_fast(hx * fmaf(hx * hx, 8.f * 0.0356774081363f, c1)), hx);
            }
            const int j = (jp & 1) * 2 + (lane >> 4);
            stmatrix_x4(stg + arow * 64 + ((j ^ ((arow >> 1) & 3)) << 4), pack_bf16(v[0], v[1]), pack_bf16(v[2], v[3]), pack_bf16(v[4], v[5]), pack_bf16(v[6], v[7]));
        };
        gemm_mainloop<C, 32, MIX1_SKEW, true>(s, wg, acc);
        if (wg == 0) { named_arrive(12, 256); named_bar(10, 256); }
        else named_bar(12, 256);
#pragma unroll
        for (int jp = 0; jp < 14; jp++) {
            const int jq = jp + MIX1_PAT * 2;
            if (jp == 0 || (jq & 3) == 0) next_piece();
            out_pair(jp, s.base + C::stage_off(wg) + (jp >> 1) * 4096);
            if ((jq & 3) == 3 || jp == 13) hand_over(2 + wg * 4 + (jq >> 2));
        }
    }
}

typedef CUresult (*EncodeFn)(CUtensorMap*, CUtensorMapDataType, cuuint32_t, void*, const cuuint64_t*, const cuuint64_t*, const cuuint32_t*,
                             const cuuint32_t*, CUtensorMapInterleave, CUtensorMapSwizzle, CUtensorMapL2promotion, CUtensorMapFloatOOBfill);
EncodeFn g_encode;

void make_map(CUtensorMap* m, const void* ptr, int rank, const uint64_t* dims, const uint64_t* strides_bytes, const uint32_t* box, CUtensorMapSwizzle swz) {
    cuuint64_t d[5], st[5]; cuuint32_t b[5], es[5];
    for (int i = 0; i < rank; i++) { d[i] = dims[i]; b[i] = box[i]; es[i] = 1; }
    for (int i = 0; i + 1 < rank; i++) st[i] = strides_bytes[i];
    CUresult r = g_encode(m, CU_TENSOR_MAP_DATA_TYPE_BFLOAT16, rank, const_cast<void*>(ptr), d, st, b, es, CU_TENSOR_MAP_INTERLEAVE_NONE, swz,
                          CU_TENSOR_MAP_L2_PROMOTION_L2_128B, CU_TENSOR_MAP_FLOAT_OOB_FILL_NONE);
    if (r != CUDA_SUCCESS) fprintf(stderr, "cuTensorMapEncodeTiled failed: %d\n", (int)r);
}
void map2d(CUtensorMap* m, const void* ptr, uint64_t cols, uint64_t rows, uint32_t bc, uint32_t br, CUtensorMapSwizzle swz, uint64_t pitch = 0) {
    uint64_t dims[2] = {cols, rows}, st[1] = {(pitch ? pitch : cols) * 2}; uint32_t box[2] = {bc, br};
    make_map(m, ptr, 2, dims, st, box, swz);
}
void map3d(CUtensorMap* m, const void* ptr, uint64_t cols, uint64_t rows, uint32_t inner, uint32_t br, uint32_t nblk, CUtensorMapSwizzle swz, uint64_t pitch = 0) {
    uint64_t dims[3] = {inner, rows, cols / inner}, st[2] = {(pitch ? pitch : cols) * 2, (uint64_t)inner * 2}; uint32_t box[3] = {inner, br, nblk};
    make_map(m, ptr, 3, dims, st, box, swz);
}

template <class... KArgs, class... Args>
void launch(void (*kern)(KArgs...), int grid, int block, int smem, bool pdl, bool pair, Args&&... args) {
    cudaLaunchConfig_t cfg = {};
    cfg.gridDim = dim3(grid); cfg.blockDim = dim3(block); cfg.dynamicSmemBytes = smem; cfg.stream = 0;
    cudaLaunchAttribute at[2];
    int n = 0;
    if (pdl) { at[n].id = cudaLaunchAttributeProgrammaticStreamSerialization; at[n].val.programmaticStreamSerializationAllowed = 1; n++; }
    if (pair) { at[n].id = cudaLaunchAttributeClusterDimension; at[n].val.clusterDim.x = 2; at[n].val.clusterDim.y = 1; at[n].val.clusterDim.z = 1; n++; }
    cfg.attrs = at; cfg.numAttrs = n;
    cudaError_t e = cudaLaunchKernelEx(&cfg, kern, KArgs(args)...);
    if (e != cudaSuccess) fprintf(stderr, "launch failed: %s\n", cudaGetErrorString(e));
}

struct HostState {
    bool ready;
    const void* key[9];
    QkvParams qkv; AttnParams attn; ResParams wo, mix2; Mix1Params mix1;
    bf16 *qkvp, *o, *hn, *u;
};
HostState g_hs;

}

extern "C" void kernel_launch(void* const* d_in, const int* in_sizes, int n_in, void* d_out, int out_size) {
    const bf16* x = (const bf16*)d_in[0];
    const bf16* wqkv = (const bf16*)d_in[1];
    const bf16* wo = (const bf16*)d_in[2];
    const bf16* w1 = (const bf16*)d_in[4];
    const bf16* b1 = (const bf16*)d_in[5];
    const bf16* w2 = (const bf16*)d_in[6];
    const bf16* b2 = (const bf16*)d_in[7];
    HostState& hs = g_hs;
    bool same = hs.ready;
    for (int i = 0; i < 8 && same; i++) same = (hs.key[i] == d_in[i]);
    same = same && hs.key[8] == d_out;
    if (!same) {
        if (!g_encode) {
            void* fn = nullptr; cudaDriverEntryPointQueryResult qr;
            cudaGetDriverEntryPoint("cuTensorMapEncodeTiled", &fn, cudaEnableDefault, &qr);
            g_encode = (EncodeFn)fn;
            cudaFuncSetAttribute(qkv_kernel, cudaFuncAttributeMaxDynamicSharedMemorySize, QkvCfg::SMEM);
            cudaFuncSetAttribute(attn_kernel, cudaFuncAttributeMaxDynamicSharedMemorySize, AT_SMEM);
            cudaFuncSetAttribute(res_gemm_kernel<false>, cudaFuncAttributeMaxDynamicSharedMemorySize, ResCfg<false>::SMEM);
            cudaFuncSetAttribute(res_gemm_kernel<true>, cudaFuncAttributeMaxDynamicSharedMemorySize, ResCfg<true>::SMEM);
            cudaFuncSetAttribute(mix1_kernel, cudaFuncAttributeMaxDynamicSharedMemorySize, Mix1Cfg::SMEM);
        }
        cudaGetSymbolAddress((void**)&hs.qkvp, g_qkv); cudaGetSymbolAddress((void**)&hs.o, g_o);
        cudaGetSymbolAddress((void**)&hs.hn, g_hn); cudaGetSymbolAddress((void**)&hs.u, g_u);
        const CUtensorMapSwizzle S128 = CU_TENSOR_MAP_SWIZZLE_128B, S64 = CU_TENSOR_MAP_SWIZZLE_64B;
        map2d(&hs.qkv.x, x, DM, SEQ, 64, 128, S128);
        hs.qkv.xp = x; hs.qkv.wp = wqkv;
        {
            uint64_t dims[4] = {64, (uint64_t)DM, 3, 16}, st[3] = {3 * DM * 2, DM * 2, 128}; uint32_t box[4] = {64, 32, 3, 1};
            make_map(&hs.qkv.w, wqkv, 4, dims, st, box, S128);
        }
        map2d(&hs.qkv.out, hs.qkvp, HD, 3 * NH * SEQ, 32, 64, S64);
        map2d(&hs.attn.kv, hs.qkvp, HD, 3 * NH * SEQ, 32, 256, S64);
        hs.attn.optr = hs.o;
        {
            uint64_t dims[3] = {(uint64_t)HD, (uint64_t)NH * SEQ, 3}, st[2] = {HD * 2, (uint64_t)NH * SEQ * HD * 2}; uint32_t box[3] = {32, 128, 2};
            make_map(&hs.attn.kv2, hs.qkvp, 3, dims, st, box, S64);
        }
        map2d(&hs.wo.a, hs.o, DM, SEQ, 64, 128, S128, PITCH);
        map3d(&hs.wo.b, wo, DM, DM, 64, 64, 2, S128);
        map2d(&hs.wo.res, x, DM, SEQ, 64, 128, S128);
        map2d(&hs.wo.out, hs.hn, DM, SEQ, 64, 64, S128, PITCH);
        hs.wo.bias = nullptr;
        map3d(&hs.mix1.hn, hs.hn, DM, SEQ, 64, 64, 2, S128, PITCH);
        map3d(&hs.mix1.w1, w1, FF, SEQ, 32, 32, 7, S64);
        hs.mix1.pf = (const uint8_t*)w2;
        hs.attn.dbase = 0x8000002000000000ull;
        cudaGetSymbolAddress((void**)&hs.attn.norm, g_norm); cudaGetSymbolAddress(&hs.attn.colsum2, g_colsum2); cudaGetSymbolAddress(&hs.attn.rowstat2, g_rowstat2);
        cudaGetSymbolAddress(&hs.attn.hpart, g_hpart);
        hs.attn.pf_wo = (const uint8_t*)wo; hs.attn.pf_w1 = (const uint8_t*)w1; hs.attn.pf_b1 = (const uint8_t*)b1;
        map3d(&hs.mix1.out, hs.u, FF, DM, 32, 64, 1, S64);
        hs.mix1.bias = b1;
        map3d(&hs.mix2.a, w2, SEQ, FF, 64, 64, 2, S128);
        map2d(&hs.mix2.b, hs.u, FF, DM, 64, 128, S128);
        map2d(&hs.mix2.res, hs.hn, DM, SEQ, 64, 128, S128, PITCH);
        map2d(&hs.mix2.out, d_out, DM, SEQ, 64, 64, S128);
        hs.mix2.bias = b2;
        for (int i = 0; i < 8; i++) hs.key[i] = d_in[i];
        hs.key[8] = d_out;
        hs.ready = true;
    }
    launch(qkv_kernel, 128, 384, QkvCfg::SMEM, false, true, hs.qkv);
    launch(attn_kernel, 128, 512, AT_SMEM, true, false, hs.attn);
    launch(res_gemm_kernel<false>, 128, 384, ResCfg<false>::SMEM, true, true, hs.wo);
    launch(mix1_kernel, 128, 384, Mix1Cfg::SMEM, true, true, hs.mix1);
    launch(res_gemm_kernel<true>, 128, 384, ResCfg<true>::SMEM, true, true, hs.mix2);
}
```
